```python
import torch

def _softmax(x, axis=-1):
    return torch.softmax(x, dim=axis)
def _gelu(x):
    return torch.nn.functional.gelu(x, approximate="tanh")
def _silu(x):
    return torch.nn.functional.silu(x)
def _sigmoid(x):
    return torch.sigmoid(x)
def _layernorm(x, axis=-1, eps=1e-5):
    m = x.mean(dim=axis, keepdim=True)
    v = x.var(dim=axis, keepdim=True, unbiased=False)
    return (x - m) / torch.sqrt(v + eps)
def _scatter_add(tgt, idx, src, axis=0):
    return tgt.clone().index_add_(axis, idx, src)
def _segment_sum(src, seg, n):
    out = torch.zeros((n,) + src.shape[1:], dtype=src.dtype)
    return out.index_add_(0, seg, src)
def _pad(x, pw):
    flat = tuple(v for pair in reversed(pw) for v in pair)
    return torch.nn.functional.pad(x, flat)

kernel_name = 'recurrent_scan__ssm_conv_h3__mixer_token_mlp__prompt'

def setup_inputs():

    _w = (lambda a: (lambda t: t.to(torch.bfloat16) if t.is_floating_point() else t)(torch.as_tensor(a)))
    def _A_setup():
        B, S, D = 1, 2048, 576
        ks = 4
        return {
            "q": _w((lambda *s: torch.randn(*s, dtype=torch.bfloat16) * 0.05)(B, S, D)),
            "k": _w((lambda *s: torch.randn(*s, dtype=torch.bfloat16) * 0.8)(B, S, D)),
            "v": _w((lambda *s: torch.randn(*s, dtype=torch.bfloat16) * 0.8)(B, S, D)),
            "shift_k": _w((lambda *s: torch.randn(*s, dtype=torch.bfloat16) * 0.8)(D, ks) * 0.5),
            "ssm_k": _w((lambda *s: torch.randn(*s, dtype=torch.bfloat16) * 0.8)(D, S) * (1.0 / S ** 0.5)),
            "ssm_D": _w((lambda *s: torch.randn(*s, dtype=torch.bfloat16) * 0.8)(D)),
        }
    _A_in = _A_setup()

    def _B_setup():
        B, S, D, F = 1, 2048, 576, 4608
        return {
            "x": _w((lambda *s: torch.randn(*s, dtype=torch.bfloat16) * 0.05)(B, S, D)),
            "w1": _w((lambda *s: torch.randn(*s, dtype=torch.bfloat16) * 0.8)(S, F) * (S ** -0.5)),
            "b1": _w((lambda *s: torch.randn(*s, dtype=torch.bfloat16) * 12.8)(F) * 0.02),
            "w2": _w((lambda *s: torch.randn(*s, dtype=torch.bfloat16) * 0.2)(F, S) * (F ** -0.5)),
            "b2": _w((lambda *s: torch.randn(*s, dtype=torch.bfloat16) * 3.2)(S) * 0.02),
        }
    _B_in = _B_setup()

    return {
        "A_q": _A_in["q"],
        "A_k": _A_in["k"],
        "A_v": _A_in["v"],
        "A_shift_k": _A_in["shift_k"],
        "A_ssm_k": _A_in["ssm_k"],
        "A_ssm_D": _A_in["ssm_D"],
        "B_x": _B_in["x"],
        "B_w1": _B_in["w1"],
        "B_b1": _B_in["b1"],
        "B_w2": _B_in["w2"],
        "B_b2": _B_in["b2"],
    }

def reference(A_q, A_k, A_v, A_shift_k, A_ssm_k, A_ssm_D, B_x, B_w1, B_b1, B_w2, B_b2):
    def _A_ref(q, k, v, shift_k, ssm_k, ssm_D):
        B, S, D = q.shape
        ks = shift_k.shape[-1]
        k_pad = _pad(k, ((0, 0), (ks - 1, 0), (0, 0)))
        k_shift = torch.zeros_like(k)
        for t in range(ks):
            k_shift = k_shift + k_pad[:, t:t + S, :] * shift_k[:, ks - 1 - t][None, None, :]
        kv = k_shift * v
        L = 2 * S
        kv_pad = _pad(kv, ((0, 0), (0, S), (0, 0)))
        kf_pad = _pad(ssm_k, ((0, 0), (0, S)))
        kv_f = (lambda x, axes=(-2,-1): torch.fft.rfft2(x.float(), dim=axes))(kv_pad[:, None, :, :], axes=(1, 2))
        kf_f = (lambda x, axes=(-2,-1): torch.fft.rfft2(x.float(), dim=axes))(kf_pad[:, None, :], axes=(1, 2))
        kf_f = (lambda x, *d: x.permute(*d))(kf_f, 1, 2, 0)
        y_f = kv_f * kf_f[None, :, :, :]
        y = (lambda x, s, axes=(-2,-1): torch.fft.irfft2(x, s=s, dim=axes).to(torch.bfloat16))(y_f, (1, L), axes=(1, 2))[:, 0, :S, :]
        y = y + kv * ssm_D[None, None, :]
        return q * y

    def _B_ref(x, w1, b1, w2, b2):
        B, S, D = x.shape
        h = _layernorm(x, axis=-1)
        u = torch.einsum("bsd,sf->bdf", h, w1) + b1
        u = _gelu(u)
        y = torch.einsum("bdf,fs->bds", u, w2) + b2
        return (lambda x, *d: x.permute(*d))(y, 0, 2, 1)

    x = A_q
    xn = _layernorm(x, axis=-1)
    s = _A_ref(xn, A_k, A_v, A_shift_k, A_ssm_k, A_ssm_D)
    g = _silu(_B_ref(xn, B_w1, B_b1, B_w2, B_b2))
    return x + s * g
```

```cpp
#include <cuda_runtime.h>
#include <cuda_bf16.h>
#include <cuda.h>
#include <stdint.h>

namespace {

constexpr int S_ = 2048, D_ = 576, F_ = 4608;
constexpr int NCTA = 132, NG2 = 128, NCONV = 6;
constexpr int ST = 5, ASZ = 16384, PITCH_S = ASZ + 144 * 128, PITCH_B = ASZ + 192 * 128;
constexpr int KVIN = (36 + 33) * 128, KVW = 2 * KVIN + 64 * 176;
constexpr int BAR_OFF = ST * PITCH_S + 2 * KVW;
constexpr int SMEM_BYTES = BAR_OFF + 512;
constexpr int QLATE = 20, QDELAY = 400, QRAMP = 5, ATIME = 1500, ADT = 300;
constexpr int SPEC_T0 = 3600, SPEC_DT = 400;
constexpr int KVROWS = 32, KVGAP = 300, KVSTAG = 1200;
constexpr int KVGO = 6;
constexpr int SKEW = 1;
constexpr int LEAD_S = 3, LEAD_B = 2;
constexpr int GATE_NAP = 50;
constexpr int LAG = 4;
constexpr int CBUF = 14464, CH_OFF = 128, CT_OFF = 4224, KVT = 10240;
constexpr int CSTG_OFF = ST * PITCH_S + 3 * CBUF;
constexpr uint32_t SPIN_LIMIT = 1u << 22;

__device__ __align__(1024) uint8_t g_h[32 * 72 * 1024];
__device__ __align__(1024) uint8_t g_u[72 * D_ * 128];
__device__ __align__(1024) uint8_t g_kv[D_ * KVT];
__device__ __align__(1024) __nv_bfloat16 g_z[D_ * S_];
__device__ uint4 g_stats[S_];
constexpr int FL_H = 0, FL_U = 32, FL_KV = 38, FL_Z = 41, FL_GATE = 42, FL_N = 43;
__device__ __align__(128) uint32_t g_flags[FL_N * 32];
__device__ unsigned g_done;
struct RoleMap { uint32_t role[NCTA / 2]; };
#define PROF(i) do {} while (0)
#define PROFG(i) do {} while (0)

template<int TB> __device__ __forceinline__ void wgmma_ss(float (&d)[96], uint64_t da, uint64_t db, int sd) {
  asm volatile("{\n.reg .pred p;\nsetp.ne.b32 p, %98, 0;\n"
    "wgmma.mma_async.sync.aligned.m64n192k16.f32.bf16.bf16 {%0, %1, %2, %3, %4, %5, %6, %7, %8, %9, %10, %11, %12, %13, %14, %15, %16, %17, %18, %19, %20, %21, %22, %23, %24, %25, %26, %27, %28, %29, %30, %31, %32, %33, %34, %35, %36, %37, %38, %39, %40, %41, %42, %43, %44, %45, %46, %47, %48, %49, %50, %51, %52, %53, %54, %55, %56, %57, %58, %59, %60, %61, %62, %63, %64, %65, %66, %67, %68, %69, %70, %71, %72, %73, %74, %75, %76, %77, %78, %79, %80, %81, %82, %83, %84, %85, %86, %87, %88, %89, %90, %91, %92, %93, %94, %95}, %96, %97, p, 1, 1, 1, %99;\n}\n"
    : "+f"(d[0]), "+f"(d[1]), "+f"(d[2]), "+f"(d[3]), "+f"(d[4]), "+f"(d[5]), "+f"(d[6]), "+f"(d[7]), "+f"(d[8]), "+f"(d[9]), "+f"(d[10]), "+f"(d[11]), "+f"(d[12]), "+f"(d[13]), "+f"(d[14]), "+f"(d[15]), "+f"(d[16]), "+f"(d[17]), "+f"(d[18]), "+f"(d[19]), "+f"(d[20]), "+f"(d[21]), "+f"(d[22]), "+f"(d[23]), "+f"(d[24]), "+f"(d[25]), "+f"(d[26]), "+f"(d[27]), "+f"(d[28]), "+f"(d[29]), "+f"(d[30]), "+f"(d[31]), "+f"(d[32]), "+f"(d[33]), "+f"(d[34]), "+f"(d[35]), "+f"(d[36]), "+f"(d[37]), "+f"(d[38]), "+f"(d[39]), "+f"(d[40]), "+f"(d[41]), "+f"(d[42]), "+f"(d[43]), "+f"(d[44]), "+f"(d[45]), "+f"(d[46]), "+f"(d[47]), "+f"(d[48]), "+f"(d[49]), "+f"(d[50]), "+f"(d[51]), "+f"(d[52]), "+f"(d[53]), "+f"(d[54]), "+f"(d[55]), "+f"(d[56]), "+f"(d[57]), "+f"(d[58]), "+f"(d[59]), "+f"(d[60]), "+f"(d[61]), "+f"(d[62]), "+f"(d[63]), "+f"(d[64]), "+f"(d[65]), "+f"(d[66]), "+f"(d[67]), "+f"(d[68]), "+f"(d[69]), "+f"(d[70]), "+f"(d[71]), "+f"(d[72]), "+f"(d[73]), "+f"(d[74]), "+f"(d[75]), "+f"(d[76]), "+f"(d[77]), "+f"(d[78]), "+f"(d[79]), "+f"(d[80]), "+f"(d[81]), "+f"(d[82]), "+f"(d[83]), "+f"(d[84]), "+f"(d[85]), "+f"(d[86]), "+f"(d[87]), "+f"(d[88]), "+f"(d[89]), "+f"(d[90]), "+f"(d[91]), "+f"(d[92]), "+f"(d[93]), "+f"(d[94]), "+f"(d[95])
    : "l"(da), "l"(db), "r"(sd), "n"(TB));
}
template<int TB> __device__ __forceinline__ void wgmma_ss(float (&d)[72], uint64_t da, uint64_t db, int sd) {
  asm volatile("{\n.reg .pred p;\nsetp.ne.b32 p, %74, 0;\n"
    "wgmma.mma_async.sync.aligned.m64n144k16.f32.bf16.bf16 {%0, %1, %2, %3, %4, %5, %6, %7, %8, %9, %10, %11, %12, %13, %14, %15, %16, %17, %18, %19, %20, %21, %22, %23, %24, %25, %26, %27, %28, %29, %30, %31, %32, %33, %34, %35, %36, %37, %38, %39, %40, %41, %42, %43, %44, %45, %46, %47, %48, %49, %50, %51, %52, %53, %54, %55, %56, %57, %58, %59, %60, %61, %62, %63, %64, %65, %66, %67, %68, %69, %70, %71}, %72, %73, p, 1, 1, 1, %75;\n}\n"
    : "+f"(d[0]), "+f"(d[1]), "+f"(d[2]), "+f"(d[3]), "+f"(d[4]), "+f"(d[5]), "+f"(d[6]), "+f"(d[7]), "+f"(d[8]), "+f"(d[9]), "+f"(d[10]), "+f"(d[11]), "+f"(d[12]), "+f"(d[13]), "+f"(d[14]), "+f"(d[15]), "+f"(d[16]), "+f"(d[17]), "+f"(d[18]), "+f"(d[19]), "+f"(d[20]), "+f"(d[21]), "+f"(d[22]), "+f"(d[23]), "+f"(d[24]), "+f"(d[25]), "+f"(d[26]), "+f"(d[27]), "+f"(d[28]), "+f"(d[29]), "+f"(d[30]), "+f"(d[31]), "+f"(d[32]), "+f"(d[33]), "+f"(d[34]), "+f"(d[35]), "+f"(d[36]), "+f"(d[37]), "+f"(d[38]), "+f"(d[39]), "+f"(d[40]), "+f"(d[41]), "+f"(d[42]), "+f"(d[43]), "+f"(d[44]), "+f"(d[45]), "+f"(d[46]), "+f"(d[47]), "+f"(d[48]), "+f"(d[49]), "+f"(d[50]), "+f"(d[51]), "+f"(d[52]), "+f"(d[53]), "+f"(d[54]), "+f"(d[55]), "+f"(d[56]), "+f"(d[57]), "+f"(d[58]), "+f"(d[59]), "+f"(d[60]), "+f"(d[61]), "+f"(d[62]), "+f"(d[63]), "+f"(d[64]), "+f"(d[65]), "+f"(d[66]), "+f"(d[67]), "+f"(d[68]), "+f"(d[69]), "+f"(d[70]), "+f"(d[71])
    : "l"(da), "l"(db), "r"(sd), "n"(TB));
}
template<int TB> __device__ __forceinline__ void wgmma_acc(float (&d)[36], uint64_t da, uint64_t db) {
  asm volatile("wgmma.mma_async.sync.aligned.m64n72k16.f32.bf16.bf16 {%0, %1, %2, %3, %4, %5, %6, %7, %8, %9, %10, %11, %12, %13, %14, %15, %16, %17, %18, %19, %20, %21, %22, %23, %24, %25, %26, %27, %28, %29, %30, %31, %32, %33, %34, %35}, %36, %37, 1, 1, 1, 1, %38;\n"
    : "+f"(d[0]), "+f"(d[1]), "+f"(d[2]), "+f"(d[3]), "+f"(d[4]), "+f"(d[5]), "+f"(d[6]), "+f"(d[7]), "+f"(d[8]), "+f"(d[9]), "+f"(d[10]), "+f"(d[11]), "+f"(d[12]), "+f"(d[13]), "+f"(d[14]), "+f"(d[15]), "+f"(d[16]), "+f"(d[17]), "+f"(d[18]), "+f"(d[19]), "+f"(d[20]), "+f"(d[21]), "+f"(d[22]), "+f"(d[23]), "+f"(d[24]), "+f"(d[25]), "+f"(d[26]), "+f"(d[27]), "+f"(d[28]), "+f"(d[29]), "+f"(d[30]), "+f"(d[31]), "+f"(d[32]), "+f"(d[33]), "+f"(d[34]), "+f"(d[35])
    : "l"(da), "l"(db), "n"(TB));
}
__device__ __forceinline__ void wgmma_rs_n32(float (&d)[16], uint32_t a0, uint32_t a1, uint32_t a2, uint32_t a3, uint64_t db, int sd) {
  asm volatile("{\n.reg .pred p;\nsetp.ne.b32 p, %21, 0;\n"
    "wgmma.mma_async.sync.aligned.m64n32k16.f32.bf16.bf16 {%0, %1, %2, %3, %4, %5, %6, %7, %8, %9, %10, %11, %12, %13, %14, %15}, {%16, %17, %18, %19}, %20, p, 1, 1, 0;\n}\n"
    : "+f"(d[0]), "+f"(d[1]), "+f"(d[2]), "+f"(d[3]), "+f"(d[4]), "+f"(d[5]), "+f"(d[6]), "+f"(d[7]), "+f"(d[8]), "+f"(d[9]), "+f"(d[10]), "+f"(d[11]), "+f"(d[12]), "+f"(d[13]), "+f"(d[14]), "+f"(d[15])
    : "r"(a0), "r"(a1), "r"(a2), "r"(a3), "l"(db), "r"(sd));
}

__device__ __forceinline__ void wg_fence() { asm volatile("wgmma.fence.sync.aligned;" ::: "memory"); }
__device__ __forceinline__ void wg_commit() { asm volatile("wgmma.commit_group.sync.aligned;" ::: "memory"); }
template <int n> __device__ __forceinline__ void wg_wait() { asm volatile("wgmma.wait_group.sync.aligned %0;" ::"n"(n) : "memory"); }
__device__ __forceinline__ uint64_t mkdesc(uint32_t addr, uint32_t lbo, uint32_t sbo, uint32_t sw) {
  return (uint64_t)((addr & 0x3FFFF) >> 4) | ((uint64_t)(lbo >> 4) << 16) | ((uint64_t)(sbo >> 4) << 32) | ((uint64_t)sw << 62);
}
__device__ __forceinline__ void mbar_init(uint32_t a, int c) { asm volatile("mbarrier.init.shared::cta.b64 [%0], %1;" ::"r"(a), "r"(c)); }
__device__ __forceinline__ void mbar_expect(uint32_t a, uint32_t b) { asm volatile("mbarrier.arrive.expect_tx.shared::cta.b64 _, [%0], %1;" ::"r"(a), "r"(b) : "memory"); }
__device__ __forceinline__ void mbar_arrive(uint32_t a) { asm volatile("mbarrier.arrive.shared::cta.b64 _, [%0];" ::"r"(a) : "memory"); }
__device__ __forceinline__ void mbar_arrive_cluster(uint32_t raddr) { asm volatile("mbarrier.arrive.shared::cluster.b64 _, [%0];" ::"r"(raddr) : "memory"); }
__device__ __forceinline__ uint32_t mapa(uint32_t a, uint32_t cta) { uint32_t r; asm("mapa.shared::cluster.u32 %0, %1, %2;" : "=r"(r) : "r"(a), "r"(cta)); return r; }
__device__ __forceinline__ void mbar_wait(uint32_t a, uint32_t ph) {
  asm volatile(
      "{\n.reg .pred p;\n.reg .u32 c;\nmov.u32 c, 0;\n"
      "WAIT_LOOP:\nmbarrier.try_wait.parity.shared::cta.b64 p, [%0], %1;\n@p bra WAIT_DONE;\n"
      "add.u32 c, c, 1;\nsetp.lt.u32 p, c, %2;\n@p bra WAIT_LOOP;\ntrap;\nWAIT_DONE:\n}" ::"r"(a), "r"(ph), "n"(SPIN_LIMIT) : "memory");
}
__device__ __forceinline__ void tma2d(uint32_t dst, const CUtensorMap* m, int c0, int c1, uint32_t bar) {
  asm volatile("cp.async.bulk.tensor.2d.shared::cluster.global.mbarrier::complete_tx::bytes [%0], [%1, {%3, %4}], [%2];" ::"r"(dst), "l"(m), "r"(bar), "r"(c0), "r"(c1) : "memory");
}
__device__ __forceinline__ void bulk_g2s(uint32_t dst, const void* src, uint32_t sz, uint32_t bar) {
  asm volatile("cp.async.bulk.shared::cluster.global.mbarrier::complete_tx::bytes [%0], [%1], %2, [%3];" ::"r"(dst), "l"(src), "r"(sz), "r"(bar) : "memory");
}
__device__ __forceinline__ void bulk_s2g(void* dst, uint32_t src, uint32_t sz) {
  asm volatile("cp.async.bulk.global.shared::cta.bulk_group [%0], [%1], %2;" ::"l"(dst), "r"(src), "r"(sz) : "memory");
}
__device__ __forceinline__ uint64_t stream_policy() {
  uint64_t p;
  asm volatile("createpolicy.fractional.L2::evict_first.b64 %0, 1.0;" : "=l"(p));
  return p;
}
__device__ __forceinline__ void tma_weights(uint32_t dst, const CUtensorMap* m, int k0, int mchunk, uint32_t bar, uint64_t pol) {
  asm volatile("cp.async.bulk.tensor.3d.shared::cluster.global.mbarrier::complete_tx::bytes.L2::cache_hint [%0], [%1, {%6, %3, %4}], [%2], %5;"
               ::"r"(dst), "l"(m), "r"(bar), "r"(k0), "r"(mchunk), "l"(pol), "r"(0) : "memory");
}
__device__ __forceinline__ bool elect_one() {
  uint32_t p;
  asm volatile("{\n.reg .pred P;\nelect.sync _|P, 0xffffffff;\nselp.u32 %0, 1, 0, P;\n}" : "=r"(p));
  return p;
}
__device__ __forceinline__ void bulk_g2s_stream(uint32_t dst, const void* src, uint32_t sz, uint32_t bar, uint64_t pol) {
  asm volatile("cp.async.bulk.shared::cluster.global.mbarrier::complete_tx::bytes.L2::cache_hint [%0], [%1], %2, [%3], %4;"
               ::"r"(dst), "l"(src), "r"(sz), "r"(bar), "l"(pol) : "memory");
}
__device__ __forceinline__ void tma3d_store(const CUtensorMap* m, int c1, int c2, uint32_t src) {
  asm volatile("cp.async.bulk.tensor.3d.global.shared::cta.bulk_group [%0, {%4, %2, %3}], [%1];" ::"l"(m), "r"(src), "r"(c1), "r"(c2), "r"(0) : "memory");
}
__device__ __forceinline__ void tma2d_stream(uint32_t dst, const CUtensorMap* m, int c0, int c1, uint32_t bar, uint64_t pol) {
  asm volatile("cp.async.bulk.tensor.2d.shared::cluster.global.mbarrier::complete_tx::bytes.L2::cache_hint [%0], [%1, {%3, %4}], [%2], %5;"
               ::"r"(dst), "l"(m), "r"(bar), "r"(c0), "r"(c1), "l"(pol) : "memory");
}
__device__ __forceinline__ void tma4d_store(const CUtensorMap* m, int c1, int c2, int c3, uint32_t src) {
  asm volatile("cp.async.bulk.tensor.4d.global.shared::cta.bulk_group [%0, {%5, %2, %3, %4}], [%1];" ::"l"(m), "r"(src), "r"(c1), "r"(c2), "r"(c3), "r"(0) : "memory");
}
__device__ __forceinline__ void bulk_commit() { asm volatile("cp.async.bulk.commit_group;" ::: "memory"); }
__device__ __forceinline__ void bulk_wait_all() { asm volatile("cp.async.bulk.wait_group 0;" ::: "memory"); }
__device__ __forceinline__ void fence_async_smem() { asm volatile("fence.proxy.async.shared::cta;" ::: "memory"); }
__device__ __forceinline__ void fence_async_global() { asm volatile("fence.proxy.async.global;" ::: "memory"); }
__device__ __forceinline__ void named_bar(int id, int n) { asm volatile("bar.sync %0, %1;" ::"r"(id), "r"(n) : "memory"); }
__device__ __forceinline__ void named_arrive(int id, int n) { asm volatile("bar.arrive %0, %1;" ::"r"(id), "r"(n) : "memory"); }
__device__ __forceinline__ void flag_add(int i, uint32_t v) { asm volatile("red.relaxed.gpu.global.add.u32 [%0], %1;" ::"l"(g_flags + i * 32), "r"(v) : "memory"); }
__device__ __forceinline__ uint32_t flag_ld(int i) { uint32_t v; asm volatile("ld.relaxed.gpu.global.u32 %0, [%1];" : "=r"(v) : "l"(g_flags + i * 32) : "memory"); return v; }
__device__ __forceinline__ void prefetch_map(const CUtensorMap* m) { asm volatile("prefetch.tensormap [%0];" ::"l"(m) : "memory"); }
__device__ __forceinline__ void stsm4_t(uint32_t a, uint32_t r0, uint32_t r1, uint32_t r2, uint32_t r3) {
  asm volatile("stmatrix.sync.aligned.m8n8.x4.trans.shared.b16 [%0], {%1, %2, %3, %4};" ::"r"(a), "r"(r0), "r"(r1), "r"(r2), "r"(r3) : "memory");
}
__device__ __forceinline__ uint32_t lds32(uint32_t a) { uint32_t v; asm volatile("ld.shared.u32 %0, [%1];" : "=r"(v) : "r"(a) : "memory"); return v; }
__device__ __forceinline__ void sts32(uint32_t a, uint32_t v) { asm volatile("st.shared.u32 [%0], %1;" ::"r"(a), "r"(v) : "memory"); }
__device__ __forceinline__ uint4 ld_l2(const uint4* p) { uint4 v; asm volatile("ld.relaxed.gpu.global.v4.u32 {%0, %1, %2, %3}, [%4];" : "=r"(v.x), "=r"(v.y), "=r"(v.z), "=r"(v.w) : "l"(p) : "memory"); return v; }
__device__ __forceinline__ void sts128(uint32_t a, uint32_t x, uint32_t y, uint32_t z, uint32_t w) { asm volatile("st.shared.v4.u32 [%0], {%1, %2, %3, %4};" ::"r"(a), "r"(x), "r"(y), "r"(z), "r"(w) : "memory"); }
__device__ __forceinline__ uint4 lds128(uint32_t a) { uint4 v; asm volatile("ld.shared.v4.u32 {%0, %1, %2, %3}, [%4];" : "=r"(v.x), "=r"(v.y), "=r"(v.z), "=r"(v.w) : "r"(a) : "memory"); return v; }
__device__ __forceinline__ void st_async4(uint32_t raddr, uint32_t a, uint32_t b, uint32_t c, uint32_t d, uint32_t rbar) {
  asm volatile("st.async.weak.shared::cluster.mbarrier::complete_tx::bytes.v4.b32 [%0], {%1, %2, %3, %4}, [%5];" ::"r"(raddr), "r"(a), "r"(b), "r"(c), "r"(d), "r"(rbar) : "memory");
}
__device__ __forceinline__ uint32_t pack_bf16(float lo, float hi) { uint32_t r; asm("cvt.rn.bf16x2.f32 %0, %1, %2;" : "=r"(r) : "f"(hi), "f"(lo)); return r; }
__device__ __forceinline__ float bf_lo(uint32_t v) { return __uint_as_float(v << 16); }
__device__ __forceinline__ float bf_hi(uint32_t v) { return __uint_as_float(v & 0xffff0000u); }
__device__ __forceinline__ float bf_round(float x) { return bf_lo(pack_bf16(x, 0.f)); }
__device__ __forceinline__ uint32_t hmul2(uint32_t a, uint32_t b) { uint32_t r; asm("mul.rn.bf16x2 %0, %1, %2;" : "=r"(r) : "r"(a), "r"(b)); return r; }
__device__ __forceinline__ uint32_t hsub2(uint32_t a, uint32_t b) { uint32_t r; asm("sub.rn.bf16x2 %0, %1, %2;" : "=r"(r) : "r"(a), "r"(b)); return r; }
__device__ __forceinline__ uint32_t hfma2(uint32_t a, uint32_t b, uint32_t c) { uint32_t r; asm("fma.rn.bf16x2 %0, %1, %2, %3;" : "=r"(r) : "r"(a), "r"(b), "r"(c)); return r; }
__device__ __forceinline__ uint4 ldg128(const void* p) { uint4 v; asm volatile("ld.global.nc.v4.u32 {%0, %1, %2, %3}, [%4];" : "=r"(v.x), "=r"(v.y), "=r"(v.z), "=r"(v.w) : "l"(p)); return v; }
__device__ __forceinline__ uint32_t ldg16(const void* p) { uint32_t v; asm volatile("ld.global.nc.u16 %0, [%1];" : "=r"(v) : "l"(p)); return v; }
__device__ __forceinline__ float tanh_ordered(float x) { float y; asm volatile("tanh.approx.f32 %0, %1;" : "=f"(y) : "f"(x)); return y; }
__device__ __forceinline__ void mma16816(float (&d)[4], uint32_t a0, uint32_t a1, uint32_t a2, uint32_t a3, uint32_t b0, uint32_t b1) {
  asm("mma.sync.aligned.m16n8k16.row.col.f32.bf16.bf16.f32 {%0, %1, %2, %3}, {%4, %5, %6, %7}, {%8, %9}, {%0, %1, %2, %3};"
      : "+f"(d[0]), "+f"(d[1]), "+f"(d[2]), "+f"(d[3]) : "r"(a0), "r"(a1), "r"(a2), "r"(a3), "r"(b0), "r"(b1));
}
__device__ __forceinline__ uint32_t hadd2(uint32_t a, uint32_t b) { uint32_t r; asm("add.rn.bf16x2 %0, %1, %2;" : "=r"(r) : "r"(a), "r"(b)); return r; }
__device__ __forceinline__ uint32_t ldg32(const void* p) { uint32_t v; asm volatile("ld.global.nc.L1::no_allocate.u32 %0, [%1];" : "=r"(v) : "l"(p)); return v; }
__device__ __forceinline__ uint2 lds64(uint32_t a) { uint2 v; asm volatile("ld.shared.v2.u32 {%0, %1}, [%2];" : "=r"(v.x), "=r"(v.y) : "r"(a) : "memory"); return v; }
__device__ __forceinline__ uint32_t lds32_if(uint32_t a, uint32_t on) {
  uint32_t v;
  asm volatile("{\n.reg .pred p;\nsetp.ne.u32 p, %2, 0;\n@p ld.shared.u32 %0, [%1];\n}" : "=r"(v) : "r"(a), "r"(on) : "memory");
  return v;
}
__device__ __forceinline__ uint32_t clock_now() { uint32_t t; asm volatile("mov.u32 %0, %%clock;" : "=r"(t)); return t; }
__device__ __forceinline__ void spin_until(uint32_t t0, uint32_t n) { while (clock_now() - t0 < n) {} }
__device__ __forceinline__ uint2 ldg64_if(const void* p, uint32_t on) {
  uint2 v;
  asm volatile("{\n.reg .pred p;\nsetp.ne.u32 p, %3, 0;\n@p ld.global.nc.v2.u32 {%0, %1}, [%2];\n}" : "=r"(v.x), "=r"(v.y) : "l"(p), "r"(on));
  return v;
}
template <class T> __device__ __forceinline__ T pin(T v) { asm volatile("" : "+r"(v)); return v; }
__device__ __forceinline__ void st_async2(uint32_t raddr, uint32_t a, uint32_t b, uint32_t rbar) {
  asm volatile("st.async.weak.shared::cluster.mbarrier::complete_tx::bytes.v2.b32 [%0], {%1, %2}, [%3];" ::"r"(raddr), "r"(a), "r"(b), "r"(rbar) : "memory");
}
__device__ __forceinline__ void bulk_prefetch(const void* src, uint32_t sz, uint64_t pol) {
  asm volatile("cp.async.bulk.prefetch.L2.global.L2::cache_hint [%0], %1, %2;" ::"l"(src), "r"(sz), "l"(pol) : "memory");
}
__device__ __forceinline__ void bulk_wait_read() { asm volatile("cp.async.bulk.wait_group.read 0;" ::: "memory"); }
__device__ __forceinline__ uint32_t shfl_ordered(uint32_t v, int src) { uint32_t r; asm volatile("shfl.sync.idx.b32 %0, %1, %2, 0x1f, 0xffffffff;" : "=r"(r) : "r"(v), "r"(src)); return r; }
__device__ __forceinline__ int chan_pos(int d) {
  return d < 512 ? 72 * (d >> 6) + ((d & 33) | ((d & 6) << 2) | ((d >> 2) & 6)) : 72 * ((d - 512) >> 3) + 64 + (d & 7);
}

struct Ring {
  uint32_t s, ph;
  __device__ __forceinline__ void next() { if (++s == ST) { s = 0; ph ^= 1; } }
};
constexpr int B_FULL = 0, B_GO = 40, B_CFULL = 48, B_SEMPTY = 80, B_ZFULL = 96, B_RFULL = 104, B_UDONE = 120, B_KFULL = 136, B_RAW = 168,
              B_EMPTY = 248, B_KVGO = 288, B_G1DONE = 296,
              B_CEMPTY = 304, B_SFULL = 336, B_USTG = 352, B_END = 368;

__device__ __forceinline__ void poll_once(uint32_t& ready, int idx, uint32_t want, bool active) {
  bool ok = false;
  if (active) ok = flag_ld(idx) == want;
  const uint32_t seen = __ballot_sync(0xffffffffu, ok);
  if (seen & ~ready) fence_async_global();
  ready |= seen;
}
__device__ __forceinline__ void poll_bits(uint32_t& ready, uint32_t bits, int idx, uint32_t want, bool active) {
  for (uint32_t spins = 0; (ready & bits) != bits; spins++) {
    poll_once(ready, idx, want, active);
    if (spins > SPIN_LIMIT) asm volatile("trap;");
  }
}
__device__ __forceinline__ void wait_counter(int idx, uint32_t want, uint32_t first, uint32_t nap) {
#pragma unroll 1
  for (uint32_t spins = 0; first != want; spins++) {
    if (spins) __nanosleep(nap);
    first = flag_ld(idx);
    if (spins > SPIN_LIMIT) asm volatile("trap;");
  }
  fence_async_global();
}

__device__ __forceinline__ float ln_rinv(float var) {
  float rt, rinv;
  asm("sqrt.approx.ftz.f32 %0, %1;" : "=f"(rt) : "f"(bf_round(bf_round(var) + 1e-5f)));
  asm("rcp.approx.ftz.f32 %0, %1;" : "=f"(rinv) : "f"(bf_round(rt)));
  return rinv;
}
__device__ __forceinline__ uint32_t ln_apply(uint32_t x, const uint4& st) {
  const uint32_t d = hsub2(x, st.x);
  return hfma2(d, st.y, hmul2(d, st.z));
}

__device__ __forceinline__ void polling_done(int lane) {
  unsigned old = 0;
  if (lane == 0) asm volatile("atom.relaxed.gpu.global.add.u32 %0, [%1], 1;" : "=r"(old) : "l"(&g_done) : "memory");
  old = __shfl_sync(0xffffffffu, old, 0);
  if (old == NCTA + NG2 - 1) {
#pragma unroll 1
    for (int i = lane; i < FL_N; i += 32) g_flags[i * 32] = 0;
    if (lane == 0) g_done = 0;
  }
}

struct Pipe { Ring r; uint32_t prev; bool pending; };
template <int TB, int R>
__device__ __forceinline__ void gemm_run(float (&acc)[R], int n, int accumulate, Pipe& p, uint32_t sb, uint32_t pitch, int wg, bool leader) {
  const uint32_t bars = sb + BAR_OFF;
  const uint64_t dA0 = mkdesc(sb + wg * 8192, 8192, 1024, 1);
  const uint64_t dB0 = TB ? mkdesc(sb + ASZ, 128, 1024, 0) : mkdesc(sb + ASZ, 16, 1024, 1);
  constexpr int KB_STEP = TB ? 16 : 2;
#pragma unroll 1
  for (int kb = 0; kb < n; kb++) {
    mbar_wait(bars + B_FULL + p.r.s * 8, p.r.ph);
    if (kb == 0 && !accumulate && threadIdx.x == 0) PROF(21 + TB);
    if (TB && !accumulate && threadIdx.x == 0 && (kb & 3) == 0 && kb) PROF(55 + (kb >> 2));
    const uint64_t dA = dA0 + p.r.s * (pitch >> 4), dB = dB0 + p.r.s * (pitch >> 4);
    wg_fence();
    wgmma_ss<TB>(acc, dA, dB, accumulate | kb);
#pragma unroll
    for (int k = 1; k < 4; k++) wgmma_ss<TB>(acc, dA + k * 128, dB + k * KB_STEP, 1);
    wg_commit();
    wg_wait<1>();
    if (p.pending && leader) mbar_arrive(bars + B_EMPTY + p.prev * 8);
    p.pending = true;
    p.prev = p.r.s;
    p.r.next();
  }
}
__device__ __forceinline__ void pipe_drain(Pipe& p, uint32_t bars, bool leader) {
  wg_wait<0>();
  if (leader) mbar_arrive(bars + B_EMPTY + p.prev * 8);
  p.pending = false;
}

template <int BROW0, class Slice>
__device__ __forceinline__ void gemm2_part(float (&c)[36], Ring r, uint32_t sb, uint32_t pitch, int wg, Slice slice) {
  const uint64_t dA0 = mkdesc(sb + wg * 8192, 8192, 1024, 1), dB0 = mkdesc(sb + ASZ + BROW0 * 128, 16, 1024, 1);
#pragma unroll
  for (int i = 0; i < 4 * LAG; i++) {
    if ((i & 3) == 0 && BROW0 == 0) { mbar_wait(sb + BAR_OFF + B_FULL + r.s * 8, r.ph); wg_fence(); }
    wgmma_acc<0>(c, dA0 + r.s * (pitch >> 4) + (i & 3) * 128, dB0 + r.s * (pitch >> 4) + (i & 3) * 2);
    if ((i & 3) == 3) r.next();
    slice(i);
  }
  wg_commit();
}
__device__ __forceinline__ void split_acc(const float (&acc)[72], float (&a)[36], float (&b)[36]) {
#pragma unroll
  for (int i = 0; i < 36; i++) { asm volatile("mov.b32 %0, %1;" : "=f"(a[i]) : "f"(acc[i])); asm volatile("mov.b32 %0, %1;" : "=f"(b[i]) : "f"(acc[36 + i])); }
}
template <int R>
__device__ __forceinline__ void gelu_store(const float (&acc)[R], float hbias0, float hbias1, uint32_t sa) {
  uint32_t pk[4];
#pragma unroll
  for (int j = 0; j <= R / 4; j += 2) {
    float hx[8], t[8];
    if (j < R / 4) {
#pragma unroll
      for (int u = 0; u < 8; u++) {
        hx[u] = fmaf(acc[4 * j + u], 0.5f, (u & 2) ? hbias1 : hbias0);
        t[u] = tanh_ordered(hx[u] * fmaf(hx[u] * hx[u], 0.2854192651f, 1.5957691216f));
      }
    }
    if (j > 0) stsm4_t(sa + (j - 2) * 1024, pk[0], pk[1], pk[2], pk[3]);
    if (j < R / 4) {
#pragma unroll
      for (int u = 0; u < 4; u++) pk[u] = pack_bf16(fmaf(hx[2 * u], t[2 * u], hx[2 * u]), fmaf(hx[2 * u + 1], t[2 * u + 1], hx[2 * u + 1]));
    }
  }
  fence_async_smem();
  __syncwarp();
}
struct Role { int half, kind, g2_m, dt, g1_mt, g1_nt, cs; uint32_t pitch; };
__device__ __forceinline__ Role get_role(const RoleMap& roles) {
  uint32_t b;
  asm volatile("mov.u32 %0, %%ctaid.x;" : "=r"(b));
  const uint32_t w = roles.role[b >> 1];
  const int half = b & 1, kind = w & 3, m = (w >> 4) & 15, dt = (w >> 2) & 3;
  return Role{half, kind, m * 128, dt, half * 18 + (int)((w >> 8) & 31), (int)(w >> 16), (m * 4 + dt) * 2 + half, kind ? (uint32_t)PITCH_B : (uint32_t)PITCH_S};
}
__device__ __forceinline__ int g2_block(int half, int j) { return half * 36 + (j < 12 ? 2 * j : j < 24 ? 2 * j - 23 : j); }
__device__ __forceinline__ int conv_chan(int cs, int i) { return (3 * (cs >> 5) + (i >> 1)) * 64 + ((2 * cs) & 63) + (i & 1); }
__device__ __forceinline__ uint32_t conv_buf(uint32_t sb, int b) { return sb + (b == 3 ? (36 % ST) * PITCH_S : ST * PITCH_S + b * CBUF); }

template <int R, int LEAD>
__device__ __forceinline__ void gemm1(float (&acc)[R], Pipe& p, uint32_t sb, int wg, bool leader) {
  constexpr uint32_t pitch = ASZ + R * 256;
  gemm_run<1>(acc, 32 - LEAD, 0, p, sb, pitch, wg, leader);
  if (LEAD) {
    if (wg == 1) { pipe_drain(p, sb + BAR_OFF, leader); named_bar(8, 256); }
    gemm_run<1>(acc, LEAD, 1, p, sb, pitch, wg, leader);
    if (wg == 0) named_arrive(8, 256);
  }
}

__global__ void __cluster_dims__(2, 1, 1) __launch_bounds__(384, 1)
fused_kernel(const __grid_constant__ CUtensorMap tmW1, const __grid_constant__ CUtensorMap tmW2, const __grid_constant__ CUtensorMap tmZ,
             const __grid_constant__ CUtensorMap tmH, const __grid_constant__ CUtensorMap tmK, const __grid_constant__ CUtensorMap tmV,
             const __grid_constant__ CUtensorMap tmKV, const __grid_constant__ RoleMap roles, const __nv_bfloat16* __restrict__ q,
             const __nv_bfloat16* __restrict__ shiftk, const __nv_bfloat16* __restrict__ ssmk,
             const __nv_bfloat16* __restrict__ ssmD, const __nv_bfloat16* __restrict__ b1, const __nv_bfloat16* __restrict__ b2,
             __nv_bfloat16* __restrict__ out) {
  extern __shared__ __align__(1024) uint8_t smem_raw[];
  const uint32_t sb = (uint32_t)__cvta_generic_to_shared(smem_raw);
  const uint32_t bars = sb + BAR_OFF;
  const int cta = blockIdx.x;
  const int tid = threadIdx.x;
  const int warp = __shfl_sync(0xffffffffu, tid >> 5, 0);
  const int lane = tid & 31;
  const int wg = warp >> 2;
  if (tid == 288) PROFG(0);

  const uint32_t t_start = clock_now();
  const int lc = (cta + 120) & 127;
  const uint32_t do_ln = cta < 128 && warp < 8;
  const int ln_row = lc * 16 + (warp & 7) * 2 + (lane >> 4), l16 = lane & 15;
  uint2 xr[9];
  if (do_ln && lc >= QLATE) spin_until(t_start, QDELAY + QRAMP * lc);
#pragma unroll
  for (int i = 0; i < 9; i++) xr[i] = ldg64_if(q + (size_t)ln_row * D_ + i * 64 + l16 * 4, do_ln);
  constexpr int LN_OFF = ST * PITCH_B;
  uint32_t hs[9];
  {
    const int g0 = 4 * (l16 >> 3) + 2 * (l16 & 1), g8 = 9 * (l16 >> 1) + 8;
    const uint32_t hrow = sb + LN_OFF + ((ln_row >> 3) & 1) * 9216;
#pragma unroll
    for (int i = 0; i < 8; i++) hs[i] = hrow + g0 * 128 + ((((g0 + i) ^ ln_row) & 7) << 4) + ((l16 >> 1) & 3) * 4;
    hs[8] = hrow + g8 * 128 + (((g8 ^ ln_row) & 7) << 4) + (l16 & 1) * 8;
#pragma unroll
    for (int i = 0; i < 9; i++) hs[i] = shfl_ordered(hs[i], lane);
  }
  if (warp == 8 && elect_one()) {
#pragma unroll
    for (int o = 0; o < B_END; o += 8) mbar_init(bars + o, o < B_EMPTY ? 1 : o < B_CEMPTY ? 2 : 4);
    asm volatile("fence.mbarrier_init.release.cluster;" ::: "memory");
    prefetch_map(&tmW1);
    prefetch_map(&tmH);
    prefetch_map(&tmW2);
  }
  __syncwarp();
  asm volatile("barrier.cluster.arrive.relaxed.aligned;" ::: "memory");

  if (warp != 8) {
    const int hq = (lane & 16) >> 3, hb = (lane & 16) + hq;
    float da[3][4] = {};
#pragma unroll
    for (int i = 0; i < 9; i++) mma16816(da[i % 3], xr[i].x, 0x3f803f80u, xr[i].y, 0x3f803f80u, xr[i].x, xr[i].y);
    const float r1 = ((da[0][2] + da[0][3]) + (da[1][2] + da[1][3])) + (da[2][2] + da[2][3]);
    const float r2 = (lane & 4) ? (da[0][1] + da[1][1]) + da[2][1] : (da[0][0] + da[1][0]) + da[2][0];
    const float s1 = __shfl_sync(0xffffffffu, r1, hq) + __shfl_sync(0xffffffffu, r1, hq + 1);
    const float s2 = (__shfl_sync(0xffffffffu, r2, hb) + __shfl_sync(0xffffffffu, r2, hb + 4)) + (__shfl_sync(0xffffffffu, r2, hb + 9) + __shfl_sync(0xffffffffu, r2, hb + 13));
    if (tid == 0) { asm volatile("" ::"f"(s2) : "memory"); PROF(27); }
    const float mean = s1 * (1.f / D_), var = fmaxf(fmaf(-mean, mean, s2 * (1.f / D_)), 0.f);
    const float rinv = ln_rinv(var), rinv2 = ln_rinv(var * rinv * rinv), scale = rinv * rinv2, shift = -bf_round((mean - bf_round(mean)) * rinv) * rinv2;
    const uint32_t m2 = pack_bf16(mean, mean), hi2 = pack_bf16(scale, scale), lo2 = pack_bf16(scale - bf_lo(hi2), scale - bf_lo(hi2)), sh2 = pack_bf16(shift, shift);
    uint32_t w[18];
#pragma unroll
    for (int i = 0; i < 18; i++) {
      const uint32_t d = hsub2((i & 1) ? xr[i >> 1].y : xr[i >> 1].x, m2);
      asm("max.u32 %0, %1, 1;" : "=r"(w[i]) : "r"(hfma2(d, hi2, hfma2(d, lo2, sh2))));
    }
#pragma unroll
    for (int i = 0; i < 16; i++) {
      const int gi = 9 * (i >> 1) + (i & 1);
      asm volatile("{\n.reg .pred p;\nsetp.ne.u32 p, %2, 0;\n@p st.shared.u32 [%0], %1;\n}" ::"r"(hs[gi & 7] + gi * 128), "r"(w[i]), "r"(do_ln) : "memory");
    }
    asm volatile("{\n.reg .pred p;\nsetp.ne.u32 p, %3, 0;\n@p st.shared.v2.u32 [%0], {%1, %2};\n}" ::"r"(hs[8]), "r"(w[16]), "r"(w[17]), "r"(do_ln) : "memory");
    if (tid == 0) PROF(13);
    const uint32_t hi1 = pack_bf16(rinv, rinv);
    if (do_ln && l16 == 0) sts128(sb + LN_OFF + 18432 + (ln_row & 15) * 16, m2, hi1, pack_bf16(rinv - bf_lo(hi1), rinv - bf_lo(hi1)), 0u);
    fence_async_smem();
  }
  if (warp == 8) { named_arrive(0, 320); named_arrive(5, 96); }
  else if (warp == 9 || warp == 10) named_bar(5, 96);
  else named_bar(0, 320);
  if (cta < 128 && warp == 11) {
    if (elect_one()) {
      tma3d_store(&tmH, (lc >> 2) * 72, (lc & 3) * 2, sb + LN_OFF);
      bulk_s2g(g_stats + lc * 16, sb + LN_OFF + 18432, 256);
      bulk_commit();
      bulk_wait_all();
      flag_add(FL_H + (lc >> 2), 1);
      mbar_arrive(bars + B_KVGO);
      PROFG(1);
    }
  }

  if (wg == 2) {
    asm volatile("setmaxnreg.dec.sync.aligned.u32 56;");
    const Role ro = get_role(roles);
    if (warp == 11) {
      Ring r{0, 1};
      uint32_t ready = 0;
      const uint32_t bsz = ro.pitch - ASZ;
      const uint8_t* src = g_h + ro.g1_nt * bsz + ST * 73728;
      named_bar(10, 64);
#pragma unroll 1
      for (int i = ST; i < 32; i++) {
        poll_bits(ready, i == 31 ? 0xffffffffu : 1u << i, FL_H + lane, 4u, true);
        mbar_wait(bars + B_EMPTY + r.s * 8, r.ph ^ 1);
        if (elect_one()) bulk_g2s(sb + r.s * ro.pitch + ASZ, src, bsz, bars + B_FULL + r.s * 8);
        if (i == ST && lane == 0) PROF(25);
        if (i == KVGO && lane == 0) mbar_arrive(bars + B_KVGO);
        src += 73728;
        r.next();
      }
      if (ro.kind != 2) {
        uint32_t look = 0;
#pragma unroll 1
        for (int j = 0; j < 36; j++) {
          const uint8_t* su = g_u + ((size_t)g2_block(ro.half, j) * D_ + ro.dt * 144) * 128;
          if (j == 0 || j == 12 || j == 24) wait_counter(FL_U + ro.half * 3 + j / 12, j == 24 ? 36u : 48u, look, 100);
          if (ro.kind ? j == 4 : j < 2) mbar_wait(bars + B_UDONE + (j ? 8 : 0), 0);
          if (j == ST) {
            wait_counter(FL_GATE, NCTA, 0, GATE_NAP);
            named_arrive(9, 64);
            if (lane == 0) PROF(24);
          }
          if (j == ST + 1) {
#pragma unroll 1
            for (int o = lane; o < ST * 73728 / 16 / NG2; o += 32) ((uint4*)g_h)[cta * (ST * 73728 / 16 / NG2) + o] = make_uint4(0u, 0u, 0u, 0u);
          }
          mbar_wait(bars + B_EMPTY + r.s * 8, r.ph ^ 1);
          if (elect_one()) {
            bulk_g2s(sb + r.s * ro.pitch + ASZ, su + (ro.half ^ 1) * 9216, 9216, bars + B_FULL + r.s * 8);
            bulk_g2s(sb + r.s * ro.pitch + ASZ + 9216, su + ro.half * 9216, 9216, bars + B_FULL + r.s * 8);
          }
          if (j == 9 || j == 21) look = flag_ld(FL_U + ro.half * 3 + j / 12 + 1);
          if (j == 0 && lane == 0) PROF(8);
          r.next();
        }
      }
      polling_done(lane);
    } else if (warp == 8) {
      const uint64_t pol = stream_policy();
      Ring r{0, 0};
      asm volatile("barrier.cluster.wait.aligned;" ::: "memory");
#pragma unroll 1
      for (int i = 0; i < 32; i++) {
        if (i < ST) spin_until(t_start, ATIME + i * ADT);
        mbar_wait(bars + B_EMPTY + r.s * 8, r.ph ^ 1);
        if (elect_one()) {
          mbar_expect(bars + B_FULL + r.s * 8, ro.pitch);
          tma_weights(sb + r.s * ro.pitch, &tmW1, i * 64, ro.g1_mt * 2, bars + B_FULL + r.s * 8, pol);
        }
        r.next();
      }
      if (ro.kind != 2) {
#pragma unroll 1
        for (int j = 0; j < 36; j++) {
          if (j == 4 && ro.kind == 0) mbar_wait(bars + B_CEMPTY + 24, 0);
          if (j == ST) named_bar(9, 64);
          mbar_wait(bars + B_EMPTY + r.s * 8, r.ph ^ 1);
          if (elect_one()) {
            mbar_expect(bars + B_FULL + r.s * 8, PITCH_S);
            tma_weights(sb + r.s * ro.pitch, &tmW2, g2_block(ro.half, j) * 64, ro.g2_m >> 6, bars + B_FULL + r.s * 8, pol);
          }
          r.next();
        }
        if (lane < 2) mbar_expect(bars + B_RFULL + lane * 8, 9216);
        __syncwarp();
        mbar_wait(bars + B_EMPTY + r.s * 8, r.ph ^ 1);
        if (lane == 0) mbar_arrive_cluster(mapa(bars + B_GO, ro.half ^ 1));
      }
      if (lane == 0) PROF(28);
    } else {
      const uint64_t pol = stream_policy();
      {
        const uint32_t hb = (ro.pitch - ASZ) >> 1, raw = bars + B_RAW + (warp - 9) * 40, dst = sb + ASZ + (warp - 9) * hb;
        const uint8_t* src = g_h + (2 * ro.g1_nt + warp - 9) * hb;
        auto fetch_h = [&](int i) { if (elect_one()) { mbar_expect(raw + i * 8, hb); bulk_g2s(dst + i * ro.pitch, src + i * 73728, hb, raw + i * 8); } };
        spin_until(t_start, SPEC_T0);
        fetch_h(0);
        if (warp == 10) named_arrive(10, 64);
        if (tid == 288) PROF(3);
        spin_until(t_start, SPEC_T0 + SPEC_DT);
        fetch_h(1);
#pragma unroll 1
        for (int i = 0; i < ST; i++) {
#pragma unroll 1
          for (uint32_t tries = 0;; tries++) {
            mbar_wait(raw + i * 8, tries & 1);
            if (tid == 288 && i < 2) PROF(38 + i);
            const uint32_t pa = dst + i * ro.pitch + lane * 32 + (lane >> 2) * 4;
            uint32_t m = 1;
#pragma unroll
            for (int j = 0; j < 12; j++) m = min(m, lds32(pa + (j < 9 || ro.kind ? j : 0) * 1024));
            if (__all_sync(0xffffffffu, m)) break;
            if (tries > SPIN_LIMIT) asm volatile("trap;");
            if (tid == 288 && i == 0) PROF(26);
            fetch_h(i);
          }
          if (elect_one()) asm volatile("mbarrier.complete_tx.relaxed.cta.shared::cta.b64 [%0], %1;" ::"r"(bars + B_FULL + i * 8), "r"(hb) : "memory");
          if (tid == 288 && i < 2) PROF(46 + i);
          if (i == 0) { fetch_h(2); fetch_h(3); }
          if (i == 1) fetch_h(4);
        }
      }
      if (ro.kind == 0) {
        mbar_wait(bars + B_KVGO, 0);
        const int cs = ro.cs, grp = (cs / 3) * 2 + warp - 9, cb0 = (cs % 3) * 3;
        const uint32_t kin_s = sb + ST * PITCH_S + (warp - 9) * KVW, kout = kin_s + 2 * KVIN + lane * 176, fb = bars + B_KFULL + (warp - 9) * 16;
        auto fetch = [&](int i) {
          if (elect_one()) {
            mbar_expect(fb + (i & 1) * 8, KVIN);
            tma2d_stream(kin_s + (i & 1) * KVIN, &tmK, (cb0 + i) * 64, grp * 32 - 4, fb + (i & 1) * 8, pol);
            tma2d_stream(kin_s + (i & 1) * KVIN + 4608, &tmV, (cb0 + i) * 64, grp * 32 - 1, fb + (i & 1) * 8, pol);
          }
        };
        if (tid == 288) PROF(29);
        if (warp == 10) spin_until(clock_now(), KVSTAG);
        fetch(0);
        uint4 shk = ldg128(shiftk + (cb0 * 64 + lane * 2) * 4);
#pragma unroll 1
        for (int i = 0; i < 3; i++) {
          const uint32_t w0 = __byte_perm(shk.x, shk.z, 0x5410), w1 = __byte_perm(shk.x, shk.z, 0x7632);
          const uint32_t w2 = __byte_perm(shk.y, shk.w, 0x5410), w3 = __byte_perm(shk.y, shk.w, 0x7632);
          const uint32_t ka = kin_s + (i & 1) * KVIN + lane * 4;
          mbar_wait(fb + (i & 1) * 8, i >> 1);
          if (tid == 288 && i < 2) PROF(30 + i);
          if (i < 2) { fetch(i + 1); shk = ldg128(shiftk + ((cb0 + i + 1) * 64 + lane * 2) * 4); }
          uint32_t kr[36], x[33];
          auto rows = [&](int o) {
#pragma unroll
            for (int j = 4 * o; j < 4 * o + 4; j++) { kr[j] = lds32(ka + j * 128); if (j >= 3) x[j - 3] = lds32(ka + 4608 + (j - 3) * 128); }
          };
          rows(0); rows(1); rows(2);
          if (i) { if (elect_one()) bulk_wait_read(); __syncwarp(); }
#pragma unroll
          for (int o = 0; o < 8; o++) {
#pragma unroll
            for (int j = o ? 4 * o + 1 : 0; j < 4 * o + 5; j++) x[j] = hmul2(hfma2(kr[j + 3], w0, hfma2(kr[j + 2], w1, hfma2(kr[j + 1], w2, hmul2(kr[j], w3)))), x[j]);
#pragma unroll
            for (int c = 0; c < 2; c++) {
              const uint32_t sel = c ? 0x7632 : 0x5410;
              const uint32_t a0 = __byte_perm(x[4 * o + 1], x[4 * o], sel), a1 = __byte_perm(x[4 * o + 2], x[4 * o + 1], sel);
              const uint32_t a2 = __byte_perm(x[4 * o + 3], x[4 * o + 2], sel), a3 = __byte_perm(x[4 * o + 4], x[4 * o + 3], sel);
              sts128(kout + c * 5632 + o * 16, a0, a1, a2, a3);
              if (o >= 6) sts128(kout + c * 5632 + 32 + o * 16, a0, a1, a2, a3);
            }
            if (o < 6) rows(o + 3);
          }
          fence_async_smem();
          __syncwarp();
          if (i && elect_one()) { bulk_wait_all(); flag_add(FL_KV + i - 1, 1); }
#pragma unroll 1
          for (int k = 0; k < 64 / KVROWS; k++) {
            if (k) spin_until(clock_now(), KVGAP);
            if (elect_one()) { tma4d_store(&tmKV, (cb0 + i) * 32 + ((k * KVROWS) & 31), (k * KVROWS) >> 5, grp, kin_s + 2 * KVIN + k * KVROWS * 176); bulk_commit(); }
          }
        }
        uint4 h0 = make_uint4(0u, 0u, 0u, 0u);
        if (lane < NCONV) {
          h0 = ldg128(ssmk + (size_t)conv_chan(cs, lane) * S_);
          h0.x = __byte_perm(pack_bf16(bf_lo(h0.x) + bf_lo(ldg16(ssmD + conv_chan(cs, lane))), 0.f), h0.x, 0x7610);
        }
        if (elect_one()) {
          bulk_wait_all();
          flag_add(FL_KV + 2, 1);
          if (warp == 9) PROFG(2);
        }
        __syncwarp();
#pragma unroll 1
        for (int i = warp == 9 ? 0 : 2; i < (warp == 9 ? 2 : NCONV); i++) {
          const int b = i & 3, d = conv_chan(cs, i);
          const uint32_t base = conv_buf(sb, b), cf = bars + B_CFULL + b * 8;
          if (!(i & 1)) wait_counter(FL_KV + (i >> 1), 192u, 0, 200);
          if (i == 0 && lane == 0) PROF(23);
          if (i == 3) {
            mbar_wait(bars + B_G1DONE, 0);
            if (elect_one()) bulk_prefetch(ssmk + (size_t)conv_chan(cs, 4) * S_, 2 * S_ * 2, pol);
          }
          if (i >= 4) mbar_wait(bars + B_CEMPTY + b * 8, 0);
          if (lane == i) sts128(base + CH_OFF, h0.x, h0.y, h0.z, h0.w);
          if (lane >= 27) sts128(base + (lane >= 29 ? CH_OFF + (lane - 32) * 16 : CT_OFF + (lane - 27) * 16), 0u, 0u, 0u, 0u);
          fence_async_smem();
          __syncwarp();
          if (elect_one()) {
            mbar_expect(cf, 4080 + KVT - 32);
            bulk_g2s(base + CT_OFF + 32, g_kv + (size_t)d * KVT, KVT - 32, cf);
            bulk_g2s_stream(base + CH_OFF + 16, ssmk + (size_t)d * S_ + 8, 4080, cf, pol);
          }
        }
      }
      if (warp == 9) {
        if (elect_one()) {
          const uint32_t bsz = ro.pitch - ASZ;
#pragma unroll 1
          for (int w = 0; w < 2; w++) {
            const uint32_t src = sb + (ro.kind ? (w ? (36 % ST) * PITCH_B + ASZ : ST * PITCH_B) : ((32 % ST) + w) * PITCH_S + ASZ);
            mbar_wait(bars + B_USTG + w * 8, 0);
            bulk_s2g(g_u + (size_t)(2 * ro.g1_mt + w) * D_ * 128 + ro.g1_nt * bsz, src, bsz);
            bulk_commit();
            bulk_wait_read();
            mbar_arrive(bars + B_UDONE + w * 8);
            bulk_wait_all();
            flag_add(FL_U + ro.half * 3 + (ro.kind ? 2 : w), 1);
            PROFG(5 + 12 * w);
          }
          if (ro.kind == 0) {
#pragma unroll 1
            for (int i = 0; i < NCONV; i++) {
              mbar_wait(bars + B_SFULL + (i & 1) * 8, (i >> 1) & 1);
              bulk_s2g(g_z + (size_t)chan_pos(conv_chan(ro.cs, i)) * S_, sb + CSTG_OFF + (i & 1) * 4096, 4096);
              bulk_commit();
              bulk_wait_read();
              mbar_arrive(bars + B_SEMPTY + (i & 1) * 8);
            }
            bulk_wait_all();
            flag_add(FL_Z, 1);
            PROFG(6);
          }
        }
      } else if (ro.kind != 2) {
        mbar_wait(bars + B_UDONE, 0);
        wait_counter(FL_Z, 96u, 0, 300);
        if (elect_one()) {
          mbar_expect(bars + B_ZFULL, 18432);
          tma2d(sb + ST * ro.pitch, &tmZ, ro.g2_m, ro.dt * 144 + ro.half * 72, bars + B_ZFULL);
          tma2d(sb + ST * ro.pitch + 9216, &tmZ, ro.g2_m + 64, ro.dt * 144 + ro.half * 72, bars + B_ZFULL);
          PROFG(7);
        }
        polling_done(lane);
      }
    }
  } else {
    asm volatile("setmaxnreg.inc.sync.aligned.u32 224;");
    const int wi = warp & 3, g = lane >> 2, qd = lane & 3, wt = tid & 127;
    const bool leader = wt == 0;
    Pipe p{{0, 0}, 0, false};
    asm volatile("barrier.cluster.wait.aligned;" ::: "memory");
    int kind;
    {
      const Role ro = get_role(roles);
      kind = ro.kind;
      const int f0 = ro.g1_mt * 128 + wg * 64 + wi * 16 + g;
      const float bias0 = 0.5f * __bfloat162float(b1[f0]), bias1 = 0.5f * __bfloat162float(b1[f0 + 8]);
      const uint32_t so = ((lane >> 4) * 8 + (lane & 7)) * 128 + (((2 * wi + ((lane >> 3) & 1)) ^ (lane & 7)) << 4);
      if (kind) {
        float acc[96];
        gemm1<96, LEAD_B>(acc, p, sb, wg, leader);
        pipe_drain(p, bars, leader);
        if (wg) mbar_wait(bars + B_EMPTY + (36 % ST) * 8, ((36 / ST) & 1) ^ 1);
        if (leader) PROF(4 + 10 * wg);
        gelu_store(acc, bias0, bias1, sb + (wg ? (36 % ST) * PITCH_B + ASZ : ST * PITCH_B) + so);
        if (lane == 0) mbar_arrive(bars + B_USTG + wg * 8);
        if (leader) PROF(15 + wg);
      } else {
        const int cB = (g >> 1) & 1, cA = g >> 2, b = 2 * wi + (g & 1);
        const uint32_t toff = pin(CT_OFF + (40 * (2 * cA + cB) + 8 + b - 2 * qd) * 4);
        uint32_t a[16][4];
        auto load_a = [&](uint32_t base, int t, uint32_t on) {
          const uint32_t pt = base + toff + (t >> 1) * 1280 + (t & 1) * 64;
          a[t][0] = lds32_if(pt + 32, on); a[t][1] = lds32_if(pt + 672, on); a[t][2] = lds32_if(pt, on); a[t][3] = lds32_if(pt + 640, on);
        };
        {
          float acc[72];
          gemm1<72, LEAD_S>(acc, p, sb, wg, leader);
          if (wg == 1) named_arrive(6, 256);
          mbar_wait(bars + B_CFULL + wg * 8, 0);
#pragma unroll
          for (int t = 0; t < 8; t++) load_a(conv_buf(sb, wg), t, 1);
          pipe_drain(p, bars, leader);
          if (leader) mbar_arrive(bars + B_G1DONE);
          mbar_wait(bars + B_EMPTY + ((32 % ST) + wg) * 8, ((32 / ST) & 1) ^ 1);
          if (leader) PROF(4 + 10 * wg);
          gelu_store(acc, bias0, bias1, sb + ((32 % ST) + wg) * PITCH_S + ASZ + so);
          if (lane == 0) mbar_arrive(bars + B_USTG + wg * 8);
          if (leader) PROF(15 + wg);
        }
        const int phi = 2 * cA + (qd >> 1) + cB, pp = cB ? (phi & 3) : ((phi + 3) & 3);
        const int srcB = pin(((pp >> 1) << 4) | ((cB ^ 1) << 3) | ((g & 1) << 2) | ((pp & 1) << 1) | (qd & 1));
        const bool pB1 = cB && phi < 4, pB2 = cB && phi == 4;
        const int word = (8 * cB + 2 * (phi & 3) + (qd & 1)) * 8 + b;
        const uint32_t sto = pin(sb + CSTG_OFF + wg * 4096 + (word ^ (((word >> 5) & 3) << 1)) * 4);
#pragma unroll 1
        for (int i = wg; i < NCONV; i += 2) {
          const uint32_t base = conv_buf(sb, i & 3), next = conv_buf(sb, (i + 2) & 3);
          const uint64_t dH = mkdesc(base + CH_OFF, 16, 128, 0);
          float y[8][16];
          named_bar(6 + wg, 256);
          wg_fence();
#pragma unroll
          for (int t = 0; t < 16; t++) {
            if (t == 8) wg_fence();
            if (t == 14) named_arrive(7 - wg, 256);
#pragma unroll
            for (int cb = t >> 1; cb < 8; cb++) {
              wgmma_rs_n32(y[cb], a[t][0], a[t][1], a[t][2], a[t][3], dH + (32 * cb - 32 * (t >> 1) - 2 * (t & 1) - 1), t);
              if (t == 0 && cb == 1 && leader) PROF(32 + i);
              if (t < 4 && (cb & 3) == 3) load_a(base, 8 + 2 * t + (cb >> 2), 1);
            }
          }
          wg_commit();
          const bool more = i + 2 < NCONV;
          if (more) mbar_wait(bars + B_CFULL + ((i + 2) & 3) * 8, (i + 2) >> 2);
          mbar_wait(bars + B_SEMPTY + wg * 8, ((i >> 1) & 1) ^ 1);
          wg_wait<0>();
          if (lane == 0) mbar_arrive(bars + B_CEMPTY + (i & 3) * 8);
          if (leader) PROF(40 + i);
          uint32_t P[16], Q[16], R[16], o[8];
#pragma unroll
          for (int j = 0; j < 32; j++) {
            if ((j & 3) == 0) load_a(next, j >> 2, more);
            float v0 = y[j >> 2][4 * (j & 3)], v1 = y[j >> 2][4 * (j & 3) + 1];
            if (j >= 2) { v0 += y[(j - 2) >> 2][4 * ((j - 2) & 3) + 2]; v1 += y[(j - 2) >> 2][4 * ((j - 2) & 3) + 3]; }
            if (j & 1) R[j >> 1] = shfl_ordered(pack_bf16(v0, v1), lane ^ 16);
            else P[j >> 1] = pack_bf16(v0, v1);
          }
#pragma unroll
          for (int m = 0; m < 16; m++) Q[m] = hadd2(P[m], cA ? R[m] : (m ? R[m - 1] : 0u));
#pragma unroll
          for (int m = 0; m < 8; m++) o[m] = shfl_ordered(pB1 ? Q[2 * m] : (pB2 ? (m ? Q[2 * m - 1] : 0u) : Q[2 * m + 1]), srcB);
#pragma unroll
          for (int m = 0; m < 8; m++) sts32(sto + m * 512, hadd2(pB1 ? Q[2 * m + 1] : Q[2 * m], o[m]));
          fence_async_smem();
          __syncwarp();
          if (lane == 0) mbar_arrive(bars + B_SFULL + wg * 8);
          if (leader) PROF(48 + i);
        }
        if (wg == 0) named_bar(6, 256);
      }
      if (tid == 128) flag_add(FL_GATE, 1);
    }
    if (kind != 2) {
      const Role ro = get_role(roles);
      const uint32_t pitch = ro.pitch;
      const int s0 = ro.g2_m + wg * 64 + wi * 16 + g;
      const size_t go = (size_t)s0 * D_ + ro.dt * 128 + ro.half * 64 + qd * 8, go8 = (size_t)s0 * D_ + 512 + ro.dt * 16 + ro.half * 8 + qd * 2;
      uint32_t x[2][9], sg[2][9];
      float acc[72];
      gemm_run<0>(acc, 6 + 2 * wg, 0, p, sb, pitch, wg, leader);
#pragma unroll
      for (int J = 0; J < 4; J++) {
        const uint4 v = ldg128(q + go + (J & 1) * 8 * D_ + (J >> 1) * 32);
        x[J & 1][4 * (J >> 1)] = v.x; x[J & 1][4 * (J >> 1) + 1] = v.y; x[J & 1][4 * (J >> 1) + 2] = v.z; x[J & 1][4 * (J >> 1) + 3] = v.w;
      }
      x[0][8] = ldg32(q + go8); x[1][8] = ldg32(q + go8 + 8 * D_);
      const uint4 st0 = ld_l2(g_stats + s0), st1 = ld_l2(g_stats + s0 + 8);
      const uint32_t braw0 = ldg16(b2 + s0), braw1 = ldg16(b2 + s0 + 8);
      gemm_run<0>(acc, 14, 1, p, sb, pitch, wg, leader);
      {
        const int zw = 8 * wi + (g ^ ((((ro.g2_m >> 6) + wg) & 3) << 1));
        const uint32_t za = sb + ST * pitch + wg * 9216 + qd * 256 + (zw & 3) * 4;
        mbar_wait(bars + B_ZFULL, 0);
#pragma unroll
        for (int j = 0; j < 9; j++) {
          sg[0][j] = lds32(za + j * 1024 + (((zw >> 2) ^ (2 * qd)) << 4));
          sg[1][j] = lds32(za + j * 1024 + 128 + (((zw >> 2) ^ (2 * qd + 1)) << 4));
        }
      }
      gemm_run<0>(acc, 1, 1, p, sb, pitch, wg, leader);
#pragma unroll
      for (int j = 0; j < 9; j++) {
        const uint32_t z0 = __byte_perm(sg[0][j], sg[1][j], 0x5410), z1 = __byte_perm(sg[0][j], sg[1][j], 0x7632);
        sg[0][j] = hmul2(ln_apply(x[0][j], st0), z0);
        sg[1][j] = hmul2(ln_apply(x[1][j], st1), z1);
        asm volatile("" : "+r"(sg[0][j]), "+r"(sg[1][j]));
      }
      gemm_run<0>(acc, 15 - LAG - SKEW - 2 * wg, 1, p, sb, pitch, wg, leader);
      if (wg == 1) named_bar(8, 256);
      gemm_run<0>(acc, SKEW, 1, p, sb, pitch, wg, leader);
      if (wg == 0) named_arrive(8, 256);
      uint32_t rp[18];
      Ring r0 = p.r;
      for (int i = 0; i < LAG; i++) r0.next();
      const uint32_t rofs = r0.s * pitch + wg * 9216 + wt * 16;
      const uint32_t rdst = mapa(sb + rofs, ro.half ^ 1), rbar = mapa(bars + B_RFULL + wg * 8, ro.half ^ 1);
      pipe_drain(p, bars, leader);
      if (leader) PROF(9 + 10 * wg);
      float cs[36], ck[36];
      split_acc(acc, cs, ck);
      gemm2_part<0>(cs, p.r, sb, pitch, wg, [&](int) {});
      const float hb0 = 0.5f * bf_lo(braw0), hb1 = 0.5f * bf_lo(braw1);
      gemm2_part<72>(ck, p.r, sb, pitch, wg, [&](int i) {
        if (i == 1) { wg_commit(); mbar_wait(bars + B_GO, 0); wg_wait<1>(); }
        if (i >= 1 && i <= 5) {
          const float* c = &cs[8 * (i - 1)];
          const uint32_t v0 = pack_bf16(fmaf(c[0], 0.5f, hb0), fmaf(c[1], 0.5f, hb0)), v1 = pack_bf16(fmaf(c[2], 0.5f, hb1), fmaf(c[3], 0.5f, hb1));
          if (i < 5) st_async4(rdst + (i - 1) * 2048, v0, v1, pack_bf16(fmaf(c[4], 0.5f, hb0), fmaf(c[5], 0.5f, hb0)), pack_bf16(fmaf(c[6], 0.5f, hb1), fmaf(c[7], 0.5f, hb1)), rbar);
          else st_async2(rdst + 8192 - wt * 8, v0, v1, rbar);
        }
        if (i == 14) mbar_wait(bars + B_RFULL + wg * 8, 0);
        if (i >= 14) {
#pragma unroll
          for (int m = 2 * (i - 14); m < 2 * (i - 13); m++) {
            const uint4 v = lds128(sb + rofs + m * 2048);
            rp[4 * m] = v.x; rp[4 * m + 1] = v.y; rp[4 * m + 2] = v.z; rp[4 * m + 3] = v.w;
          }
        }
        if (i == 15) { const uint2 v = lds64(sb + rofs + 8192 - wt * 8); rp[16] = v.x; rp[17] = v.y; }
      });
      __nv_bfloat16* o = out + go;
      wg_wait<0>();
      if (leader) PROF(10 + 10 * wg);
      float h[2][4], t[2][4], half = 0.5f;
#pragma unroll
      for (int j = 0; j <= 9; j++) {
        if (j < 9) {
          const uint32_t ra = rp[2 * j], rb = rp[2 * j + 1];
          if (j >= 2) half = fmaf(t[j & 1][3], 0.f, 0.5f);
          h[j & 1][0] = fmaf(ck[4 * j], half, bf_lo(ra)); h[j & 1][1] = fmaf(ck[4 * j + 1], half, bf_hi(ra));
          h[j & 1][2] = fmaf(ck[4 * j + 2], half, bf_lo(rb)); h[j & 1][3] = fmaf(ck[4 * j + 3], half, bf_hi(rb));
#pragma unroll
          for (int u = 0; u < 4; u++) t[j & 1][u] = tanh_ordered(h[j & 1][u]);
        }
        if (j > 0) {
          const int k = j - 1;
          const float* hh = h[k & 1];
          const float* tt = t[k & 1];
          x[0][k] = hfma2(sg[0][k], pack_bf16(fmaf(hh[0], tt[0], hh[0]), fmaf(hh[1], tt[1], hh[1])), x[0][k]);
          x[1][k] = hfma2(sg[1][k], pack_bf16(fmaf(hh[2], tt[2], hh[2]), fmaf(hh[3], tt[3], hh[3])), x[1][k]);
          if ((k & 3) == 3) {
            *(uint4*)(o + (k >> 2) * 32) = make_uint4(x[0][k - 3], x[0][k - 2], x[0][k - 1], x[0][k]);
            *(uint4*)(o + 8 * D_ + (k >> 2) * 32) = make_uint4(x[1][k - 3], x[1][k - 2], x[1][k - 1], x[1][k]);
          }
        }
      }
      *(uint32_t*)(out + go8) = x[0][8];
      *(uint32_t*)(out + go8 + 8 * D_) = x[1][8];
      if (leader) PROF(11 + 7 * wg);
    }
  }
  if (tid == 0) PROFG(12);
}

typedef CUresult (*EncodeFn)(CUtensorMap*, CUtensorMapDataType, cuuint32_t, void*, const cuuint64_t*, const cuuint64_t*, const cuuint32_t*,
                             const cuuint32_t*, CUtensorMapInterleave, CUtensorMapSwizzle, CUtensorMapL2promotion, CUtensorMapFloatOOBfill);

uint32_t role_of_cluster(int k) {
  int grp, i;
  if (k < 4) { grp = 0; i = k; }
  else if (k < 36) { const int j = (k - 4) & 7; i = (k - 4) >> 3; grp = j < 6 ? 1 + j : 12 + 2 * (j - 6); }
  else if (k < 64) { const int j = (k - 36) % 7; i = (k - 36) / 7; grp = j < 5 ? 7 + j : 13 + 2 * (j - 5); }
  else return 2u | (uint32_t)(14 + 3 * (k - 64)) << 8 | 2u << 16;
  if (grp < 12) return (uint32_t)(i << 2 | grp << 4 | grp << 8 | i << 16);
  const int u = (grp & 1) * 4 + i;
  return (uint32_t)(1 | i << 2 | grp << 4 | (12 + 3 * ((grp - 12) >> 1) + u / 3) << 8 | (u % 3) << 16);
}

}

extern "C" void kernel_launch(void* const* d_in, const int* in_sizes, int n_in, void* d_out, int out_size) {
  (void)in_sizes; (void)n_in; (void)out_size;
  EncodeFn enc = nullptr;
  cudaDriverEntryPointQueryResult qr;
  cudaGetDriverEntryPoint("cuTensorMapEncodeTiled", (void**)&enc, cudaEnableDefault, &qr);
  void* zp = nullptr;
  cudaGetSymbolAddress(&zp, g_z);
  void* hp = nullptr;
  cudaGetSymbolAddress(&hp, g_h);
  void* kvp = nullptr;
  cudaGetSymbolAddress(&kvp, g_kv);
  CUtensorMap tmW1, tmW2, tmZ, tmH, tmK, tmV, tmKV;
  for (int w = 0; w < 2; w++) {
    cuuint64_t gd[2] = {D_, S_};
    cuuint64_t gs[1] = {D_ * 2};
    cuuint32_t bx[2] = {64, w ? 33u : 36u};
    cuuint32_t es[2] = {1, 1};
    enc(w ? &tmV : &tmK, CU_TENSOR_MAP_DATA_TYPE_BFLOAT16, 2, d_in[1 + w], gd, gs, bx, es, CU_TENSOR_MAP_INTERLEAVE_NONE, CU_TENSOR_MAP_SWIZZLE_NONE,
        CU_TENSOR_MAP_L2_PROMOTION_L2_128B, CU_TENSOR_MAP_FLOAT_OOB_FILL_NONE);
  }
  {
    cuuint64_t gd[4] = {40, D_ / 2, 2, 64};
    cuuint64_t gs[3] = {2 * KVT, KVT, 160};
    cuuint32_t bx[4] = {44, KVROWS, 1, 1};
    cuuint32_t es[4] = {1, 1, 1, 1};
    enc(&tmKV, CU_TENSOR_MAP_DATA_TYPE_UINT32, 4, kvp, gd, gs, bx, es, CU_TENSOR_MAP_INTERLEAVE_NONE, CU_TENSOR_MAP_SWIZZLE_NONE,
        CU_TENSOR_MAP_L2_PROMOTION_NONE, CU_TENSOR_MAP_FLOAT_OOB_FILL_NONE);
  }
  {
    cuuint64_t gd[3] = {64, 32 * 72, 8};
    cuuint64_t gs[2] = {1024, 128};
    cuuint32_t bx[3] = {64, 72, 2};
    cuuint32_t es[3] = {1, 1, 1};
    enc(&tmH, CU_TENSOR_MAP_DATA_TYPE_BFLOAT16, 3, hp, gd, gs, bx, es, CU_TENSOR_MAP_INTERLEAVE_NONE, CU_TENSOR_MAP_SWIZZLE_128B,
        CU_TENSOR_MAP_L2_PROMOTION_NONE, CU_TENSOR_MAP_FLOAT_OOB_FILL_NONE);
  }
  for (int w = 0; w < 2; w++) {
    const cuuint64_t M = w ? S_ : F_, K = w ? F_ : S_;
    cuuint64_t gd[3] = {64, K, M / 64};
    cuuint64_t gs[2] = {M * 2, 128};
    cuuint32_t bx[3] = {64, 64, 2};
    cuuint32_t es[3] = {1, 1, 1};
    enc(w ? &tmW2 : &tmW1, CU_TENSOR_MAP_DATA_TYPE_BFLOAT16, 3, d_in[w ? 9 : 7], gd, gs, bx, es, CU_TENSOR_MAP_INTERLEAVE_NONE,
        CU_TENSOR_MAP_SWIZZLE_128B, CU_TENSOR_MAP_L2_PROMOTION_L2_256B, CU_TENSOR_MAP_FLOAT_OOB_FILL_NONE);
  }
  {
    cuuint64_t gd[2] = {S_, D_};
    cuuint64_t gs[1] = {S_ * 2};
    cuuint32_t bx[2] = {64, 72};
    cuuint32_t es[2] = {1, 1};
    enc(&tmZ, CU_TENSOR_MAP_DATA_TYPE_BFLOAT16, 2, zp, gd, gs, bx, es, CU_TENSOR_MAP_INTERLEAVE_NONE, CU_TENSOR_MAP_SWIZZLE_128B,
        CU_TENSOR_MAP_L2_PROMOTION_L2_256B, CU_TENSOR_MAP_FLOAT_OOB_FILL_NONE);
  }
  RoleMap roles;
  for (int k = 0; k < NCTA / 2; k++) roles.role[k] = role_of_cluster(k);
  cudaFuncSetAttribute(fused_kernel, cudaFuncAttributeMaxDynamicSharedMemorySize, SMEM_BYTES);
  fused_kernel<<<NCTA, 384, SMEM_BYTES>>>(tmW1, tmW2, tmZ, tmH, tmK, tmV, tmKV, roles, (const __nv_bfloat16*)d_in[0],
                                          (const __nv_bfloat16*)d_in[3], (const __nv_bfloat16*)d_in[4],
                                          (const __nv_bfloat16*)d_in[5], (const __nv_bfloat16*)d_in[8], (const __nv_bfloat16*)d_in[10],
                                          (__nv_bfloat16*)d_out);
}
```

```cpp
#include <cuda_runtime.h>
#include <cuda_bf16.h>
#include <cuda.h>
#include <stdint.h>

namespace {

constexpr int S_ = 2048, D_ = 576, F_ = 4608;
constexpr int NCTA = 132, NG2 = 128, NCONV = 6;
constexpr int ST = 5, ASZ = 16384, PITCH_S = ASZ + 144 * 128, PITCH_B = ASZ + 192 * 128;
constexpr int KVIN = (36 + 33) * 128, KVW = 2 * KVIN + 64 * 176;
constexpr int BAR_OFF = ST * PITCH_S + 2 * KVW;
constexpr int SMEM_BYTES = BAR_OFF + 512;
constexpr int QLATE = 20, QDELAY = 400, QRAMP = 5, ATIME = 1500, ADT = 300;
constexpr int SPEC_T0 = 3600, SPEC_DT = 400;
constexpr int KVROWS = 32, KVGAP = 300, KVSTAG = 1200;
constexpr int KVGO = 6;
constexpr int SKEW = 1;
constexpr int LEAD_S = 3, LEAD_B = 2;
constexpr int TURN = 2, PFTAIL = 99;
constexpr int GATE_NAP = 50, ZDELAY = 3000, ZRAMP = 40, NPF = 1, PFGAP = 600, XAT = 12;
constexpr int LAG = 4;
constexpr int CBUF = 14464, CH_OFF = 128, CT_OFF = 4224, KVT = 10240;
constexpr int CSTG_OFF = ST * PITCH_S + 3 * CBUF;
constexpr uint32_t SPIN_LIMIT = 1u << 22;

__device__ __align__(1024) uint8_t g_h[32 * 72 * 1024];
__device__ __align__(1024) uint8_t g_u[72 * D_ * 128];
__device__ __align__(1024) uint8_t g_kv[D_ * KVT];
__device__ __align__(1024) __nv_bfloat16 g_z[D_ * S_];
__device__ uint4 g_stats[S_];
constexpr int FL_H = 0, FL_U = 32, FL_KV = 38, FL_Z = 41, FL_GATE = 42, FL_N = 43;
__device__ __align__(128) uint32_t g_flags[FL_N * 32];
__device__ unsigned g_done;
struct RoleMap { uint32_t role[NCTA / 2]; };
#define PROF(i) do {} while (0)
#define PROFG(i) do {} while (0)

template<int TB> __device__ __forceinline__ void wgmma_ss(float (&d)[96], uint64_t da, uint64_t db, int sd) {
  asm volatile("{\n.reg .pred p;\nsetp.ne.b32 p, %98, 0;\n"
    "wgmma.mma_async.sync.aligned.m64n192k16.f32.bf16.bf16 {%0, %1, %2, %3, %4, %5, %6, %7, %8, %9, %10, %11, %12, %13, %14, %15, %16, %17, %18, %19, %20, %21, %22, %23, %24, %25, %26, %27, %28, %29, %30, %31, %32, %33, %34, %35, %36, %37, %38, %39, %40, %41, %42, %43, %44, %45, %46, %47, %48, %49, %50, %51, %52, %53, %54, %55, %56, %57, %58, %59, %60, %61, %62, %63, %64, %65, %66, %67, %68, %69, %70, %71, %72, %73, %74, %75, %76, %77, %78, %79, %80, %81, %82, %83, %84, %85, %86, %87, %88, %89, %90, %91, %92, %93, %94, %95}, %96, %97, p, 1, 1, 1, %99;\n}\n"
    : "+f"(d[0]), "+f"(d[1]), "+f"(d[2]), "+f"(d[3]), "+f"(d[4]), "+f"(d[5]), "+f"(d[6]), "+f"(d[7]), "+f"(d[8]), "+f"(d[9]), "+f"(d[10]), "+f"(d[11]), "+f"(d[12]), "+f"(d[13]), "+f"(d[14]), "+f"(d[15]), "+f"(d[16]), "+f"(d[17]), "+f"(d[18]), "+f"(d[19]), "+f"(d[20]), "+f"(d[21]), "+f"(d[22]), "+f"(d[23]), "+f"(d[24]), "+f"(d[25]), "+f"(d[26]), "+f"(d[27]), "+f"(d[28]), "+f"(d[29]), "+f"(d[30]), "+f"(d[31]), "+f"(d[32]), "+f"(d[33]), "+f"(d[34]), "+f"(d[35]), "+f"(d[36]), "+f"(d[37]), "+f"(d[38]), "+f"(d[39]), "+f"(d[40]), "+f"(d[41]), "+f"(d[42]), "+f"(d[43]), "+f"(d[44]), "+f"(d[45]), "+f"(d[46]), "+f"(d[47]), "+f"(d[48]), "+f"(d[49]), "+f"(d[50]), "+f"(d[51]), "+f"(d[52]), "+f"(d[53]), "+f"(d[54]), "+f"(d[55]), "+f"(d[56]), "+f"(d[57]), "+f"(d[58]), "+f"(d[59]), "+f"(d[60]), "+f"(d[61]), "+f"(d[62]), "+f"(d[63]), "+f"(d[64]), "+f"(d[65]), "+f"(d[66]), "+f"(d[67]), "+f"(d[68]), "+f"(d[69]), "+f"(d[70]), "+f"(d[71]), "+f"(d[72]), "+f"(d[73]), "+f"(d[74]), "+f"(d[75]), "+f"(d[76]), "+f"(d[77]), "+f"(d[78]), "+f"(d[79]), "+f"(d[80]), "+f"(d[81]), "+f"(d[82]), "+f"(d[83]), "+f"(d[84]), "+f"(d[85]), "+f"(d[86]), "+f"(d[87]), "+f"(d[88]), "+f"(d[89]), "+f"(d[90]), "+f"(d[91]), "+f"(d[92]), "+f"(d[93]), "+f"(d[94]), "+f"(d[95])
    : "l"(da), "l"(db), "r"(sd), "n"(TB));
}
template<int TB> __device__ __forceinline__ void wgmma_ss(float (&d)[72], uint64_t da, uint64_t db, int sd) {
  asm volatile("{\n.reg .pred p;\nsetp.ne.b32 p, %74, 0;\n"
    "wgmma.mma_async.sync.aligned.m64n144k16.f32.bf16.bf16 {%0, %1, %2, %3, %4, %5, %6, %7, %8, %9, %10, %11, %12, %13, %14, %15, %16, %17, %18, %19, %20, %21, %22, %23, %24, %25, %26, %27, %28, %29, %30, %31, %32, %33, %34, %35, %36, %37, %38, %39, %40, %41, %42, %43, %44, %45, %46, %47, %48, %49, %50, %51, %52, %53, %54, %55, %56, %57, %58, %59, %60, %61, %62, %63, %64, %65, %66, %67, %68, %69, %70, %71}, %72, %73, p, 1, 1, 1, %75;\n}\n"
    : "+f"(d[0]), "+f"(d[1]), "+f"(d[2]), "+f"(d[3]), "+f"(d[4]), "+f"(d[5]), "+f"(d[6]), "+f"(d[7]), "+f"(d[8]), "+f"(d[9]), "+f"(d[10]), "+f"(d[11]), "+f"(d[12]), "+f"(d[13]), "+f"(d[14]), "+f"(d[15]), "+f"(d[16]), "+f"(d[17]), "+f"(d[18]), "+f"(d[19]), "+f"(d[20]), "+f"(d[21]), "+f"(d[22]), "+f"(d[23]), "+f"(d[24]), "+f"(d[25]), "+f"(d[26]), "+f"(d[27]), "+f"(d[28]), "+f"(d[29]), "+f"(d[30]), "+f"(d[31]), "+f"(d[32]), "+f"(d[33]), "+f"(d[34]), "+f"(d[35]), "+f"(d[36]), "+f"(d[37]), "+f"(d[38]), "+f"(d[39]), "+f"(d[40]), "+f"(d[41]), "+f"(d[42]), "+f"(d[43]), "+f"(d[44]), "+f"(d[45]), "+f"(d[46]), "+f"(d[47]), "+f"(d[48]), "+f"(d[49]), "+f"(d[50]), "+f"(d[51]), "+f"(d[52]), "+f"(d[53]), "+f"(d[54]), "+f"(d[55]), "+f"(d[56]), "+f"(d[57]), "+f"(d[58]), "+f"(d[59]), "+f"(d[60]), "+f"(d[61]), "+f"(d[62]), "+f"(d[63]), "+f"(d[64]), "+f"(d[65]), "+f"(d[66]), "+f"(d[67]), "+f"(d[68]), "+f"(d[69]), "+f"(d[70]), "+f"(d[71])
    : "l"(da), "l"(db), "r"(sd), "n"(TB));
}
template<int TB> __device__ __forceinline__ void wgmma_acc(float (&d)[36], uint64_t da, uint64_t db) {
  asm volatile("wgmma.mma_async.sync.aligned.m64n72k16.f32.bf16.bf16 {%0, %1, %2, %3, %4, %5, %6, %7, %8, %9, %10, %11, %12, %13, %14, %15, %16, %17, %18, %19, %20, %21, %22, %23, %24, %25, %26, %27, %28, %29, %30, %31, %32, %33, %34, %35}, %36, %37, 1, 1, 1, 1, %38;\n"
    : "+f"(d[0]), "+f"(d[1]), "+f"(d[2]), "+f"(d[3]), "+f"(d[4]), "+f"(d[5]), "+f"(d[6]), "+f"(d[7]), "+f"(d[8]), "+f"(d[9]), "+f"(d[10]), "+f"(d[11]), "+f"(d[12]), "+f"(d[13]), "+f"(d[14]), "+f"(d[15]), "+f"(d[16]), "+f"(d[17]), "+f"(d[18]), "+f"(d[19]), "+f"(d[20]), "+f"(d[21]), "+f"(d[22]), "+f"(d[23]), "+f"(d[24]), "+f"(d[25]), "+f"(d[26]), "+f"(d[27]), "+f"(d[28]), "+f"(d[29]), "+f"(d[30]), "+f"(d[31]), "+f"(d[32]), "+f"(d[33]), "+f"(d[34]), "+f"(d[35])
    : "l"(da), "l"(db), "n"(TB));
}
__device__ __forceinline__ void wgmma_rs_n32(float (&d)[16], uint32_t a0, uint32_t a1, uint32_t a2, uint32_t a3, uint64_t db, int sd) {
  asm volatile("{\n.reg .pred p;\nsetp.ne.b32 p, %21, 0;\n"
    "wgmma.mma_async.sync.aligned.m64n32k16.f32.bf16.bf16 {%0, %1, %2, %3, %4, %5, %6, %7, %8, %9, %10, %11, %12, %13, %14, %15}, {%16, %17, %18, %19}, %20, p, 1, 1, 0;\n}\n"
    : "+f"(d[0]), "+f"(d[1]), "+f"(d[2]), "+f"(d[3]), "+f"(d[4]), "+f"(d[5]), "+f"(d[6]), "+f"(d[7]), "+f"(d[8]), "+f"(d[9]), "+f"(d[10]), "+f"(d[11]), "+f"(d[12]), "+f"(d[13]), "+f"(d[14]), "+f"(d[15])
    : "r"(a0), "r"(a1), "r"(a2), "r"(a3), "l"(db), "r"(sd));
}

__device__ __forceinline__ void wg_fence() { asm volatile("wgmma.fence.sync.aligned;" ::: "memory"); }
__device__ __forceinline__ void wg_commit() { asm volatile("wgmma.commit_group.sync.aligned;" ::: "memory"); }
template <int n> __device__ __forceinline__ void wg_wait() { asm volatile("wgmma.wait_group.sync.aligned %0;" ::"n"(n) : "memory"); }
__device__ __forceinline__ uint64_t mkdesc(uint32_t addr, uint32_t lbo, uint32_t sbo, uint32_t sw) {
  return (uint64_t)((addr & 0x3FFFF) >> 4) | ((uint64_t)(lbo >> 4) << 16) | ((uint64_t)(sbo >> 4) << 32) | ((uint64_t)sw << 62);
}
__device__ __forceinline__ void mbar_init(uint32_t a, int c) { asm volatile("mbarrier.init.shared::cta.b64 [%0], %1;" ::"r"(a), "r"(c)); }
__device__ __forceinline__ void mbar_expect(uint32_t a, uint32_t b) { asm volatile("mbarrier.arrive.expect_tx.shared::cta.b64 _, [%0], %1;" ::"r"(a), "r"(b) : "memory"); }
__device__ __forceinline__ void mbar_arrive(uint32_t a) { asm volatile("mbarrier.arrive.shared::cta.b64 _, [%0];" ::"r"(a) : "memory"); }
__device__ __forceinline__ void mbar_arrive_cluster(uint32_t raddr) { asm volatile("mbarrier.arrive.shared::cluster.b64 _, [%0];" ::"r"(raddr) : "memory"); }
__device__ __forceinline__ uint32_t mapa(uint32_t a, uint32_t cta) { uint32_t r; asm("mapa.shared::cluster.u32 %0, %1, %2;" : "=r"(r) : "r"(a), "r"(cta)); return r; }
__device__ __forceinline__ void mbar_wait(uint32_t a, uint32_t ph) {
  asm volatile(
      "{\n.reg .pred p;\n.reg .u32 c;\nmov.u32 c, 0;\n"
      "WAIT_LOOP:\nmbarrier.try_wait.parity.shared::cta.b64 p, [%0], %1;\n@p bra WAIT_DONE;\n"
      "add.u32 c, c, 1;\nsetp.lt.u32 p, c, %2;\n@p bra WAIT_LOOP;\ntrap;\nWAIT_DONE:\n}" ::"r"(a), "r"(ph), "n"(SPIN_LIMIT) : "memory");
}
__device__ __forceinline__ void tma2d(uint32_t dst, const CUtensorMap* m, int c0, int c1, uint32_t bar) {
  asm volatile("cp.async.bulk.tensor.2d.shared::cluster.global.mbarrier::complete_tx::bytes [%0], [%1, {%3, %4}], [%2];" ::"r"(dst), "l"(m), "r"(bar), "r"(c0), "r"(c1) : "memory");
}
__device__ __forceinline__ void bulk_g2s(uint32_t dst, const void* src, uint32_t sz, uint32_t bar) {
  asm volatile("cp.async.bulk.shared::cluster.global.mbarrier::complete_tx::bytes [%0], [%1], %2, [%3];" ::"r"(dst), "l"(src), "r"(sz), "r"(bar) : "memory");
}
__device__ __forceinline__ void bulk_s2g(void* dst, uint32_t src, uint32_t sz) {
  asm volatile("cp.async.bulk.global.shared::cta.bulk_group [%0], [%1], %2;" ::"l"(dst), "r"(src), "r"(sz) : "memory");
}
__device__ __forceinline__ uint64_t stream_policy() {
  uint64_t p;
  asm volatile("createpolicy.fractional.L2::evict_first.b64 %0, 1.0;" : "=l"(p));
  return p;
}
__device__ __forceinline__ void tma_weights(uint32_t dst, const CUtensorMap* m, int k0, int mchunk, uint32_t bar, uint64_t pol) {
  asm volatile("cp.async.bulk.tensor.3d.shared::cluster.global.mbarrier::complete_tx::bytes.L2::cache_hint [%0], [%1, {%6, %3, %4}], [%2], %5;"
               ::"r"(dst), "l"(m), "r"(bar), "r"(k0), "r"(mchunk), "l"(pol), "r"(0) : "memory");
}
__device__ __forceinline__ void tma_weights_prefetch(const CUtensorMap* m, int k0, int mchunk, uint64_t pol) {
  asm volatile("cp.async.bulk.prefetch.tensor.3d.L2.global.L2::cache_hint [%0, {%4, %1, %2}], %3;" ::"l"(m), "r"(k0), "r"(mchunk), "l"(pol), "r"(0) : "memory");
}
__device__ __forceinline__ bool elect_one() {
  uint32_t p;
  asm volatile("{\n.reg .pred P;\nelect.sync _|P, 0xffffffff;\nselp.u32 %0, 1, 0, P;\n}" : "=r"(p));
  return p;
}
__device__ __forceinline__ void bulk_g2s_stream(uint32_t dst, const void* src, uint32_t sz, uint32_t bar, uint64_t pol) {
  asm volatile("cp.async.bulk.shared::cluster.global.mbarrier::complete_tx::bytes.L2::cache_hint [%0], [%1], %2, [%3], %4;"
               ::"r"(dst), "l"(src), "r"(sz), "r"(bar), "l"(pol) : "memory");
}
__device__ __forceinline__ void tma3d_store(const CUtensorMap* m, int c1, int c2, uint32_t src) {
  asm volatile("cp.async.bulk.tensor.3d.global.shared::cta.bulk_group [%0, {%4, %2, %3}], [%1];" ::"l"(m), "r"(src), "r"(c1), "r"(c2), "r"(0) : "memory");
}
__device__ __forceinline__ void tma2d_stream(uint32_t dst, const CUtensorMap* m, int c0, int c1, uint32_t bar, uint64_t pol) {
  asm volatile("cp.async.bulk.tensor.2d.shared::cluster.global.mbarrier::complete_tx::bytes.L2::cache_hint [%0], [%1, {%3, %4}], [%2], %5;"
               ::"r"(dst), "l"(m), "r"(bar), "r"(c0), "r"(c1), "l"(pol) : "memory");
}
__device__ __forceinline__ void tma4d_store(const CUtensorMap* m, int c1, int c2, int c3, uint32_t src) {
  asm volatile("cp.async.bulk.tensor.4d.global.shared::cta.bulk_group [%0, {%5, %2, %3, %4}], [%1];" ::"l"(m), "r"(src), "r"(c1), "r"(c2), "r"(c3), "r"(0) : "memory");
}
__device__ __forceinline__ void bulk_commit() { asm volatile("cp.async.bulk.commit_group;" ::: "memory"); }
__device__ __forceinline__ void bulk_wait_all() { asm volatile("cp.async.bulk.wait_group 0;" ::: "memory"); }
__device__ __forceinline__ void fence_async_smem() { asm volatile("fence.proxy.async.shared::cta;" ::: "memory"); }
__device__ __forceinline__ void fence_async_global() { asm volatile("fence.proxy.async.global;" ::: "memory"); }
__device__ __forceinline__ void named_bar(int id, int n) { asm volatile("bar.sync %0, %1;" ::"r"(id), "r"(n) : "memory"); }
__device__ __forceinline__ void named_arrive(int id, int n) { asm volatile("bar.arrive %0, %1;" ::"r"(id), "r"(n) : "memory"); }
__device__ __forceinline__ void flag_add(int i, uint32_t v) { asm volatile("red.relaxed.gpu.global.add.u32 [%0], %1;" ::"l"(g_flags + i * 32), "r"(v) : "memory"); }
__device__ __forceinline__ uint32_t flag_ld(int i) { uint32_t v; asm volatile("ld.relaxed.gpu.global.u32 %0, [%1];" : "=r"(v) : "l"(g_flags + i * 32) : "memory"); return v; }
__device__ __forceinline__ void prefetch_map(const CUtensorMap* m) { asm volatile("prefetch.tensormap [%0];" ::"l"(m) : "memory"); }
__device__ __forceinline__ void stsm4_t(uint32_t a, uint32_t r0, uint32_t r1, uint32_t r2, uint32_t r3) {
  asm volatile("stmatrix.sync.aligned.m8n8.x4.trans.shared.b16 [%0], {%1, %2, %3, %4};" ::"r"(a), "r"(r0), "r"(r1), "r"(r2), "r"(r3) : "memory");
}
__device__ __forceinline__ uint32_t lds32(uint32_t a) { uint32_t v; asm volatile("ld.shared.u32 %0, [%1];" : "=r"(v) : "r"(a) : "memory"); return v; }
__device__ __forceinline__ void sts32(uint32_t a, uint32_t v) { asm volatile("st.shared.u32 [%0], %1;" ::"r"(a), "r"(v) : "memory"); }
__device__ __forceinline__ uint4 ld_l2(const uint4* p) { uint4 v; asm volatile("ld.relaxed.gpu.global.v4.u32 {%0, %1, %2, %3}, [%4];" : "=r"(v.x), "=r"(v.y), "=r"(v.z), "=r"(v.w) : "l"(p) : "memory"); return v; }
__device__ __forceinline__ void sts128(uint32_t a, uint32_t x, uint32_t y, uint32_t z, uint32_t w) { asm volatile("st.shared.v4.u32 [%0], {%1, %2, %3, %4};" ::"r"(a), "r"(x), "r"(y), "r"(z), "r"(w) : "memory"); }
__device__ __forceinline__ uint4 lds128(uint32_t a) { uint4 v; asm volatile("ld.shared.v4.u32 {%0, %1, %2, %3}, [%4];" : "=r"(v.x), "=r"(v.y), "=r"(v.z), "=r"(v.w) : "r"(a) : "memory"); return v; }
__device__ __forceinline__ void st_async4(uint32_t raddr, uint32_t a, uint32_t b, uint32_t c, uint32_t d, uint32_t rbar) {
  asm volatile("st.async.weak.shared::cluster.mbarrier::complete_tx::bytes.v4.b32 [%0], {%1, %2, %3, %4}, [%5];" ::"r"(raddr), "r"(a), "r"(b), "r"(c), "r"(d), "r"(rbar) : "memory");
}
__device__ __forceinline__ uint32_t pack_bf16(float lo, float hi) { uint32_t r; asm("cvt.rn.bf16x2.f32 %0, %1, %2;" : "=r"(r) : "f"(hi), "f"(lo)); return r; }
__device__ __forceinline__ float bf_lo(uint32_t v) { return __uint_as_float(v << 16); }
__device__ __forceinline__ float bf_hi(uint32_t v) { return __uint_as_float(v & 0xffff0000u); }
__device__ __forceinline__ float bf_round(float x) { return bf_lo(pack_bf16(x, 0.f)); }
__device__ __forceinline__ uint32_t hmul2(uint32_t a, uint32_t b) { uint32_t r; asm("mul.rn.bf16x2 %0, %1, %2;" : "=r"(r) : "r"(a), "r"(b)); return r; }
__device__ __forceinline__ uint32_t hsub2(uint32_t a, uint32_t b) { uint32_t r; asm("sub.rn.bf16x2 %0, %1, %2;" : "=r"(r) : "r"(a), "r"(b)); return r; }
__device__ __forceinline__ uint32_t hfma2(uint32_t a, uint32_t b, uint32_t c) { uint32_t r; asm("fma.rn.bf16x2 %0, %1, %2, %3;" : "=r"(r) : "r"(a), "r"(b), "r"(c)); return r; }
__device__ __forceinline__ uint4 ldg128(const void* p) { uint4 v; asm volatile("ld.global.nc.v4.u32 {%0, %1, %2, %3}, [%4];" : "=r"(v.x), "=r"(v.y), "=r"(v.z), "=r"(v.w) : "l"(p)); return v; }
__device__ __forceinline__ uint32_t ldg16(const void* p) { uint32_t v; asm volatile("ld.global.nc.u16 %0, [%1];" : "=r"(v) : "l"(p)); return v; }
__device__ __forceinline__ float tanh_ordered(float x) { float y; asm volatile("tanh.approx.f32 %0, %1;" : "=f"(y) : "f"(x)); return y; }
__device__ __forceinline__ void mma16816(float (&d)[4], uint32_t a0, uint32_t a1, uint32_t a2, uint32_t a3, uint32_t b0, uint32_t b1) {
  asm("mma.sync.aligned.m16n8k16.row.col.f32.bf16.bf16.f32 {%0, %1, %2, %3}, {%4, %5, %6, %7}, {%8, %9}, {%0, %1, %2, %3};"
      : "+f"(d[0]), "+f"(d[1]), "+f"(d[2]), "+f"(d[3]) : "r"(a0), "r"(a1), "r"(a2), "r"(a3), "r"(b0), "r"(b1));
}
__device__ __forceinline__ uint32_t hadd2(uint32_t a, uint32_t b) { uint32_t r; asm("add.rn.bf16x2 %0, %1, %2;" : "=r"(r) : "r"(a), "r"(b)); return r; }
__device__ __forceinline__ uint32_t ldg32(const void* p) { uint32_t v; asm volatile("ld.global.nc.L1::no_allocate.u32 %0, [%1];" : "=r"(v) : "l"(p)); return v; }
__device__ __forceinline__ uint2 lds64(uint32_t a) { uint2 v; asm volatile("ld.shared.v2.u32 {%0, %1}, [%2];" : "=r"(v.x), "=r"(v.y) : "r"(a) : "memory"); return v; }
__device__ __forceinline__ uint32_t lds32_if(uint32_t a, uint32_t on) {
  uint32_t v;
  asm volatile("{\n.reg .pred p;\nsetp.ne.u32 p, %2, 0;\n@p ld.shared.u32 %0, [%1];\n}" : "=r"(v) : "r"(a), "r"(on) : "memory");
  return v;
}
__device__ __forceinline__ uint32_t clock_now() { uint32_t t; asm volatile("mov.u32 %0, %%clock;" : "=r"(t)); return t; }
__device__ __forceinline__ void spin_until(uint32_t t0, uint32_t n) { while (clock_now() - t0 < n) {} }
__device__ __forceinline__ uint2 ldg64_if(const void* p, uint32_t on) {
  uint2 v;
  asm volatile("{\n.reg .pred p;\nsetp.ne.u32 p, %3, 0;\n@p ld.global.nc.v2.u32 {%0, %1}, [%2];\n}" : "=r"(v.x), "=r"(v.y) : "l"(p), "r"(on));
  return v;
}
template <class T> __device__ __forceinline__ T pin(T v) { asm volatile("" : "+r"(v)); return v; }
__device__ __forceinline__ void st_async2(uint32_t raddr, uint32_t a, uint32_t b, uint32_t rbar) {
  asm volatile("st.async.weak.shared::cluster.mbarrier::complete_tx::bytes.v2.b32 [%0], {%1, %2}, [%3];" ::"r"(raddr), "r"(a), "r"(b), "r"(rbar) : "memory");
}
__device__ __forceinline__ void bulk_prefetch(const void* src, uint32_t sz, uint64_t pol) {
  asm volatile("cp.async.bulk.prefetch.L2.global.L2::cache_hint [%0], %1, %2;" ::"l"(src), "r"(sz), "l"(pol) : "memory");
}
__device__ __forceinline__ void bulk_wait_read() { asm volatile("cp.async.bulk.wait_group.read 0;" ::: "memory"); }
__device__ __forceinline__ uint32_t shfl_ordered(uint32_t v, int src) { uint32_t r; asm volatile("shfl.sync.idx.b32 %0, %1, %2, 0x1f, 0xffffffff;" : "=r"(r) : "r"(v), "r"(src)); return r; }
__device__ __forceinline__ int chan_pos(int d) {
  return d < 512 ? 72 * (d >> 6) + ((d & 33) | ((d & 6) << 2) | ((d >> 2) & 6)) : 72 * ((d - 512) >> 3) + 64 + (d & 7);
}

struct Ring {
  uint32_t s, ph;
  __device__ __forceinline__ void next() { if (++s == ST) { s = 0; ph ^= 1; } }
};
constexpr int B_FULL = 0, B_GO = 40, B_CFULL = 48, B_SEMPTY = 80, B_ZFULL = 96, B_RFULL = 104, B_UDONE = 120, B_KFULL = 136, B_RAW = 168,
              B_EMPTY = 248, B_KVGO = 288, B_G1DONE = 296,
              B_CEMPTY = 304, B_SFULL = 336, B_USTG = 352, B_END = 368;

__device__ __forceinline__ void poll_once(uint32_t& ready, int idx, uint32_t want, bool active) {
  bool ok = false;
  if (active) ok = flag_ld(idx) == want;
  const uint32_t seen = __ballot_sync(0xffffffffu, ok);
  if (seen & ~ready) fence_async_global();
  ready |= seen;
}
__device__ __forceinline__ void poll_bits(uint32_t& ready, uint32_t bits, int idx, uint32_t want, bool active) {
  for (uint32_t spins = 0; (ready & bits) != bits; spins++) {
    poll_once(ready, idx, want, active);
    if (spins > SPIN_LIMIT) asm volatile("trap;");
  }
}
__device__ __forceinline__ void wait_counter(int idx, uint32_t want, uint32_t first, uint32_t nap) {
#pragma unroll 1
  for (uint32_t spins = 0; first != want; spins++) {
    if (spins) __nanosleep(nap);
    first = flag_ld(idx);
    if (spins > SPIN_LIMIT) asm volatile("trap;");
  }
  fence_async_global();
}

__device__ __forceinline__ float ln_rinv(float var) {
  float rt, rinv;
  asm("sqrt.approx.ftz.f32 %0, %1;" : "=f"(rt) : "f"(bf_round(bf_round(var) + 1e-5f)));
  asm("rcp.approx.ftz.f32 %0, %1;" : "=f"(rinv) : "f"(bf_round(rt)));
  return rinv;
}
__device__ __forceinline__ uint32_t ln_apply(uint32_t x, const uint4& st) {
  const uint32_t d = hsub2(x, st.x);
  return hfma2(d, st.y, hmul2(d, st.z));
}

__device__ __forceinline__ void polling_done(int lane) {
  unsigned old = 0;
  if (lane == 0) asm volatile("atom.relaxed.gpu.global.add.u32 %0, [%1], 1;" : "=r"(old) : "l"(&g_done) : "memory");
  old = __shfl_sync(0xffffffffu, old, 0);
  if (old == NCTA + NG2 - 1) {
#pragma unroll 1
    for (int i = lane; i < FL_N; i += 32) g_flags[i * 32] = 0;
    if (lane == 0) g_done = 0;
  }
}

struct Pipe { Ring r; uint32_t prev; bool pending; int cnt; };
template <int TB, int R>
__device__ __forceinline__ void gemm_run(float (&acc)[R], int n, int accumulate, Pipe& p, uint32_t sb, uint32_t pitch, int wg, bool leader) {
  const uint32_t bars = sb + BAR_OFF;
  const uint64_t dA0 = mkdesc(sb + wg * 8192, 8192, 1024, 1);
  const uint64_t dB0 = TB ? mkdesc(sb + ASZ, 128, 1024, 0) : mkdesc(sb + ASZ, 16, 1024, 1);
  constexpr int KB_STEP = TB ? 16 : 2;
#pragma unroll 1
  for (int kb = 0; kb < n; kb++) {
    mbar_wait(bars + B_FULL + p.r.s * 8, p.r.ph);
    if (kb == 0 && !accumulate && threadIdx.x == 0) PROF(21 + TB);
    const uint64_t dA = dA0 + p.r.s * (pitch >> 4), dB = dB0 + p.r.s * (pitch >> 4);
    wg_fence();
    wgmma_ss<TB>(acc, dA, dB, accumulate | kb);
#pragma unroll
    for (int k = 1; k < 4; k++) wgmma_ss<TB>(acc, dA + k * 128, dB + k * KB_STEP, 1);
    wg_commit();
    wg_wait<1>();
    if (p.pending && leader) mbar_arrive(bars + B_EMPTY + p.prev * 8);
    p.pending = true;
    p.prev = p.r.s;
    p.r.next();
  }
}
__device__ __forceinline__ void pipe_drain(Pipe& p, uint32_t bars, bool leader) {
  wg_wait<0>();
  if (leader) mbar_arrive(bars + B_EMPTY + p.prev * 8);
  p.pending = false;
}

template <int BROW0>
__device__ __forceinline__ void gemm2_part(float (&c)[36], uint32_t sb, uint32_t pitch, int wg) {
  const uint64_t dA0 = mkdesc(sb + wg * 8192, 8192, 1024, 1), dB0 = mkdesc(sb + ASZ + BROW0 * 128, 16, 1024, 1);
  wg_fence();
#pragma unroll
  for (int i = 0; i < 4 * LAG; i++) {
    const int step = 68 - LAG + (i >> 2);
    if ((i & 3) == 0 && BROW0 == 0) mbar_wait(sb + BAR_OFF + B_FULL + (step % ST) * 8, (step / ST) & 1);
    if (i == 4 * LAG - TURN && BROW0 && wg == 0) named_arrive(7, 256);
    wgmma_acc<0>(c, dA0 + (step % ST) * (pitch >> 4) + (i & 3) * 128, dB0 + (step % ST) * (pitch >> 4) + (i & 3) * 2);
  }
  wg_commit();
}
__device__ __forceinline__ void split_acc(const float (&acc)[72], float (&a)[36], float (&b)[36]) {
#pragma unroll
  for (int i = 0; i < 36; i++) { asm volatile("mov.b32 %0, %1;" : "=f"(a[i]) : "f"(acc[i])); asm volatile("mov.b32 %0, %1;" : "=f"(b[i]) : "f"(acc[36 + i])); }
}
template <int R>
__device__ __forceinline__ void gelu_store(const float (&acc)[R], float hbias0, float hbias1, uint32_t sa) {
  uint32_t pk[4];
#pragma unroll
  for (int j = 0; j <= R / 4; j += 2) {
    float hx[8], t[8];
    if (j < R / 4) {
#pragma unroll
      for (int u = 0; u < 8; u++) {
        hx[u] = fmaf(acc[4 * j + u], 0.5f, (u & 2) ? hbias1 : hbias0);
        t[u] = tanh_ordered(hx[u] * fmaf(hx[u] * hx[u], 0.2854192651f, 1.5957691216f));
      }
    }
    if (j > 0) stsm4_t(sa + (j - 2) * 1024, pk[0], pk[1], pk[2], pk[3]);
    if (j < R / 4) {
#pragma unroll
      for (int u = 0; u < 4; u++) pk[u] = pack_bf16(fmaf(hx[2 * u], t[2 * u], hx[2 * u]), fmaf(hx[2 * u + 1], t[2 * u + 1], hx[2 * u + 1]));
    }
  }
  fence_async_smem();
  __syncwarp();
}
struct Role { int half, kind, g2_m, dt, g1_mt, g1_nt, cs; uint32_t pitch; };
__device__ __forceinline__ Role get_role(const RoleMap& roles) {
  uint32_t b;
  asm volatile("mov.u32 %0, %%ctaid.x;" : "=r"(b));
  const uint32_t w = roles.role[b >> 1];
  const int half = b & 1, kind = w & 3, m = (w >> 4) & 15, dt = (w >> 2) & 3;
  return Role{half, kind, m * 128, dt, half * 18 + (int)((w >> 8) & 31), (int)(w >> 16), (m * 4 + dt) * 2 + half, kind ? (uint32_t)PITCH_B : (uint32_t)PITCH_S};
}
__device__ __forceinline__ int g2_block(int half, int j) { return half * 36 + (j < 12 ? 2 * j : j < 24 ? 2 * j - 23 : j); }
__device__ __forceinline__ int conv_chan(int cs, int i) { return (3 * (cs >> 5) + (i >> 1)) * 64 + ((2 * cs) & 63) + (i & 1); }
__device__ __forceinline__ uint32_t conv_buf(uint32_t sb, int b) { return sb + (b == 3 ? (36 % ST) * PITCH_S : ST * PITCH_S + b * CBUF); }

template <int R, int LEAD>
__device__ __forceinline__ void gemm1(float (&acc)[R], Pipe& p, uint32_t sb, int wg, bool leader) {
  constexpr uint32_t pitch = ASZ + R * 256;
  gemm_run<1>(acc, 32 - LEAD, 0, p, sb, pitch, wg, leader);
  if (LEAD) {
    if (wg == 1) { pipe_drain(p, sb + BAR_OFF, leader); named_bar(8, 256); }
    gemm_run<1>(acc, LEAD, 1, p, sb, pitch, wg, leader);
    if (wg == 0) named_arrive(8, 256);
  }
}

__global__ void __cluster_dims__(2, 1, 1) __launch_bounds__(384, 1)
fused_kernel(const __grid_constant__ CUtensorMap tmW1, const __grid_constant__ CUtensorMap tmW2, const __grid_constant__ CUtensorMap tmZ,
             const __grid_constant__ CUtensorMap tmH, const __grid_constant__ CUtensorMap tmK, const __grid_constant__ CUtensorMap tmV,
             const __grid_constant__ CUtensorMap tmKV, const __grid_constant__ RoleMap roles, const __nv_bfloat16* __restrict__ q,
             const __nv_bfloat16* __restrict__ shiftk, const __nv_bfloat16* __restrict__ ssmk,
             const __nv_bfloat16* __restrict__ ssmD, const __nv_bfloat16* __restrict__ b1, const __nv_bfloat16* __restrict__ b2,
             __nv_bfloat16* __restrict__ out) {
  extern __shared__ __align__(1024) uint8_t smem_raw[];
  const uint32_t sb = (uint32_t)__cvta_generic_to_shared(smem_raw);
  const uint32_t bars = sb + BAR_OFF;
  const int cta = blockIdx.x;
  const int tid = threadIdx.x;
  const int warp = __shfl_sync(0xffffffffu, tid >> 5, 0);
  const int lane = tid & 31;
  const int wg = warp >> 2;
  if (tid == 288) PROFG(0);

  const uint32_t t_start = clock_now();
  const int lc = (cta + 120) & 127;
  const uint32_t do_ln = cta < 128 && warp < 8;
  const int ln_row = lc * 16 + (warp & 7) * 2 + (lane >> 4), l16 = lane & 15;
  uint2 xr[9];
  if (do_ln && lc >= QLATE) spin_until(t_start, QDELAY + QRAMP * lc);
#pragma unroll
  for (int i = 0; i < 9; i++) xr[i] = ldg64_if(q + (size_t)ln_row * D_ + i * 64 + l16 * 4, do_ln);
  constexpr int LN_OFF = ST * PITCH_B;
  uint32_t hs[9];
  {
    const int g0 = 4 * (l16 >> 3) + 2 * (l16 & 1), g8 = 9 * (l16 >> 1) + 8;
    const uint32_t hrow = sb + LN_OFF + ((ln_row >> 3) & 1) * 9216;
#pragma unroll
    for (int i = 0; i < 8; i++) hs[i] = hrow + g0 * 128 + ((((g0 + i) ^ ln_row) & 7) << 4) + ((l16 >> 1) & 3) * 4;
    hs[8] = hrow + g8 * 128 + (((g8 ^ ln_row) & 7) << 4) + (l16 & 1) * 8;
#pragma unroll
    for (int i = 0; i < 9; i++) hs[i] = shfl_ordered(hs[i], lane);
  }
  if (warp == 8 && elect_one()) {
#pragma unroll
    for (int o = 0; o < B_END; o += 8) mbar_init(bars + o, o < B_EMPTY ? 1 : o < B_CEMPTY ? 2 : 4);
    asm volatile("fence.mbarrier_init.release.cluster;" ::: "memory");
    prefetch_map(&tmW1);
    prefetch_map(&tmH);
    prefetch_map(&tmW2);
  }
  __syncwarp();
  asm volatile("barrier.cluster.arrive.relaxed.aligned;" ::: "memory");

  if (warp != 8) {
    const int hq = (lane & 16) >> 3, hb = (lane & 16) + hq;
    float da[3][4] = {};
#pragma unroll
    for (int i = 0; i < 9; i++) mma16816(da[i % 3], xr[i].x, 0x3f803f80u, xr[i].y, 0x3f803f80u, xr[i].x, xr[i].y);
    const float r1 = ((da[0][2] + da[0][3]) + (da[1][2] + da[1][3])) + (da[2][2] + da[2][3]);
    const float r2 = (lane & 4) ? (da[0][1] + da[1][1]) + da[2][1] : (da[0][0] + da[1][0]) + da[2][0];
    const float s1 = __shfl_sync(0xffffffffu, r1, hq) + __shfl_sync(0xffffffffu, r1, hq + 1);
    const float s2 = (__shfl_sync(0xffffffffu, r2, hb) + __shfl_sync(0xffffffffu, r2, hb + 4)) + (__shfl_sync(0xffffffffu, r2, hb + 9) + __shfl_sync(0xffffffffu, r2, hb + 13));
    if (tid == 0) { asm volatile("" ::"f"(s2) : "memory"); PROF(27); }
    const float mean = s1 * (1.f / D_), var = fmaxf(fmaf(-mean, mean, s2 * (1.f / D_)), 0.f);
    const float rinv = ln_rinv(var), rinv2 = ln_rinv(var * rinv * rinv), scale = rinv * rinv2, shift = -bf_round((mean - bf_round(mean)) * rinv) * rinv2;
    const uint32_t m2 = pack_bf16(mean, mean), hi2 = pack_bf16(scale, scale), lo2 = pack_bf16(scale - bf_lo(hi2), scale - bf_lo(hi2)), sh2 = pack_bf16(shift, shift);
    uint32_t w[18];
#pragma unroll
    for (int i = 0; i < 18; i++) {
      const uint32_t d = hsub2((i & 1) ? xr[i >> 1].y : xr[i >> 1].x, m2);
      asm("max.u32 %0, %1, 1;" : "=r"(w[i]) : "r"(hfma2(d, hi2, hfma2(d, lo2, sh2))));
    }
#pragma unroll
    for (int i = 0; i < 16; i++) {
      const int gi = 9 * (i >> 1) + (i & 1);
      asm volatile("{\n.reg .pred p;\nsetp.ne.u32 p, %2, 0;\n@p st.shared.u32 [%0], %1;\n}" ::"r"(hs[gi & 7] + gi * 128), "r"(w[i]), "r"(do_ln) : "memory");
    }
    asm volatile("{\n.reg .pred p;\nsetp.ne.u32 p, %3, 0;\n@p st.shared.v2.u32 [%0], {%1, %2};\n}" ::"r"(hs[8]), "r"(w[16]), "r"(w[17]), "r"(do_ln) : "memory");
    if (tid == 0) PROF(13);
    const uint32_t hi1 = pack_bf16(rinv, rinv);
    if (do_ln && l16 == 0) sts128(sb + LN_OFF + 18432 + (ln_row & 15) * 16, m2, hi1, pack_bf16(rinv - bf_lo(hi1), rinv - bf_lo(hi1)), 0u);
    fence_async_smem();
  }
  if (warp == 8) { named_arrive(0, 320); named_arrive(5, 96); }
  else if (warp == 9 || warp == 10) named_bar(5, 96);
  else named_bar(0, 320);
  if (cta < 128 && warp == 11) {
    if (elect_one()) {
      tma3d_store(&tmH, (lc >> 2) * 72, (lc & 3) * 2, sb + LN_OFF);
      bulk_s2g(g_stats + lc * 16, sb + LN_OFF + 18432, 256);
      bulk_commit();
      bulk_wait_all();
      flag_add(FL_H + (lc >> 2), 1);
      mbar_arrive(bars + B_KVGO);
      PROFG(1);
    }
  }

  if (wg == 2) {
    asm volatile("setmaxnreg.dec.sync.aligned.u32 56;");
    const Role ro = get_role(roles);
    if (warp == 11) {
      Ring r{0, 1};
      uint32_t ready = 0;
      const uint32_t bsz = ro.pitch - ASZ;
      const uint8_t* src = g_h + ro.g1_nt * bsz + ST * 73728;
      named_bar(10, 64);
#pragma unroll 1
      for (int i = ST; i < 32; i++) {
        poll_bits(ready, i == 31 ? 0xffffffffu : 1u << i, FL_H + lane, 4u, true);
        mbar_wait(bars + B_EMPTY + r.s * 8, r.ph ^ 1);
        if (elect_one()) bulk_g2s(sb + r.s * ro.pitch + ASZ, src, bsz, bars + B_FULL + r.s * 8);
        if (i == ST && lane == 0) PROF(25);
        if (i == KVGO && lane == 0) mbar_arrive(bars + B_KVGO);
        src += 73728;
        r.next();
      }
      if (ro.kind != 2) {
        uint32_t look = 0;
#pragma unroll 1
        for (int j = 0; j < 36; j++) {
          const uint8_t* su = g_u + ((size_t)g2_block(ro.half, j) * D_ + ro.dt * 144) * 128;
          if (j == 0 || j == 12 || j == 24) wait_counter(FL_U + ro.half * 3 + j / 12, j == 24 ? 36u : 48u, look, 100);
          if (ro.kind ? j == 4 : j < 2) mbar_wait(bars + B_UDONE + (j ? 8 : 0), 0);
          if (j == ST) {
            wait_counter(FL_GATE, NCTA, 0, GATE_NAP);
            named_arrive(9, 64);
            if (lane == 0) PROF(24);
          }
          if (j == 30) {
#pragma unroll 1
            for (int o = lane; o < ST * 73728 / 16 / NG2; o += 32) ((uint4*)g_h)[cta * (ST * 73728 / 16 / NG2) + o] = make_uint4(0u, 0u, 0u, 0u);
          }
          mbar_wait(bars + B_EMPTY + r.s * 8, r.ph ^ 1);
          if (elect_one()) {
            bulk_g2s(sb + r.s * ro.pitch + ASZ, su + (ro.half ^ 1) * 9216, 9216, bars + B_FULL + r.s * 8);
            bulk_g2s(sb + r.s * ro.pitch + ASZ + 9216, su + ro.half * 9216, 9216, bars + B_FULL + r.s * 8);
          }
          if (j == 9 || j == 21) look = flag_ld(FL_U + ro.half * 3 + j / 12 + 1);
          if (j == 0 && lane == 0) PROF(8);
          r.next();
        }
      }
      polling_done(lane);
    } else if (warp == 8) {
      const uint64_t pol = stream_policy();
      Ring r{0, 0};
      asm volatile("barrier.cluster.wait.aligned;" ::: "memory");
#pragma unroll 1
      for (int i = 0; i < 32; i++) {
        if (i < ST) spin_until(t_start, ATIME + i * ADT);
        mbar_wait(bars + B_EMPTY + r.s * 8, r.ph ^ 1);
        if (elect_one()) {
          mbar_expect(bars + B_FULL + r.s * 8, ro.pitch);
          tma_weights(sb + r.s * ro.pitch, &tmW1, i * 64, ro.g1_mt * 2, bars + B_FULL + r.s * 8, pol);
        }
        r.next();
      }
      if (ro.kind != 2) {
#pragma unroll 1
        for (int j = 0; j < 36; j++) {
          if (j == 4) {
#pragma unroll 1
            for (int k = 0; k < NPF; k++) {
              spin_until(clock_now(), PFGAP);
              const int jj = 4 + 4 * k + ro.dt;
              if (elect_one() && jj < 36) tma_weights_prefetch(&tmW2, g2_block(ro.half, jj) * 64, ro.g2_m >> 6, pol);
            }
            if (ro.kind == 0) mbar_wait(bars + B_CEMPTY + 24, 0);
          }
          if (j == ST) named_bar(9, 64);
          mbar_wait(bars + B_EMPTY + r.s * 8, r.ph ^ 1);
          if (elect_one()) {
            mbar_expect(bars + B_FULL + r.s * 8, PITCH_S);
            tma_weights(sb + r.s * ro.pitch, &tmW2, g2_block(ro.half, j) * 64, ro.g2_m >> 6, bars + B_FULL + r.s * 8, pol);
            if (j == PFTAIL + ro.dt) tma_weights_prefetch(&tmW2, g2_block(ro.half, 32 + ro.dt) * 64, ro.g2_m >> 6, pol);
          }
          r.next();
        }
        if (lane < 2) mbar_expect(bars + B_RFULL + lane * 8, 9216);
        __syncwarp();
        mbar_wait(bars + B_EMPTY + r.s * 8, r.ph ^ 1);
        if (lane == 0) mbar_arrive_cluster(mapa(bars + B_GO, ro.half ^ 1));
      }
      if (lane == 0) PROF(28);
    } else {
      const uint64_t pol = stream_policy();
      {
        const uint32_t hb = (ro.pitch - ASZ) >> 1, raw = bars + B_RAW + (warp - 9) * 40, dst = sb + ASZ + (warp - 9) * hb;
        const uint8_t* src = g_h + (2 * ro.g1_nt + warp - 9) * hb;
        auto fetch_h = [&](int i) { if (elect_one()) { mbar_expect(raw + i * 8, hb); bulk_g2s(dst + i * ro.pitch, src + i * 73728, hb, raw + i * 8); } };
        spin_until(t_start, SPEC_T0);
        fetch_h(0);
        if (warp == 10) named_arrive(10, 64);
        if (tid == 288) PROF(3);
        spin_until(t_start, SPEC_T0 + SPEC_DT);
        fetch_h(1);
#pragma unroll 1
        for (int i = 0; i < ST; i++) {
#pragma unroll 1
          for (uint32_t tries = 0;; tries++) {
            mbar_wait(raw + i * 8, tries & 1);
            if (tid == 288 && i < 2) PROF(38 + i);
            const uint32_t pa = dst + i * ro.pitch + lane * 32 + (lane >> 2) * 4;
            uint32_t m = 1;
#pragma unroll
            for (int j = 0; j < 12; j++) m = min(m, lds32(pa + (j < 9 || ro.kind ? j : 0) * 1024));
            if (__all_sync(0xffffffffu, m)) break;
            if (tries > SPIN_LIMIT) asm volatile("trap;");
            if (tid == 288 && i == 0) PROF(26);
            fetch_h(i);
          }
          if (elect_one()) asm volatile("mbarrier.complete_tx.relaxed.cta.shared::cta.b64 [%0], %1;" ::"r"(bars + B_FULL + i * 8), "r"(hb) : "memory");
          if (tid == 288 && i < 2) PROF(46 + i);
          if (i == 0) { fetch_h(2); fetch_h(3); }
          if (i == 1) fetch_h(4);
        }
      }
      if (ro.kind == 0) {
        mbar_wait(bars + B_KVGO, 0);
        const int cs = ro.cs, grp = (cs / 3) * 2 + warp - 9, cb0 = (cs % 3) * 3;
        const uint32_t kin_s = sb + ST * PITCH_S + (warp - 9) * KVW, kout = kin_s + 2 * KVIN + lane * 176, fb = bars + B_KFULL + (warp - 9) * 16;
        auto fetch = [&](int i) {
          if (elect_one()) {
            mbar_expect(fb + (i & 1) * 8, KVIN);
            tma2d_stream(kin_s + (i & 1) * KVIN, &tmK, (cb0 + i) * 64, grp * 32 - 4, fb + (i & 1) * 8, pol);
            tma2d_stream(kin_s + (i & 1) * KVIN + 4608, &tmV, (cb0 + i) * 64, grp * 32 - 1, fb + (i & 1) * 8, pol);
          }
        };
        if (tid == 288) PROF(29);
        if (warp == 10) spin_until(clock_now(), KVSTAG);
        fetch(0);
        uint4 shk = ldg128(shiftk + (cb0 * 64 + lane * 2) * 4);
#pragma unroll 1
        for (int i = 0; i < 3; i++) {
          const uint32_t w0 = __byte_perm(shk.x, shk.z, 0x5410), w1 = __byte_perm(shk.x, shk.z, 0x7632);
          const uint32_t w2 = __byte_perm(shk.y, shk.w, 0x5410), w3 = __byte_perm(shk.y, shk.w, 0x7632);
          const uint32_t ka = kin_s + (i & 1) * KVIN + lane * 4;
          mbar_wait(fb + (i & 1) * 8, i >> 1);
          if (tid == 288 && i < 2) PROF(30 + i);
          if (i < 2) { fetch(i + 1); shk = ldg128(shiftk + ((cb0 + i + 1) * 64 + lane * 2) * 4); }
          uint32_t kr[36], x[33];
          auto rows = [&](int o) {
#pragma unroll
            for (int j = 4 * o; j < 4 * o + 4; j++) { kr[j] = lds32(ka + j * 128); if (j >= 3) x[j - 3] = lds32(ka + 4608 + (j - 3) * 128); }
          };
          rows(0); rows(1); rows(2);
          if (i) { if (elect_one()) bulk_wait_read(); __syncwarp(); }
#pragma unroll
          for (int o = 0; o < 8; o++) {
#pragma unroll
            for (int j = o ? 4 * o + 1 : 0; j < 4 * o + 5; j++) x[j] = hmul2(hfma2(kr[j + 3], w0, hfma2(kr[j + 2], w1, hfma2(kr[j + 1], w2, hmul2(kr[j], w3)))), x[j]);
#pragma unroll
            for (int c = 0; c < 2; c++) {
              const uint32_t sel = c ? 0x7632 : 0x5410;
              const uint32_t a0 = __byte_perm(x[4 * o + 1], x[4 * o], sel), a1 = __byte_perm(x[4 * o + 2], x[4 * o + 1], sel);
              const uint32_t a2 = __byte_perm(x[4 * o + 3], x[4 * o + 2], sel), a3 = __byte_perm(x[4 * o + 4], x[4 * o + 3], sel);
              sts128(kout + c * 5632 + o * 16, a0, a1, a2, a3);
              if (o >= 6) sts128(kout + c * 5632 + 32 + o * 16, a0, a1, a2, a3);
            }
            if (o < 6) rows(o + 3);
          }
          fence_async_smem();
          __syncwarp();
          if (i && elect_one()) { bulk_wait_all(); flag_add(FL_KV + i - 1, 1); }
#pragma unroll 1
          for (int k = 0; k < 64 / KVROWS; k++) {
            if (k) spin_until(clock_now(), KVGAP);
            if (elect_one()) { tma4d_store(&tmKV, (cb0 + i) * 32 + ((k * KVROWS) & 31), (k * KVROWS) >> 5, grp, kin_s + 2 * KVIN + k * KVROWS * 176); bulk_commit(); }
          }
        }
        uint4 h0 = make_uint4(0u, 0u, 0u, 0u);
        if (lane < NCONV) {
          h0 = ldg128(ssmk + (size_t)conv_chan(cs, lane) * S_);
          h0.x = __byte_perm(pack_bf16(bf_lo(h0.x) + bf_lo(ldg16(ssmD + conv_chan(cs, lane))), 0.f), h0.x, 0x7610);
        }
        if (elect_one()) {
          bulk_wait_all();
          flag_add(FL_KV + 2, 1);
          if (warp == 9) PROFG(2);
        }
        __syncwarp();
#pragma unroll 1
        for (int i = warp == 9 ? 0 : 2; i < (warp == 9 ? 2 : NCONV); i++) {
          const int b = i & 3, d = conv_chan(cs, i);
          const uint32_t base = conv_buf(sb, b), cf = bars + B_CFULL + b * 8;
          if (!(i & 1)) wait_counter(FL_KV + (i >> 1), 192u, 0, 200);
          if (i == 0 && lane == 0) PROF(23);
          if (i == 3) {
            mbar_wait(bars + B_G1DONE, 0);
            if (elect_one()) bulk_prefetch(ssmk + (size_t)conv_chan(cs, 4) * S_, 2 * S_ * 2, pol);
          }
          if (i >= 4) mbar_wait(bars + B_CEMPTY + b * 8, 0);
          if (lane == i) sts128(base + CH_OFF, h0.x, h0.y, h0.z, h0.w);
          if (lane >= 27) sts128(base + (lane >= 29 ? CH_OFF + (lane - 32) * 16 : CT_OFF + (lane - 27) * 16), 0u, 0u, 0u, 0u);
          fence_async_smem();
          __syncwarp();
          if (elect_one()) {
            mbar_expect(cf, 4080 + KVT - 32);
            bulk_g2s(base + CT_OFF + 32, g_kv + (size_t)d * KVT, KVT - 32, cf);
            bulk_g2s_stream(base + CH_OFF + 16, ssmk + (size_t)d * S_ + 8, 4080, cf, pol);
          }
        }
      }
      if (warp == 9) {
        if (elect_one()) {
          const uint32_t bsz = ro.pitch - ASZ;
#pragma unroll 1
          for (int w = 0; w < 2; w++) {
            const uint32_t src = sb + (ro.kind ? (w ? (36 % ST) * PITCH_B + ASZ : ST * PITCH_B) : ((32 % ST) + w) * PITCH_S + ASZ);
            mbar_wait(bars + B_USTG + w * 8, 0);
            bulk_s2g(g_u + (size_t)(2 * ro.g1_mt + w) * D_ * 128 + ro.g1_nt * bsz, src, bsz);
            bulk_commit();
            bulk_wait_read();
            mbar_arrive(bars + B_UDONE + w * 8);
            bulk_wait_all();
            flag_add(FL_U + ro.half * 3 + (ro.kind ? 2 : w), 1);
            PROFG(5 + 12 * w);
          }
          if (ro.kind == 0) {
#pragma unroll 1
            for (int i = 0; i < NCONV; i++) {
              mbar_wait(bars + B_SFULL + (i & 1) * 8, (i >> 1) & 1);
              bulk_s2g(g_z + (size_t)chan_pos(conv_chan(ro.cs, i)) * S_, sb + CSTG_OFF + (i & 1) * 4096, 4096);
              bulk_commit();
              bulk_wait_read();
              mbar_arrive(bars + B_SEMPTY + (i & 1) * 8);
            }
            bulk_wait_all();
            flag_add(FL_Z, 1);
            PROFG(6);
          }
        }
      } else if (ro.kind != 2) {
        mbar_wait(bars + B_UDONE, 0);
        wait_counter(FL_Z, 96u, 0, 300);
        spin_until(clock_now(), ZDELAY + ZRAMP * cta);
        if (elect_one()) {
          mbar_expect(bars + B_ZFULL, 18432);
          tma2d(sb + ST * ro.pitch, &tmZ, ro.g2_m, ro.dt * 144 + ro.half * 72, bars + B_ZFULL);
          tma2d(sb + ST * ro.pitch + 9216, &tmZ, ro.g2_m + 64, ro.dt * 144 + ro.half * 72, bars + B_ZFULL);
          PROFG(7);
        }
        polling_done(lane);
      }
    }
  } else {
    asm volatile("setmaxnreg.inc.sync.aligned.u32 224;");
    const int wi = warp & 3, g = lane >> 2, qd = lane & 3, wt = tid & 127;
    const bool leader = wt == 0;
    Pipe p{{0, 0}, 0, false, 0};
    asm volatile("barrier.cluster.wait.aligned;" ::: "memory");
    int kind;
    {
      const Role ro = get_role(roles);
      kind = ro.kind;
      const int f0 = ro.g1_mt * 128 + wg * 64 + wi * 16 + g;
      const float bias0 = 0.5f * __bfloat162float(b1[f0]), bias1 = 0.5f * __bfloat162float(b1[f0 + 8]);
      const uint32_t so = ((lane >> 4) * 8 + (lane & 7)) * 128 + (((2 * wi + ((lane >> 3) & 1)) ^ (lane & 7)) << 4);
      if (kind) {
        float acc[96];
        gemm1<96, LEAD_B>(acc, p, sb, wg, leader);
        pipe_drain(p, bars, leader);
        if (wg) mbar_wait(bars + B_EMPTY + (36 % ST) * 8, ((36 / ST) & 1) ^ 1);
        if (leader) PROF(4 + 10 * wg);
        gelu_store(acc, bias0, bias1, sb + (wg ? (36 % ST) * PITCH_B + ASZ : ST * PITCH_B) + so);
        if (lane == 0) mbar_arrive(bars + B_USTG + wg * 8);
        if (leader) PROF(15 + wg);
      } else {
        const int cB = (g >> 1) & 1, cA = g >> 2, b = 2 * wi + (g & 1);
        const uint32_t toff = pin(CT_OFF + (40 * (2 * cA + cB) + 8 + b - 2 * qd) * 4);
        uint32_t a[16][4];
        auto load_a = [&](uint32_t base, int t, uint32_t on) {
          const uint32_t pt = base + toff + (t >> 1) * 1280 + (t & 1) * 64;
          a[t][0] = lds32_if(pt + 32, on); a[t][1] = lds32_if(pt + 672, on); a[t][2] = lds32_if(pt, on); a[t][3] = lds32_if(pt + 640, on);
        };
        {
          float acc[72];
          gemm1<72, LEAD_S>(acc, p, sb, wg, leader);
          if (wg == 1) named_arrive(6, 256);
          mbar_wait(bars + B_CFULL + wg * 8, 0);
#pragma unroll
          for (int t = 0; t < 8; t++) load_a(conv_buf(sb, wg), t, 1);
          pipe_drain(p, bars, leader);
          if (leader) mbar_arrive(bars + B_G1DONE);
          mbar_wait(bars + B_EMPTY + ((32 % ST) + wg) * 8, ((32 / ST) & 1) ^ 1);
          if (leader) PROF(4 + 10 * wg);
          gelu_store(acc, bias0, bias1, sb + ((32 % ST) + wg) * PITCH_S + ASZ + so);
          if (lane == 0) mbar_arrive(bars + B_USTG + wg * 8);
          if (leader) PROF(15 + wg);
        }
        const int phi = 2 * cA + (qd >> 1) + cB, pp = cB ? (phi & 3) : ((phi + 3) & 3);
        const int srcB = pin(((pp >> 1) << 4) | ((cB ^ 1) << 3) | ((g & 1) << 2) | ((pp & 1) << 1) | (qd & 1));
        const bool pB1 = cB && phi < 4, pB2 = cB && phi == 4;
        const int word = (8 * cB + 2 * (phi & 3) + (qd & 1)) * 8 + b;
        const uint32_t sto = pin(sb + CSTG_OFF + wg * 4096 + (word ^ (((word >> 5) & 3) << 1)) * 4);
#pragma unroll 1
        for (int i = wg; i < NCONV; i += 2) {
          const uint32_t base = conv_buf(sb, i & 3), next = conv_buf(sb, (i + 2) & 3);
          const uint64_t dH = mkdesc(base + CH_OFF, 16, 128, 0);
          float y[8][16];
          named_bar(6 + wg, 256);
          wg_fence();
#pragma unroll
          for (int t = 0; t < 16; t++) {
            if (t == 8) wg_fence();
            if (t == 14) named_arrive(7 - wg, 256);
#pragma unroll
            for (int cb = t >> 1; cb < 8; cb++) {
              wgmma_rs_n32(y[cb], a[t][0], a[t][1], a[t][2], a[t][3], dH + (32 * cb - 32 * (t >> 1) - 2 * (t & 1) - 1), t);
              if (t == 0 && cb == 1 && leader) PROF(32 + i);
              if (t < 4 && (cb & 3) == 3) load_a(base, 8 + 2 * t + (cb >> 2), 1);
            }
          }
          wg_commit();
          const bool more = i + 2 < NCONV;
          if (more) mbar_wait(bars + B_CFULL + ((i + 2) & 3) * 8, (i + 2) >> 2);
          mbar_wait(bars + B_SEMPTY + wg * 8, ((i >> 1) & 1) ^ 1);
          wg_wait<0>();
          if (lane == 0) mbar_arrive(bars + B_CEMPTY + (i & 3) * 8);
          if (leader) PROF(40 + i);
          uint32_t P[16], Q[16], R[16], o[8];
#pragma unroll
          for (int j = 0; j < 32; j++) {
            if ((j & 3) == 0) load_a(next, j >> 2, more);
            float v0 = y[j >> 2][4 * (j & 3)], v1 = y[j >> 2][4 * (j & 3) + 1];
            if (j >= 2) { v0 += y[(j - 2) >> 2][4 * ((j - 2) & 3) + 2]; v1 += y[(j - 2) >> 2][4 * ((j - 2) & 3) + 3]; }
            if (j & 1) R[j >> 1] = shfl_ordered(pack_bf16(v0, v1), lane ^ 16);
            else P[j >> 1] = pack_bf16(v0, v1);
          }
#pragma unroll
          for (int m = 0; m < 16; m++) Q[m] = hadd2(P[m], cA ? R[m] : (m ? R[m - 1] : 0u));
#pragma unroll
          for (int m = 0; m < 8; m++) o[m] = shfl_ordered(pB1 ? Q[2 * m] : (pB2 ? (m ? Q[2 * m - 1] : 0u) : Q[2 * m + 1]), srcB);
#pragma unroll
          for (int m = 0; m < 8; m++) sts32(sto + m * 512, hadd2(pB1 ? Q[2 * m + 1] : Q[2 * m], o[m]));
          fence_async_smem();
          __syncwarp();
          if (lane == 0) mbar_arrive(bars + B_SFULL + wg * 8);
          if (leader) PROF(48 + i);
        }
        if (wg == 0) named_bar(6, 256);
      }
      if (tid == 128) flag_add(FL_GATE, 1);
    }
    if (kind != 2) {
      const Role ro = get_role(roles);
      const uint32_t pitch = ro.pitch;
      const int s0 = ro.g2_m + wg * 64 + wi * 16 + g;
      const size_t go = (size_t)s0 * D_ + ro.dt * 128 + ro.half * 64 + qd * 8, go8 = (size_t)s0 * D_ + 512 + ro.dt * 16 + ro.half * 8 + qd * 2;
      uint32_t x[2][9], sg[2][9];
      float acc[72];
      gemm_run<0>(acc, XAT + 2 * wg, 0, p, sb, pitch, wg, leader);
#pragma unroll
      for (int J = 0; J < 4; J++) {
        const uint4 v = ldg128(q + go + (J & 1) * 8 * D_ + (J >> 1) * 32);
        x[J & 1][4 * (J >> 1)] = v.x; x[J & 1][4 * (J >> 1) + 1] = v.y; x[J & 1][4 * (J >> 1) + 2] = v.z; x[J & 1][4 * (J >> 1) + 3] = v.w;
      }
      x[0][8] = ldg32(q + go8); x[1][8] = ldg32(q + go8 + 8 * D_);
      const uint4 st0 = ld_l2(g_stats + s0), st1 = ld_l2(g_stats + s0 + 8);
      const uint32_t braw0 = ldg16(b2 + s0), braw1 = ldg16(b2 + s0 + 8);
      gemm_run<0>(acc, 20 - XAT, 1, p, sb, pitch, wg, leader);
      {
        const int zw = 8 * wi + (g ^ ((((ro.g2_m >> 6) + wg) & 3) << 1));
        const uint32_t za = sb + ST * pitch + wg * 9216 + qd * 256 + (zw & 3) * 4;
        mbar_wait(bars + B_ZFULL, 0);
#pragma unroll
        for (int j = 0; j < 9; j++) {
          sg[0][j] = lds32(za + j * 1024 + (((zw >> 2) ^ (2 * qd)) << 4));
          sg[1][j] = lds32(za + j * 1024 + 128 + (((zw >> 2) ^ (2 * qd + 1)) << 4));
        }
      }
      gemm_run<0>(acc, 1, 1, p, sb, pitch, wg, leader);
#pragma unroll
      for (int j = 0; j < 9; j++) {
        const uint32_t z0 = __byte_perm(sg[0][j], sg[1][j], 0x5410), z1 = __byte_perm(sg[0][j], sg[1][j], 0x7632);
        sg[0][j] = hmul2(ln_apply(x[0][j], st0), z0);
        sg[1][j] = hmul2(ln_apply(x[1][j], st1), z1);
        asm volatile("" : "+r"(sg[0][j]), "+r"(sg[1][j]));
      }
      gemm_run<0>(acc, 15 - LAG - SKEW - 2 * wg, 1, p, sb, pitch, wg, leader);
      if (wg == 1) named_bar(8, 256);
      gemm_run<0>(acc, SKEW, 1, p, sb, pitch, wg, leader);
      if (wg == 0) named_arrive(8, 256);
      const uint32_t rofs = (68 % ST) * pitch + wg * 9216 + wt * 16;
      const uint32_t rdst = mapa(sb + rofs, ro.half ^ 1), rbar = mapa(bars + B_RFULL + wg * 8, ro.half ^ 1);
      pipe_drain(p, bars, leader);
      if (leader) PROF(9 + 10 * wg);
      float cs[36], ck[36];
      split_acc(acc, cs, ck);
      gemm2_part<0>(cs, sb, pitch, wg);
      const float hb0 = fmaf(bf_lo(braw0), 0.5f, __uint_as_float(st0.w)), hb1 = fmaf(bf_lo(braw1), 0.5f, __uint_as_float(st1.w));
      mbar_wait(bars + B_GO, 0);
      wg_wait<0>();
      if (leader) PROF(54 + wg);
#pragma unroll
      for (int i = 0; i < 5; i++) {
        const float* c = &cs[8 * i];
        const uint32_t v0 = pack_bf16(fmaf(c[0], 0.5f, hb0), fmaf(c[1], 0.5f, hb0)), v1 = pack_bf16(fmaf(c[2], 0.5f, hb1), fmaf(c[3], 0.5f, hb1));
        if (i < 4) st_async4(rdst + i * 2048, v0, v1, pack_bf16(fmaf(c[4], 0.5f, hb0), fmaf(c[5], 0.5f, hb0)), pack_bf16(fmaf(c[6], 0.5f, hb1), fmaf(c[7], 0.5f, hb1)), rbar);
        else st_async2(rdst + 8192 - wt * 8, v0, v1, rbar);
      }
      if (wg == 1) named_bar(7, 256);
      gemm2_part<72>(ck, sb, pitch, wg);
      uint32_t rp[18];
      mbar_wait(bars + B_RFULL + wg * 8, 0);
#pragma unroll
      for (int m = 0; m < 4; m++) {
        const uint4 v = lds128(sb + rofs + m * 2048);
        rp[4 * m] = v.x; rp[4 * m + 1] = v.y; rp[4 * m + 2] = v.z; rp[4 * m + 3] = v.w;
      }
      { const uint2 v = lds64(sb + rofs + 8192 - wt * 8); rp[16] = v.x; rp[17] = v.y; }
      __nv_bfloat16* o = out + go;
      wg_wait<0>();
      if (leader) PROF(10 + 10 * wg);
      float h[2][4], t[2][4], half = 0.5f;
#pragma unroll
      for (int j = 0; j <= 9; j++) {
        if (j < 9) {
          const uint32_t ra = rp[2 * j], rb = rp[2 * j + 1];
          if (j >= 2) half = fmaf(t[j & 1][3], 0.f, 0.5f);
          h[j & 1][0] = fmaf(ck[4 * j], half, bf_lo(ra)); h[j & 1][1] = fmaf(ck[4 * j + 1], half, bf_hi(ra));
          h[j & 1][2] = fmaf(ck[4 * j + 2], half, bf_lo(rb)); h[j & 1][3] = fmaf(ck[4 * j + 3], half, bf_hi(rb));
#pragma unroll
          for (int u = 0; u < 4; u++) t[j & 1][u] = tanh_ordered(h[j & 1][u]);
        }
        if (j > 0) {
          const int k = j - 1;
          const float* hh = h[k & 1];
          const float* tt = t[k & 1];
          x[0][k] = hfma2(sg[0][k], pack_bf16(fmaf(hh[0], tt[0], hh[0]), fmaf(hh[1], tt[1], hh[1])), x[0][k]);
          x[1][k] = hfma2(sg[1][k], pack_bf16(fmaf(hh[2], tt[2], hh[2]), fmaf(hh[3], tt[3], hh[3])), x[1][k]);
          if ((k & 3) == 3) {
            *(uint4*)(o + (k >> 2) * 32) = make_uint4(x[0][k - 3], x[0][k - 2], x[0][k - 1], x[0][k]);
            *(uint4*)(o + 8 * D_ + (k >> 2) * 32) = make_uint4(x[1][k - 3], x[1][k - 2], x[1][k - 1], x[1][k]);
          }
        }
      }
      *(uint32_t*)(out + go8) = x[0][8];
      *(uint32_t*)(out + go8 + 8 * D_) = x[1][8];
      if (leader) PROF(11 + 7 * wg);
    }
  }
  if (tid == 0) PROFG(12);
}

typedef CUresult (*EncodeFn)(CUtensorMap*, CUtensorMapDataType, cuuint32_t, void*, const cuuint64_t*, const cuuint64_t*, const cuuint32_t*,
                             const cuuint32_t*, CUtensorMapInterleave, CUtensorMapSwizzle, CUtensorMapL2promotion, CUtensorMapFloatOOBfill);

uint32_t role_of_cluster(int k) {
  int grp, i;
  if (k < 4) { grp = 0; i = k; }
  else if (k < 36) { const int j = (k - 4) & 7; i = (k - 4) >> 3; grp = j < 6 ? 1 + j : 12 + 2 * (j - 6); }
  else if (k < 64) { const int j = (k - 36) % 7; i = (k - 36) / 7; grp = j < 5 ? 7 + j : 13 + 2 * (j - 5); }
  else return 2u | (uint32_t)(14 + 3 * (k - 64)) << 8 | 2u << 16;
  if (grp < 12) return (uint32_t)(i << 2 | grp << 4 | grp << 8 | i << 16);
  const int u = (grp & 1) * 4 + i;
  return (uint32_t)(1 | i << 2 | grp << 4 | (12 + 3 * ((grp - 12) >> 1) + u / 3) << 8 | (u % 3) << 16);
}

}

extern "C" void kernel_launch(void* const* d_in, const int* in_sizes, int n_in, void* d_out, int out_size) {
  (void)in_sizes; (void)n_in; (void)out_size;
  EncodeFn enc = nullptr;
  cudaDriverEntryPointQueryResult qr;
  cudaGetDriverEntryPoint("cuTensorMapEncodeTiled", (void**)&enc, cudaEnableDefault, &qr);
  void* zp = nullptr;
  cudaGetSymbolAddress(&zp, g_z);
  void* hp = nullptr;
  cudaGetSymbolAddress(&hp, g_h);
  void* kvp = nullptr;
  cudaGetSymbolAddress(&kvp, g_kv);
  CUtensorMap tmW1, tmW2, tmZ, tmH, tmK, tmV, tmKV;
  for (int w = 0; w < 2; w++) {
    cuuint64_t gd[2] = {D_, S_};
    cuuint64_t gs[1] = {D_ * 2};
    cuuint32_t bx[2] = {64, w ? 33u : 36u};
    cuuint32_t es[2] = {1, 1};
    enc(w ? &tmV : &tmK, CU_TENSOR_MAP_DATA_TYPE_BFLOAT16, 2, d_in[1 + w], gd, gs, bx, es, CU_TENSOR_MAP_INTERLEAVE_NONE, CU_TENSOR_MAP_SWIZZLE_NONE,
        CU_TENSOR_MAP_L2_PROMOTION_L2_128B, CU_TENSOR_MAP_FLOAT_OOB_FILL_NONE);
  }
  {
    cuuint64_t gd[4] = {40, D_ / 2, 2, 64};
    cuuint64_t gs[3] = {2 * KVT, KVT, 160};
    cuuint32_t bx[4] = {44, KVROWS, 1, 1};
    cuuint32_t es[4] = {1, 1, 1, 1};
    enc(&tmKV, CU_TENSOR_MAP_DATA_TYPE_UINT32, 4, kvp, gd, gs, bx, es, CU_TENSOR_MAP_INTERLEAVE_NONE, CU_TENSOR_MAP_SWIZZLE_NONE,
        CU_TENSOR_MAP_L2_PROMOTION_NONE, CU_TENSOR_MAP_FLOAT_OOB_FILL_NONE);
  }
  {
    cuuint64_t gd[3] = {64, 32 * 72, 8};
    cuuint64_t gs[2] = {1024, 128};
    cuuint32_t bx[3] = {64, 72, 2};
    cuuint32_t es[3] = {1, 1, 1};
    enc(&tmH, CU_TENSOR_MAP_DATA_TYPE_BFLOAT16, 3, hp, gd, gs, bx, es, CU_TENSOR_MAP_INTERLEAVE_NONE, CU_TENSOR_MAP_SWIZZLE_128B,
        CU_TENSOR_MAP_L2_PROMOTION_NONE, CU_TENSOR_MAP_FLOAT_OOB_FILL_NONE);
  }
  for (int w = 0; w < 2; w++) {
    const cuuint64_t M = w ? S_ : F_, K = w ? F_ : S_;
    cuuint64_t gd[3] = {64, K, M / 64};
    cuuint64_t gs[2] = {M * 2, 128};
    cuuint32_t bx[3] = {64, 64, 2};
    cuuint32_t es[3] = {1, 1, 1};
    enc(w ? &tmW2 : &tmW1, CU_TENSOR_MAP_DATA_TYPE_BFLOAT16, 3, d_in[w ? 9 : 7], gd, gs, bx, es, CU_TENSOR_MAP_INTERLEAVE_NONE,
        CU_TENSOR_MAP_SWIZZLE_128B, CU_TENSOR_MAP_L2_PROMOTION_L2_256B, CU_TENSOR_MAP_FLOAT_OOB_FILL_NONE);
  }
  {
    cuuint64_t gd[2] = {S_, D_};
    cuuint64_t gs[1] = {S_ * 2};
    cuuint32_t bx[2] = {64, 72};
    cuuint32_t es[2] = {1, 1};
    enc(&tmZ, CU_TENSOR_MAP_DATA_TYPE_BFLOAT16, 2, zp, gd, gs, bx, es, CU_TENSOR_MAP_INTERLEAVE_NONE, CU_TENSOR_MAP_SWIZZLE_128B,
        CU_TENSOR_MAP_L2_PROMOTION_L2_256B, CU_TENSOR_MAP_FLOAT_OOB_FILL_NONE);
  }
  RoleMap roles;
  for (int k = 0; k < NCTA / 2; k++) roles.role[k] = role_of_cluster(k);
  cudaFuncSetAttribute(fused_kernel, cudaFuncAttributeMaxDynamicSharedMemorySize, SMEM_BYTES);
  fused_kernel<<<NCTA, 384, SMEM_BYTES>>>(tmW1, tmW2, tmZ, tmH, tmK, tmV, tmKV, roles, (const __nv_bfloat16*)d_in[0],
                                          (const __nv_bfloat16*)d_in[3], (const __nv_bfloat16*)d_in[4],
                                          (const __nv_bfloat16*)d_in[5], (const __nv_bfloat16*)d_in[8], (const __nv_bfloat16*)d_in[10],
                                          (__nv_bfloat16*)d_out);
}
```

```cpp
#include <cuda_runtime.h>
#include <cuda_bf16.h>
#include <cuda.h>
#include <stdint.h>

namespace {

constexpr int S_ = 2048, D_ = 576, F_ = 4608;
constexpr int NCTA = 132, NG2 = 128, NCONV = 6;
constexpr int ST = 5, ASZ = 16384, PITCH_S = ASZ + 144 * 128, PITCH_B = ASZ + 192 * 128;
constexpr int KVIN = (36 + 33) * 128, KVW = 2 * KVIN + 64 * 176;
constexpr int BAR_OFF = ST * PITCH_S + 2 * KVW;
constexpr int SMEM_BYTES = BAR_OFF + 512;
constexpr int KVROWS = 16, LNROT = 120;
constexpr int SKEW = 1;
constexpr int LEAD_S = 3, LEAD_B = 2;
constexpr int CTURN = 14, CPER = 4, CEARLY = 0, CFENCE = 8;
constexpr int TURN = 2;
constexpr int XAT = 12;
constexpr int LAG = 4;
constexpr int CBUF = 14464, CH_OFF = 128, CT_OFF = 4224, KVT = 10240;
constexpr int CSTG_OFF = ST * PITCH_S + 3 * CBUF;
constexpr uint32_t SPIN_LIMIT = 1u << 22;

constexpr int FL_H = 0, FL_U = 32, FL_KV = 38, FL_Z = 41, FL_GATE = 42, FL_DONE = 43, FL_N = 44;
struct Scratch {
  uint32_t flags[64 * 32];
  uint4 stats[S_];
  uint8_t h[32 * 72 * 1024];
  uint8_t u[72 * D_ * 128];
  uint8_t kv[D_ * KVT];
  __nv_bfloat16 z[D_ * S_];
};
__device__ __align__(1024) Scratch g_scratch;
extern __shared__ __align__(1024) uint8_t smem_raw[];
#define TUNABLES(X) X(W9, 1200) X(QLATE, 20) X(QDELAY, 400) X(QRAMP, 5) X(A0, 1200) X(AD, 300) X(AN, 5) X(AL, 0) X(H0, 3500) X(HD, 400) X(KVGAP, 100) X(KVSTAG, 1200) X(KVGO, 6) X(CVGO, 31) X(GDELAY, 608) X(GDELAY1, 256) X(ZDELAY, 3000) X(ZRAMP, 40) X(NPF, 0) X(PFGAP, 600)
#define X(k, v) constexpr int T_##k = v;
TUNABLES(X)
#undef X
#define TN(k) T_##k
struct RoleMap { uint32_t role[NCTA / 2]; uint32_t by_sm; };
#define PROF(i) do {} while (0)
#define PROFG(i) do {} while (0)
#define PROFC(i) do {} while (0)

template<int TB> __device__ __forceinline__ void wgmma_ss(float (&d)[96], uint32_t da, uint32_t db, int sd) {
  asm volatile("{\n.reg .pred p;\n.reg .b64 a, b;\nsetp.ne.b32 p, %98, 0;\nmov.b64 a, {%96, %100};\nmov.b64 b, {%97, %101};\n"
    "wgmma.mma_async.sync.aligned.m64n192k16.f32.bf16.bf16 {%0, %1, %2, %3, %4, %5, %6, %7, %8, %9, %10, %11, %12, %13, %14, %15, %16, %17, %18, %19, %20, %21, %22, %23, %24, %25, %26, %27, %28, %29, %30, %31, %32, %33, %34, %35, %36, %37, %38, %39, %40, %41, %42, %43, %44, %45, %46, %47, %48, %49, %50, %51, %52, %53, %54, %55, %56, %57, %58, %59, %60, %61, %62, %63, %64, %65, %66, %67, %68, %69, %70, %71, %72, %73, %74, %75, %76, %77, %78, %79, %80, %81, %82, %83, %84, %85, %86, %87, %88, %89, %90, %91, %92, %93, %94, %95}, a, b, p, 1, 1, 1, %99;\n}\n"
    : "+f"(d[0]), "+f"(d[1]), "+f"(d[2]), "+f"(d[3]), "+f"(d[4]), "+f"(d[5]), "+f"(d[6]), "+f"(d[7]), "+f"(d[8]), "+f"(d[9]), "+f"(d[10]), "+f"(d[11]), "+f"(d[12]), "+f"(d[13]), "+f"(d[14]), "+f"(d[15]), "+f"(d[16]), "+f"(d[17]), "+f"(d[18]), "+f"(d[19]), "+f"(d[20]), "+f"(d[21]), "+f"(d[22]), "+f"(d[23]), "+f"(d[24]), "+f"(d[25]), "+f"(d[26]), "+f"(d[27]), "+f"(d[28]), "+f"(d[29]), "+f"(d[30]), "+f"(d[31]), "+f"(d[32]), "+f"(d[33]), "+f"(d[34]), "+f"(d[35]), "+f"(d[36]), "+f"(d[37]), "+f"(d[38]), "+f"(d[39]), "+f"(d[40]), "+f"(d[41]), "+f"(d[42]), "+f"(d[43]), "+f"(d[44]), "+f"(d[45]), "+f"(d[46]), "+f"(d[47]), "+f"(d[48]), "+f"(d[49]), "+f"(d[50]), "+f"(d[51]), "+f"(d[52]), "+f"(d[53]), "+f"(d[54]), "+f"(d[55]), "+f"(d[56]), "+f"(d[57]), "+f"(d[58]), "+f"(d[59]), "+f"(d[60]), "+f"(d[61]), "+f"(d[62]), "+f"(d[63]), "+f"(d[64]), "+f"(d[65]), "+f"(d[66]), "+f"(d[67]), "+f"(d[68]), "+f"(d[69]), "+f"(d[70]), "+f"(d[71]), "+f"(d[72]), "+f"(d[73]), "+f"(d[74]), "+f"(d[75]), "+f"(d[76]), "+f"(d[77]), "+f"(d[78]), "+f"(d[79]), "+f"(d[80]), "+f"(d[81]), "+f"(d[82]), "+f"(d[83]), "+f"(d[84]), "+f"(d[85]), "+f"(d[86]), "+f"(d[87]), "+f"(d[88]), "+f"(d[89]), "+f"(d[90]), "+f"(d[91]), "+f"(d[92]), "+f"(d[93]), "+f"(d[94]), "+f"(d[95])
    : "r"(da), "r"(db), "r"(sd), "n"(TB), "r"(0x40000040u), "r"(TB ? 0x40u : 0x40000040u));
}
template<int TB> __device__ __forceinline__ void wgmma_ss(float (&d)[72], uint32_t da, uint32_t db, int sd) {
  asm volatile("{\n.reg .pred p;\n.reg .b64 a, b;\nsetp.ne.b32 p, %74, 0;\nmov.b64 a, {%72, %76};\nmov.b64 b, {%73, %77};\n"
    "wgmma.mma_async.sync.aligned.m64n144k16.f32.bf16.bf16 {%0, %1, %2, %3, %4, %5, %6, %7, %8, %9, %10, %11, %12, %13, %14, %15, %16, %17, %18, %19, %20, %21, %22, %23, %24, %25, %26, %27, %28, %29, %30, %31, %32, %33, %34, %35, %36, %37, %38, %39, %40, %41, %42, %43, %44, %45, %46, %47, %48, %49, %50, %51, %52, %53, %54, %55, %56, %57, %58, %59, %60, %61, %62, %63, %64, %65, %66, %67, %68, %69, %70, %71}, a, b, p, 1, 1, 1, %75;\n}\n"
    : "+f"(d[0]), "+f"(d[1]), "+f"(d[2]), "+f"(d[3]), "+f"(d[4]), "+f"(d[5]), "+f"(d[6]), "+f"(d[7]), "+f"(d[8]), "+f"(d[9]), "+f"(d[10]), "+f"(d[11]), "+f"(d[12]), "+f"(d[13]), "+f"(d[14]), "+f"(d[15]), "+f"(d[16]), "+f"(d[17]), "+f"(d[18]), "+f"(d[19]), "+f"(d[20]), "+f"(d[21]), "+f"(d[22]), "+f"(d[23]), "+f"(d[24]), "+f"(d[25]), "+f"(d[26]), "+f"(d[27]), "+f"(d[28]), "+f"(d[29]), "+f"(d[30]), "+f"(d[31]), "+f"(d[32]), "+f"(d[33]), "+f"(d[34]), "+f"(d[35]), "+f"(d[36]), "+f"(d[37]), "+f"(d[38]), "+f"(d[39]), "+f"(d[40]), "+f"(d[41]), "+f"(d[42]), "+f"(d[43]), "+f"(d[44]), "+f"(d[45]), "+f"(d[46]), "+f"(d[47]), "+f"(d[48]), "+f"(d[49]), "+f"(d[50]), "+f"(d[51]), "+f"(d[52]), "+f"(d[53]), "+f"(d[54]), "+f"(d[55]), "+f"(d[56]), "+f"(d[57]), "+f"(d[58]), "+f"(d[59]), "+f"(d[60]), "+f"(d[61]), "+f"(d[62]), "+f"(d[63]), "+f"(d[64]), "+f"(d[65]), "+f"(d[66]), "+f"(d[67]), "+f"(d[68]), "+f"(d[69]), "+f"(d[70]), "+f"(d[71])
    : "r"(da), "r"(db), "r"(sd), "n"(TB), "r"(0x40000040u), "r"(TB ? 0x40u : 0x40000040u));
}
template<int TB> __device__ __forceinline__ void wgmma_ss(float (&d)[36], uint32_t da, uint32_t db, int sd) {
  asm volatile("{\n.reg .pred p;\n.reg .b64 a, b;\nsetp.ne.b32 p, %38, 0;\nmov.b64 a, {%36, %40};\nmov.b64 b, {%37, %41};\n"
    "wgmma.mma_async.sync.aligned.m64n72k16.f32.bf16.bf16 {%0, %1, %2, %3, %4, %5, %6, %7, %8, %9, %10, %11, %12, %13, %14, %15, %16, %17, %18, %19, %20, %21, %22, %23, %24, %25, %26, %27, %28, %29, %30, %31, %32, %33, %34, %35}, a, b, p, 1, 1, 1, %39;\n}\n"
    : "+f"(d[0]), "+f"(d[1]), "+f"(d[2]), "+f"(d[3]), "+f"(d[4]), "+f"(d[5]), "+f"(d[6]), "+f"(d[7]), "+f"(d[8]), "+f"(d[9]), "+f"(d[10]), "+f"(d[11]), "+f"(d[12]), "+f"(d[13]), "+f"(d[14]), "+f"(d[15]), "+f"(d[16]), "+f"(d[17]), "+f"(d[18]), "+f"(d[19]), "+f"(d[20]), "+f"(d[21]), "+f"(d[22]), "+f"(d[23]), "+f"(d[24]), "+f"(d[25]), "+f"(d[26]), "+f"(d[27]), "+f"(d[28]), "+f"(d[29]), "+f"(d[30]), "+f"(d[31]), "+f"(d[32]), "+f"(d[33]), "+f"(d[34]), "+f"(d[35])
    : "r"(da), "r"(db), "r"(sd), "n"(TB), "r"(0x40000040u), "r"(TB ? 0x40u : 0x40000040u));
}
__device__ __forceinline__ void wgmma_rs_n32(float (&d)[16], uint32_t a0, uint32_t a1, uint32_t a2, uint32_t a3, uint64_t db, int sd) {
  asm volatile("{\n.reg .pred p;\nsetp.ne.b32 p, %21, 0;\n"
    "wgmma.mma_async.sync.aligned.m64n32k16.f32.bf16.bf16 {%0, %1, %2, %3, %4, %5, %6, %7, %8, %9, %10, %11, %12, %13, %14, %15}, {%16, %17, %18, %19}, %20, p, 1, 1, 0;\n}\n"
    : "+f"(d[0]), "+f"(d[1]), "+f"(d[2]), "+f"(d[3]), "+f"(d[4]), "+f"(d[5]), "+f"(d[6]), "+f"(d[7]), "+f"(d[8]), "+f"(d[9]), "+f"(d[10]), "+f"(d[11]), "+f"(d[12]), "+f"(d[13]), "+f"(d[14]), "+f"(d[15])
    : "r"(a0), "r"(a1), "r"(a2), "r"(a3), "l"(db), "r"(sd));
}

__device__ __forceinline__ void wg_fence() { asm volatile("wgmma.fence.sync.aligned;" ::: "memory"); }
__device__ __forceinline__ void wg_commit() { asm volatile("wgmma.commit_group.sync.aligned;" ::: "memory"); }
template <int n> __device__ __forceinline__ void wg_wait() { asm volatile("wgmma.wait_group.sync.aligned %0;" ::"n"(n) : "memory"); }
__device__ __forceinline__ uint64_t mkdesc(uint32_t addr, uint32_t lbo, uint32_t sbo, uint32_t sw) {
  return (uint64_t)((addr & 0x3FFFF) >> 4) | ((uint64_t)(lbo >> 4) << 16) | ((uint64_t)(sbo >> 4) << 32) | ((uint64_t)sw << 62);
}
__device__ __forceinline__ void mbar_init(uint32_t a, int c) { asm volatile("mbarrier.init.shared::cta.b64 [%0], %1;" ::"r"(a), "r"(c)); }
__device__ __forceinline__ void mbar_expect(uint32_t a, uint32_t b) { asm volatile("mbarrier.arrive.expect_tx.shared::cta.b64 _, [%0], %1;" ::"r"(a), "r"(b) : "memory"); }
__device__ __forceinline__ void mbar_arrive(uint32_t a) { asm volatile("mbarrier.arrive.shared::cta.b64 _, [%0];" ::"r"(a) : "memory"); }
__device__ __forceinline__ void mbar_arrive_cluster(uint32_t raddr) { asm volatile("mbarrier.arrive.shared::cluster.b64 _, [%0];" ::"r"(raddr) : "memory"); }
__device__ __forceinline__ uint32_t mapa(uint32_t a, uint32_t cta) { uint32_t r; asm("mapa.shared::cluster.u32 %0, %1, %2;" : "=r"(r) : "r"(a), "r"(cta)); return r; }
__device__ __forceinline__ void mbar_wait(uint32_t a, uint32_t ph) {
  asm volatile(
      "{\n.reg .pred p;\n.reg .u32 c;\nmov.u32 c, 0;\n"
      "WAIT_LOOP:\nmbarrier.try_wait.parity.shared::cta.b64 p, [%0], %1;\n@p bra WAIT_DONE;\n"
      "add.u32 c, c, 1;\nsetp.lt.u32 p, c, %2;\n@p bra WAIT_LOOP;\ntrap;\nWAIT_DONE:\n}" ::"r"(a), "r"(ph), "n"(SPIN_LIMIT) : "memory");
}
__device__ __forceinline__ void mbar_wait_u(uint32_t a, uint32_t ph) {
  asm volatile("{\n.reg .pred p;\nWAIT_LOOP:\nmbarrier.try_wait.parity.shared::cta.b64 p, [%0], %1;\n@!p bra WAIT_LOOP;\n}" ::"r"(a), "r"(ph) : "memory");
}
__device__ __forceinline__ uint32_t desc_lo(uint32_t addr, uint32_t lbo) { return ((addr & 0x3FFFF) >> 4) | ((lbo >> 4) << 16); }
__device__ __forceinline__ void tma2d(uint32_t dst, const CUtensorMap* m, int c0, int c1, uint32_t bar) {
  asm volatile("cp.async.bulk.tensor.2d.shared::cluster.global.mbarrier::complete_tx::bytes [%0], [%1, {%3, %4}], [%2];" ::"r"(dst), "l"(m), "r"(bar), "r"(c0), "r"(c1) : "memory");
}
__device__ __forceinline__ void bulk_g2s(uint32_t dst, const void* src, uint32_t sz, uint32_t bar) {
  asm volatile("cp.async.bulk.shared::cluster.global.mbarrier::complete_tx::bytes [%0], [%1], %2, [%3];" ::"r"(dst), "l"(src), "r"(sz), "r"(bar) : "memory");
}
__device__ __forceinline__ void bulk_s2g(void* dst, uint32_t src, uint32_t sz) {
  asm volatile("cp.async.bulk.global.shared::cta.bulk_group [%0], [%1], %2;" ::"l"(dst), "r"(src), "r"(sz) : "memory");
}
__device__ __forceinline__ uint64_t stream_policy() {
  uint64_t p;
  asm volatile("createpolicy.fractional.L2::evict_first.b64 %0, 1.0;" : "=l"(p));
  return p;
}
__device__ __forceinline__ void tma_weights(uint32_t dst, const CUtensorMap* m, int k0, int mchunk, uint32_t bar, uint64_t pol) {
  asm volatile("cp.async.bulk.tensor.3d.shared::cluster.global.mbarrier::complete_tx::bytes.L2::cache_hint [%0], [%1, {%6, %3, %4}], [%2], %5;"
               ::"r"(dst), "l"(m), "r"(bar), "r"(k0), "r"(mchunk), "l"(pol), "r"(0) : "memory");
}
__device__ __forceinline__ void tma_weights_prefetch(const CUtensorMap* m, int k0, int mchunk, uint64_t pol) {
  asm volatile("cp.async.bulk.prefetch.tensor.3d.L2.global.L2::cache_hint [%0, {%4, %1, %2}], %3;" ::"l"(m), "r"(k0), "r"(mchunk), "l"(pol), "r"(0) : "memory");
}
__device__ __forceinline__ bool elect_one() {
  uint32_t p;
  asm volatile("{\n.reg .pred P;\nelect.sync _|P, 0xffffffff;\nselp.u32 %0, 1, 0, P;\n}" : "=r"(p));
  return p;
}
__device__ __forceinline__ void bulk_g2s_stream(uint32_t dst, const void* src, uint32_t sz, uint32_t bar, uint64_t pol) {
  asm volatile("cp.async.bulk.shared::cluster.global.mbarrier::complete_tx::bytes.L2::cache_hint [%0], [%1], %2, [%3], %4;"
               ::"r"(dst), "l"(src), "r"(sz), "r"(bar), "l"(pol) : "memory");
}
__device__ __forceinline__ void tma3d_store(const CUtensorMap* m, int c1, int c2, uint32_t src) {
  asm volatile("cp.async.bulk.tensor.3d.global.shared::cta.bulk_group [%0, {%4, %2, %3}], [%1];" ::"l"(m), "r"(src), "r"(c1), "r"(c2), "r"(0) : "memory");
}
__device__ __forceinline__ void tma2d_stream(uint32_t dst, const CUtensorMap* m, int c0, int c1, uint32_t bar, uint64_t pol) {
  asm volatile("cp.async.bulk.tensor.2d.shared::cluster.global.mbarrier::complete_tx::bytes.L2::cache_hint [%0], [%1, {%3, %4}], [%2], %5;"
               ::"r"(dst), "l"(m), "r"(bar), "r"(c0), "r"(c1), "l"(pol) : "memory");
}
__device__ __forceinline__ void tma4d_store(const CUtensorMap* m, int c1, int c2, int c3, uint32_t src) {
  asm volatile("cp.async.bulk.tensor.4d.global.shared::cta.bulk_group [%0, {%5, %2, %3, %4}], [%1];" ::"l"(m), "r"(src), "r"(c1), "r"(c2), "r"(c3), "r"(0) : "memory");
}
__device__ __forceinline__ void bulk_commit() { asm volatile("cp.async.bulk.commit_group;" ::: "memory"); }
__device__ __forceinline__ void bulk_wait_all() { asm volatile("cp.async.bulk.wait_group 0;" ::: "memory"); }
__device__ __forceinline__ void fence_async_smem() { asm volatile("fence.proxy.async.shared::cta;" ::: "memory"); }
__device__ __forceinline__ void fence_async_global() { asm volatile("fence.proxy.async.global;" ::: "memory"); }
__device__ __forceinline__ void named_bar(int id, int n) { asm volatile("bar.sync %0, %1;" ::"r"(id), "r"(n) : "memory"); }
__device__ __forceinline__ void named_arrive(int id, int n) { asm volatile("bar.arrive %0, %1;" ::"r"(id), "r"(n) : "memory"); }
__device__ __forceinline__ void flag_add(uint32_t* f, int i, uint32_t v) { asm volatile("red.relaxed.gpu.global.add.u32 [%0], %1;" ::"l"(f + i * 32), "r"(v) : "memory"); }
__device__ __forceinline__ uint32_t flag_ld(uint32_t* f, int i) { uint32_t v; asm volatile("ld.relaxed.gpu.global.u32 %0, [%1];" : "=r"(v) : "l"(f + i * 32) : "memory"); return v; }
__device__ __forceinline__ void prefetch_map(const CUtensorMap* m) { asm volatile("prefetch.tensormap [%0];" ::"l"(m) : "memory"); }
__device__ __forceinline__ void stsm4_t(uint32_t a, uint32_t r0, uint32_t r1, uint32_t r2, uint32_t r3) {
  asm volatile("stmatrix.sync.aligned.m8n8.x4.trans.shared.b16 [%0], {%1, %2, %3, %4};" ::"r"(a), "r"(r0), "r"(r1), "r"(r2), "r"(r3) : "memory");
}
__device__ __forceinline__ uint32_t lds32(uint32_t a) { uint32_t v; asm volatile("ld.shared.u32 %0, [%1];" : "=r"(v) : "r"(a) : "memory"); return v; }
__device__ __forceinline__ void sts32(uint32_t a, uint32_t v) { asm volatile("st.shared.u32 [%0], %1;" ::"r"(a), "r"(v) : "memory"); }
__device__ __forceinline__ uint4 ld_l2(const uint4* p) { uint4 v; asm volatile("ld.relaxed.gpu.global.v4.u32 {%0, %1, %2, %3}, [%4];" : "=r"(v.x), "=r"(v.y), "=r"(v.z), "=r"(v.w) : "l"(p) : "memory"); return v; }
__device__ __forceinline__ void sts128(uint32_t a, uint32_t x, uint32_t y, uint32_t z, uint32_t w) { asm volatile("st.shared.v4.u32 [%0], {%1, %2, %3, %4};" ::"r"(a), "r"(x), "r"(y), "r"(z), "r"(w) : "memory"); }
__device__ __forceinline__ uint4 lds128(uint32_t a) { uint4 v; asm volatile("ld.shared.v4.u32 {%0, %1, %2, %3}, [%4];" : "=r"(v.x), "=r"(v.y), "=r"(v.z), "=r"(v.w) : "r"(a) : "memory"); return v; }
__device__ __forceinline__ void st_async4(uint32_t raddr, uint32_t a, uint32_t b, uint32_t c, uint32_t d, uint32_t rbar) {
  asm volatile("st.async.weak.shared::cluster.mbarrier::complete_tx::bytes.v4.b32 [%0], {%1, %2, %3, %4}, [%5];" ::"r"(raddr), "r"(a), "r"(b), "r"(c), "r"(d), "r"(rbar) : "memory");
}
__device__ __forceinline__ uint32_t pack_bf16(float lo, float hi) { uint32_t r; asm("cvt.rn.bf16x2.f32 %0, %1, %2;" : "=r"(r) : "f"(hi), "f"(lo)); return r; }
__device__ __forceinline__ float bf_lo(uint32_t v) { return __uint_as_float(v << 16); }
__device__ __forceinline__ float bf_hi(uint32_t v) { return __uint_as_float(v & 0xffff0000u); }
__device__ __forceinline__ float bf_round(float x) { return bf_lo(pack_bf16(x, 0.f)); }
__device__ __forceinline__ uint32_t hmul2(uint32_t a, uint32_t b) { uint32_t r; asm("mul.rn.bf16x2 %0, %1, %2;" : "=r"(r) : "r"(a), "r"(b)); return r; }
__device__ __forceinline__ uint32_t hsub2(uint32_t a, uint32_t b) { uint32_t r; asm("sub.rn.bf16x2 %0, %1, %2;" : "=r"(r) : "r"(a), "r"(b)); return r; }
__device__ __forceinline__ uint32_t hfma2(uint32_t a, uint32_t b, uint32_t c) { uint32_t r; asm("fma.rn.bf16x2 %0, %1, %2, %3;" : "=r"(r) : "r"(a), "r"(b), "r"(c)); return r; }
__device__ __forceinline__ uint4 ldg128(const void* p) { uint4 v; asm volatile("ld.global.nc.v4.u32 {%0, %1, %2, %3}, [%4];" : "=r"(v.x), "=r"(v.y), "=r"(v.z), "=r"(v.w) : "l"(p)); return v; }
__device__ __forceinline__ uint32_t ldg16(const void* p) { uint32_t v; asm volatile("ld.global.nc.u16 %0, [%1];" : "=r"(v) : "l"(p)); return v; }
__device__ __forceinline__ float tanh_ordered(float x) { float y; asm volatile("tanh.approx.f32 %0, %1;" : "=f"(y) : "f"(x)); return y; }
__device__ __forceinline__ void mma16816(float (&d)[4], uint32_t a0, uint32_t a1, uint32_t a2, uint32_t a3, uint32_t b0, uint32_t b1) {
  asm("mma.sync.aligned.m16n8k16.row.col.f32.bf16.bf16.f32 {%0, %1, %2, %3}, {%4, %5, %6, %7}, {%8, %9}, {%0, %1, %2, %3};"
      : "+f"(d[0]), "+f"(d[1]), "+f"(d[2]), "+f"(d[3]) : "r"(a0), "r"(a1), "r"(a2), "r"(a3), "r"(b0), "r"(b1));
}
__device__ __forceinline__ uint32_t hadd2(uint32_t a, uint32_t b) { uint32_t r; asm("add.rn.bf16x2 %0, %1, %2;" : "=r"(r) : "r"(a), "r"(b)); return r; }
__device__ __forceinline__ uint32_t ldg32(const void* p) { uint32_t v; asm volatile("ld.global.nc.L1::no_allocate.u32 %0, [%1];" : "=r"(v) : "l"(p)); return v; }
__device__ __forceinline__ uint2 lds64(uint32_t a) { uint2 v; asm volatile("ld.shared.v2.u32 {%0, %1}, [%2];" : "=r"(v.x), "=r"(v.y) : "r"(a) : "memory"); return v; }
__device__ __forceinline__ uint32_t lds32_if(uint32_t a, uint32_t on) {
  uint32_t v;
  asm volatile("{\n.reg .pred p;\nsetp.ne.u32 p, %2, 0;\n@p ld.shared.u32 %0, [%1];\n}" : "=r"(v) : "r"(a), "r"(on) : "memory");
  return v;
}
__device__ __forceinline__ uint32_t clock_now() { uint32_t t; asm volatile("mov.u32 %0, %%clock;" : "=r"(t)); return t; }
__device__ __forceinline__ uint32_t time_now() { uint32_t t; asm volatile("mov.u32 %0, %%globaltimer_lo;" : "=r"(t)); return t; }
__device__ __forceinline__ void spin_until(uint32_t t0, uint32_t n) { while (clock_now() - t0 < n) {} }
__device__ __forceinline__ uint2 ldg64_if(const void* p, uint32_t on) {
  uint2 v;
  asm volatile("{\n.reg .pred p;\nsetp.ne.u32 p, %3, 0;\n@p ld.global.nc.v2.u32 {%0, %1}, [%2];\n}" : "=r"(v.x), "=r"(v.y) : "l"(p), "r"(on));
  return v;
}
template <class T> __device__ __forceinline__ T pin(T v) { asm volatile("" : "+r"(v)); return v; }
__device__ __forceinline__ void st_async2(uint32_t raddr, uint32_t a, uint32_t b, uint32_t rbar) {
  asm volatile("st.async.weak.shared::cluster.mbarrier::complete_tx::bytes.v2.b32 [%0], {%1, %2}, [%3];" ::"r"(raddr), "r"(a), "r"(b), "r"(rbar) : "memory");
}
__device__ __forceinline__ void bulk_prefetch(const void* src, uint32_t sz, uint64_t pol) {
  asm volatile("cp.async.bulk.prefetch.L2.global.L2::cache_hint [%0], %1, %2;" ::"l"(src), "r"(sz), "l"(pol) : "memory");
}
__device__ __forceinline__ void bulk_wait_read() { asm volatile("cp.async.bulk.wait_group.read 0;" ::: "memory"); }
__device__ __forceinline__ uint32_t shfl_ordered(uint32_t v, int src) { uint32_t r; asm volatile("shfl.sync.idx.b32 %0, %1, %2, 0x1f, 0xffffffff;" : "=r"(r) : "r"(v), "r"(src)); return r; }
__device__ __forceinline__ int chan_pos(int d) {
  return d < 512 ? 72 * (d >> 6) + ((d & 33) | ((d & 6) << 2) | ((d >> 2) & 6)) : 72 * ((d - 512) >> 3) + 64 + (d & 7);
}

struct Ring {
  uint32_t s, ph;
  __device__ __forceinline__ void next() { if (++s == ST) { s = 0; ph ^= 1; } }
};
constexpr int B_FULL = 0, B_GO = 40, B_CFULL = 48, B_SEMPTY = 80, B_ZFULL = 96, B_RFULL = 104, B_UDONE = 120, B_KFULL = 136, B_RAW = 168, B_CVGO = 248, B_PEER = 256, B_G2GO = 264,
              B_EMPTY = 280, B_KVGO = 320, B_G1DONE = 328,
              B_CEMPTY = 336, B_SFULL = 368, B_USTG = 384, B_END = 400;

__device__ __forceinline__ void poll_once(uint32_t* f, uint32_t& ready, int idx, uint32_t want, bool active) {
  bool ok = false;
  if (active) ok = flag_ld(f, idx) == want;
  const uint32_t seen = __ballot_sync(0xffffffffu, ok);
  if (seen & ~ready) fence_async_global();
  ready |= seen;
}
__device__ __forceinline__ void poll_bits(uint32_t* f, uint32_t& ready, uint32_t bits, int idx, uint32_t want, bool active) {
  for (uint32_t spins = 0; (ready & bits) != bits; spins++) {
    poll_once(f, ready, idx, want, active);
    if (spins > SPIN_LIMIT) asm volatile("trap;");
  }
}
__device__ __forceinline__ void wait_counter(uint32_t* f, int idx, uint32_t want, uint32_t first, uint32_t nap) {
#pragma unroll 1
  for (uint32_t spins = 0; first != want; spins++) {
    if (spins) __nanosleep(nap);
    first = flag_ld(f, idx);
    if (spins > SPIN_LIMIT) asm volatile("trap;");
  }
  fence_async_global();
}

__device__ __forceinline__ void gate_arrive(uint32_t* f, uint32_t back) {
  asm volatile("red.relaxed.gpu.global.max.u32 [%0], %1;" ::"l"(f + FL_GATE * 32 + 1), "r"(time_now() - back) : "memory");
  flag_add(f, FL_GATE, 1);
}

__device__ __forceinline__ float ln_rinv(float var) {
  float rt, rinv;
  asm("sqrt.approx.ftz.f32 %0, %1;" : "=f"(rt) : "f"(bf_round(bf_round(var) + 1e-5f)));
  asm("rcp.approx.ftz.f32 %0, %1;" : "=f"(rinv) : "f"(bf_round(rt)));
  return rinv;
}
__device__ __forceinline__ uint32_t ln_apply(uint32_t x, const uint4& st) {
  const uint32_t d = hsub2(x, st.x);
  return hfma2(d, st.y, hmul2(d, st.z));
}

__device__ __forceinline__ void polling_done(uint32_t* f, int lane) {
  unsigned old = 0;
  if (lane == 0) asm volatile("atom.relaxed.gpu.global.add.u32 %0, [%1], 1;" : "=r"(old) : "l"(f + FL_DONE * 32) : "memory");
  old = __shfl_sync(0xffffffffu, old, 0);
  if (old == NCTA + NG2 - 1) {
#pragma unroll 1
    for (int i = lane; i < FL_N; i += 32) *(uint2*)(f + i * 32) = make_uint2(0u, 0u);
  }
}

struct Pipe { Ring r; uint32_t prev; bool pending; int cnt; };
__device__ __forceinline__ void pipe_drain(Pipe& p, uint32_t bars, bool leader) {
  wg_wait<0>();
  if (leader) mbar_arrive(bars + B_EMPTY + p.prev * 8);
  p.pending = false;
}
template <int TB, int LEAD, int R>
__device__ __forceinline__ void gemm_run(float (&acc)[R], int n, int accumulate, Pipe& p, uint32_t sb, uint32_t pitch, int wg, bool leader) {
  const uint32_t bars = sb + BAR_OFF;
  const uint32_t dA0 = desc_lo(sb + wg * 8192, 8192), dB0 = desc_lo(sb + ASZ, TB ? 128 : 16);
  constexpr int KB_STEP = TB ? 16 : 2;
#pragma unroll 1
  for (int kb = 0; kb < n; kb++) {
    if (LEAD && kb == n - LEAD && wg == 1) { if (TB) pipe_drain(p, bars, leader); named_bar(8, 256); }
    mbar_wait(bars + B_FULL + p.r.s * 8, p.r.ph);
    if (kb == 0 && !accumulate && threadIdx.x == 0) { PROF(21 + TB); PROFC(49 - 2 * TB); }
    const uint32_t dA = dA0 + p.r.s * (pitch >> 4), dB = dB0 + p.r.s * (pitch >> 4);
    wg_fence();
    wgmma_ss<TB>(acc, dA, dB, accumulate | kb);
#pragma unroll
    for (int k = 1; k < 4; k++) wgmma_ss<TB>(acc, dA + k * 128, dB + k * KB_STEP, 1);
    wg_commit();
    wg_wait<1>();
    if (p.pending && leader) mbar_arrive(bars + B_EMPTY + p.prev * 8);
    p.pending = true;
    p.prev = p.r.s;
    p.r.next();
  }
  if (LEAD && wg == 0) named_arrive(8, 256);
}

template <int BROW0>
__device__ __forceinline__ void gemm2_part(float (&c)[36], uint32_t sb, uint32_t pitch, int wg) {
  const uint32_t dA0 = desc_lo(sb + wg * 8192, 8192), dB0 = desc_lo(sb + ASZ + BROW0 * 128, 16);
  wg_fence();
#pragma unroll
  for (int i = 0; i < 4 * LAG; i++) {
    const int step = 68 - LAG + (i >> 2);
    if ((i & 3) == 0 && BROW0 == 0) mbar_wait_u(sb + BAR_OFF + B_FULL + (step % ST) * 8, (step / ST) & 1);
    if (i == 4 * LAG - TURN && BROW0 && wg == 0) named_arrive(7, 256);
    wgmma_ss<0>(c, dA0 + (step % ST) * (pitch >> 4) + (i & 3) * 128, dB0 + (step % ST) * (pitch >> 4) + (i & 3) * 2, 1);
  }
  wg_commit();
}
__device__ __forceinline__ void split_acc(const float (&acc)[72], float (&a)[36], float (&b)[36]) {
#pragma unroll
  for (int i = 0; i < 36; i++) { asm volatile("mov.b32 %0, %1;" : "=f"(a[i]) : "f"(acc[i])); asm volatile("mov.b32 %0, %1;" : "=f"(b[i]) : "f"(acc[36 + i])); }
}
template <int NV, int R, class Slice>
__device__ __forceinline__ void gelu_store(const float (&acc)[R], uint32_t bias0, uint32_t bias1, uint32_t sa, Slice slice) {
  const float hbias0 = 0.5f * bf_lo(pin(bias0)), hbias1 = 0.5f * bf_lo(pin(bias1));
  float hx[2][4], t[2][4], half = 0.5f;
  uint32_t pk[4];
#pragma unroll
  for (int j = 0; j <= NV / 4; j++) {
    if (j < NV / 4) {
      if (j >= 2) half = fmaf(t[j & 1][1], 0.f, 0.5f);
#pragma unroll
      for (int u = 0; u < 4; u++) {
        hx[j & 1][u] = fmaf(acc[4 * j + u], half, (u & 2) ? hbias1 : hbias0);
        t[j & 1][u] = tanh_ordered(hx[j & 1][u] * fmaf(hx[j & 1][u] * hx[j & 1][u], 0.2854192651f, 1.5957691216f));
      }
    }
    if (j > 0) {
      const float *hh = hx[(j - 1) & 1], *tt = t[(j - 1) & 1];
      pk[2 * ((j - 1) & 1)] = pack_bf16(fmaf(hh[0], tt[0], hh[0]), fmaf(hh[1], tt[1], hh[1]));
      pk[2 * ((j - 1) & 1) + 1] = pack_bf16(fmaf(hh[2], tt[2], hh[2]), fmaf(hh[3], tt[3], hh[3]));
      if (!(j & 1)) { stsm4_t(sa + (j - 2) * 1024, pk[0], pk[1], pk[2], pk[3]); slice(j / 2 - 1); }
    }
  }
}
struct Role { int half, kind, g2_m, dt, g1_mt, g1_nt, cs; uint32_t pitch; };
__device__ __forceinline__ Role get_role(const RoleMap& roles) {
  uint32_t b, sm;
  asm volatile("mov.u32 %0, %%ctaid.x;" : "=r"(b));
  asm volatile("mov.u32 %0, %%smid;" : "=r"(sm));
  const uint32_t w = roles.role[(roles.by_sm ? sm : b) >> 1];
  const int half = b & 1, kind = w & 3, m = (w >> 4) & 15, dt = (w >> 2) & 3;
  return Role{half, kind, m * 128, dt, half * 18 + (int)((w >> 8) & 31), (int)(w >> 16), (m * 4 + dt) * 2 + half, kind ? (uint32_t)PITCH_B : (uint32_t)PITCH_S};
}
__device__ __forceinline__ int g2_block(int half, int j) { return half * 36 + (j < 12 ? 2 * j : j < 24 ? 2 * j - 23 : j); }
__device__ __forceinline__ int conv_chan(int cs, int i) { return (3 * (cs >> 5) + (i >> 1)) * 64 + ((2 * cs) & 63) + (i & 1); }
__device__ __forceinline__ uint32_t conv_buf(uint32_t sb, int b) { return sb + (b == 3 ? (36 % ST) * PITCH_S : ST * PITCH_S + b * CBUF); }

__global__ void __cluster_dims__(2, 1, 1) __launch_bounds__(384, 1)
fused_kernel(const __nv_bfloat16* __restrict__ q, Scratch* __restrict__ gs, const __nv_bfloat16* __restrict__ b1,
             const __nv_bfloat16* __restrict__ shiftk, const __nv_bfloat16* __restrict__ ssmk, const __nv_bfloat16* __restrict__ ssmD,
             const __grid_constant__ CUtensorMap tmW1, const __grid_constant__ CUtensorMap tmW2, const __grid_constant__ CUtensorMap tmZ,
             const __grid_constant__ CUtensorMap tmH, const __grid_constant__ CUtensorMap tmK, const __grid_constant__ CUtensorMap tmV,
             const __grid_constant__ CUtensorMap tmKV, const __grid_constant__ RoleMap roles, const __nv_bfloat16* __restrict__ b2,
             __nv_bfloat16* __restrict__ out) {
  const int cta = blockIdx.x;
  const int tid = threadIdx.x;
  if (tid == 288) PROFG(0);

  const uint32_t t_start = clock_now();
  if (tid == 256) { prefetch_map(&tmW1); prefetch_map(&tmH); }
  const int lc = (cta + LNROT) & 127;
  const uint32_t do_ln = cta < 128 && tid < 256;
  const int ln_row = lc * 16 + ((tid >> 4) & 15), l16 = tid & 15;
  uint2 xr[9];
  if (do_ln && lc >= TN(QLATE)) spin_until(t_start, TN(QDELAY) + TN(QRAMP) * lc);
#pragma unroll
  for (int i = 0; i < 9; i++) xr[i] = ldg64_if(q + (size_t)ln_row * D_ + i * 64 + l16 * 4, do_ln);
  if (tid == 0) PROF(32);
  const int warp = __shfl_sync(0xffffffffu, tid >> 5, 0);
  const uint32_t sb = __shfl_sync(0xffffffffu, (uint32_t)__cvta_generic_to_shared(smem_raw), 0);
  const uint32_t bars = sb + BAR_OFF;
  const int lane = tid & 31;
  const int wg = warp >> 2;
  constexpr int LN_OFF = ST * PITCH_B;

  if (warp < 8 || warp == 11) {
    asm volatile("barrier.cluster.arrive.relaxed.aligned;" ::: "memory");
    const int hq = (lane & 16) >> 3, hb = (lane & 16) + hq;
    float da[3][4] = {};
#pragma unroll
    for (int i = 0; i < 9; i++) mma16816(da[i % 3], xr[i].x, 0x3f803f80u, xr[i].y, 0x3f803f80u, xr[i].x, xr[i].y);
    const float r1 = ((da[0][2] + da[0][3]) + (da[1][2] + da[1][3])) + (da[2][2] + da[2][3]);
    const float r2 = (lane & 4) ? (da[0][1] + da[1][1]) + da[2][1] : (da[0][0] + da[1][0]) + da[2][0];
    const float s1 = __shfl_sync(0xffffffffu, r1, hq) + __shfl_sync(0xffffffffu, r1, hq + 1);
    const float s2 = (__shfl_sync(0xffffffffu, r2, hb) + __shfl_sync(0xffffffffu, r2, hb + 4)) + (__shfl_sync(0xffffffffu, r2, hb + 9) + __shfl_sync(0xffffffffu, r2, hb + 13));
    if (tid == 0) { asm volatile("" ::"f"(s2) : "memory"); PROF(27); }
    const float mean = s1 * (1.f / D_), var = fmaxf(fmaf(-mean, mean, s2 * (1.f / D_)), 0.f);
    const float rinv = ln_rinv(var), rinv2 = ln_rinv(var * rinv * rinv), scale = rinv * rinv2, shift = -bf_round((mean - bf_round(mean)) * rinv) * rinv2;
    const uint32_t m2 = pack_bf16(mean, mean), hi2 = pack_bf16(scale, scale), lo2 = pack_bf16(scale - bf_lo(hi2), scale - bf_lo(hi2)), sh2 = pack_bf16(shift, shift);
    const uint32_t hi1 = pack_bf16(rinv, rinv);
    asm volatile("{\n.reg .pred p;\nsetp.eq.u32 p, %5, 0;\n@p st.shared.v4.u32 [%0], {%1, %2, %3, %4};\n}" ::"r"(sb + LN_OFF + 18432 + tid), "r"(m2), "r"(hi1),
                 "r"(pack_bf16(rinv - bf_lo(hi1), rinv - bf_lo(hi1))), "r"(0u), "r"(tid & 0x10f) : "memory");
    const uint32_t g0 = 4 * (l16 >> 3) + 2 * (l16 & 1), hrow = sb + LN_OFF + ((tid >> 7) & 1) * 9216 + (tid & 0x70);
    const uint32_t hs0 = hrow + g0 * 128 + ((l16 >> 1) & 3) * 4, hs8 = ((hrow + (l16 >> 1) * 1152) ^ ((l16 >> 1) << 4)) + 1024 + (l16 & 1) * 8;
    uint32_t w[18];
#pragma unroll
    for (int i = 0; i < 18; i++) {
      const uint32_t d = hsub2((i & 1) ? xr[i >> 1].y : xr[i >> 1].x, m2);
      asm("max.u32 %0, %1, 1;" : "=r"(w[i]) : "r"(hfma2(d, hi2, hfma2(d, lo2, sh2))));
    }
#pragma unroll
    for (int i = 0; i < 16; i++) {
      const int gi = 9 * (i >> 1) + (i & 1);
      asm volatile("{\n.reg .pred p;\nsetp.ne.u32 p, %2, 0;\n@p st.shared.u32 [%0], %1;\n}" ::"r"((hs0 ^ ((g0 * 16 + (gi & 7) * 16) & 0x70)) + gi * 128), "r"(w[i]), "r"(do_ln) : "memory");
    }
    asm volatile("{\n.reg .pred p;\nsetp.ne.u32 p, %3, 0;\n@p st.shared.v2.u32 [%0], {%1, %2};\n}" ::"r"(hs8), "r"(w[16]), "r"(w[17]), "r"(do_ln) : "memory");
    if (tid == 0) PROF(13);
    fence_async_smem();
    if (warp < 8) named_arrive(0, 288);
    else {
      named_bar(0, 288);
      if (cta < 128 && elect_one()) {
        tma3d_store(&tmH, (lc >> 2) * 72, (lc & 3) * 2, sb + LN_OFF);
        PROF(29);
        bulk_s2g(gs->stats + lc * 16, sb + LN_OFF + 18432, 256);
        bulk_commit();
      }
      __syncwarp();
    }
  } else if (warp != 8) {
    spin_until(t_start, TN(W9));
  }

  if (wg == 2) {
    asm volatile("setmaxnreg.dec.sync.aligned.u32 56;");
    if (warp != 11) {
      if (elect_one()) {
        if (warp == 8) {
#pragma unroll
          for (int o = 0; o < B_GO; o += 8) mbar_init(bars + o, 1);
        } else if (warp == 9) {
#pragma unroll
          for (int o = B_GO; o < B_RAW + 40; o += 8) mbar_init(bars + o, 1);
        } else {
#pragma unroll
          for (int o = B_RAW + 40; o < B_END; o += 8) mbar_init(bars + o, o < B_EMPTY ? 1 : o < B_CEMPTY ? 2 : 4);
        }
        asm volatile("fence.mbarrier_init.release.cluster;" ::: "memory");
      }
      __syncwarp();
      asm volatile("barrier.cluster.arrive.relaxed.aligned;" ::: "memory");
      if (warp == 9) { prefetch_map(&tmK); prefetch_map(&tmV); prefetch_map(&tmKV); prefetch_map(&tmW2); prefetch_map(&tmZ); }
      if (tid == 256) PROF(35);
    }
    const Role ro = get_role(roles);
    if (warp != 8) asm volatile("barrier.cluster.wait.aligned;" ::: "memory");
    if (warp == 11) {
      if (elect_one()) {
        bulk_wait_all();
        if (cta < 128) flag_add(gs->flags, FL_H + (lc >> 2), 1);
        mbar_arrive(bars + B_KVGO);
        PROFG(1);
      }
      __syncwarp();
      Ring r{0, 1};
      uint32_t ready = 0;
      const uint32_t bsz = ro.pitch - ASZ;
      const uint8_t* src = gs->h + ro.g1_nt * bsz + ST * 73728;
      named_bar(10, 64);
#pragma unroll 1
      for (int i = ST; i < 32; i++) {
        poll_bits(gs->flags, ready, i == 31 ? 0xffffffffu : 1u << i, FL_H + lane, 4u, true);
        mbar_wait(bars + B_EMPTY + r.s * 8, r.ph ^ 1);
        if (elect_one()) bulk_g2s(sb + r.s * ro.pitch + ASZ, src, bsz, bars + B_FULL + r.s * 8);
        if (i == ST && lane == 0) PROF(25);
        if (i == TN(KVGO) && lane == 0) mbar_arrive(bars + B_KVGO);
        if (i == TN(CVGO) && lane == 0) mbar_arrive(bars + B_CVGO);
        src += 73728;
        r.next();
      }
      if (ro.kind != 2) {
        uint32_t look = 0;
#pragma unroll 1
        for (int j = 0; j < 36; j++) {
          const uint8_t* su = gs->u + ((size_t)g2_block(ro.half, j) * D_ + ro.dt * 144) * 128;
          if (j == 0 || j == 12 || j == 24) wait_counter(gs->flags, FL_U + ro.half * 3 + j / 12, j == 24 ? 36u : 48u, look, 100);
          if (ro.kind ? j == 4 : j < 2) mbar_wait_u(bars + B_UDONE + (j ? 8 : 0), 0);
          mbar_wait(bars + B_EMPTY + r.s * 8, r.ph ^ 1);
          if (elect_one()) {
            bulk_g2s(sb + r.s * ro.pitch + ASZ, su + (ro.half ^ 1) * 9216, 9216, bars + B_FULL + r.s * 8);
            bulk_g2s(sb + r.s * ro.pitch + ASZ + 9216, su + ro.half * 9216, 9216, bars + B_FULL + r.s * 8);
          }
          if (j == 9 || j == 21) look = flag_ld(gs->flags, FL_U + ro.half * 3 + j / 12 + 1);
          if (j == 0 && lane == 0) PROF(8);
          r.next();
        }
#pragma unroll 1
        for (int o = lane; o < ST * 73728 / 16 / NG2; o += 32) ((uint4*)gs->h)[ro.cs * (ST * 73728 / 16 / NG2) + o] = make_uint4(0u, 0u, 0u, 0u);
      }
      polling_done(gs->flags, lane);
    } else if (warp == 8) {
      const uint64_t pol = stream_policy();
      Ring r{0, 0};
#pragma unroll 1
      for (int i = 0; i < 32; i++) {
        if (i < ST) spin_until(t_start, TN(A0) + i * TN(AD) + (i >= TN(AN) ? TN(AL) : 0));
        if (i == ST) {
          asm volatile("barrier.cluster.wait.aligned;" ::: "memory");
          if (roles.by_sm) {
            uint32_t sm;
            asm volatile("mov.u32 %0, %%smid;" : "=r"(sm));
            if (elect_one()) { mbar_expect(bars + B_PEER, 8); st_async2(mapa(bars + B_END, ro.half ^ 1), sm, sm, mapa(bars + B_PEER, ro.half ^ 1)); }
            mbar_wait_u(bars + B_PEER, 0);
            if ((lds32(bars + B_END) ^ sm) != 1 || sm >= NCTA) asm volatile("trap;");
          }
        }
        if (i >= ST) mbar_wait(bars + B_EMPTY + r.s * 8, r.ph ^ 1);
        if (elect_one()) {
          mbar_expect(bars + B_FULL + r.s * 8, ro.pitch);
          tma_weights(sb + r.s * ro.pitch, &tmW1, i * 64, ro.g1_mt * 2, bars + B_FULL + r.s * 8, pol);
        }
        r.next();
      }
      if (ro.kind != 2) {
#pragma unroll 1
        for (int j = 0; j < 36; j++) {
          if (j == 4) {
#pragma unroll 1
            for (int k = 0; k < TN(NPF); k++) {
              spin_until(clock_now(), TN(PFGAP));
              const int jj = 4 + 4 * k + ro.dt;
              if (elect_one() && jj < 36) tma_weights_prefetch(&tmW2, g2_block(ro.half, jj) * 64, ro.g2_m >> 6, pol);
            }
            if (ro.kind == 0) mbar_wait_u(bars + B_CEMPTY + 24, 0);
          }
          mbar_wait(bars + B_EMPTY + r.s * 8, r.ph ^ 1);
          if (elect_one()) {
            mbar_expect(bars + B_FULL + r.s * 8, PITCH_S);
            tma_weights(sb + r.s * ro.pitch, &tmW2, g2_block(ro.half, j) * 64, ro.g2_m >> 6, bars + B_FULL + r.s * 8, pol);
          }
          r.next();
        }
        if (lane < 2) mbar_expect(bars + B_RFULL + lane * 8, 9216);
        __syncwarp();
        mbar_wait(bars + B_EMPTY + r.s * 8, r.ph ^ 1);
        if (lane == 0) mbar_arrive_cluster(mapa(bars + B_GO, ro.half ^ 1));
      }
      if (lane == 0) PROF(28);
    } else {
      const uint64_t pol = stream_policy();
      {
        const uint32_t hb = (ro.pitch - ASZ) >> 1, raw = bars + B_RAW + (warp - 9) * 40, dst = sb + ASZ + (warp - 9) * hb;
        const uint8_t* src = gs->h + (2 * ro.g1_nt + warp - 9) * hb;
        auto fetch_h = [&](int i) { if (elect_one()) { mbar_expect(raw + i * 8, hb); bulk_g2s(dst + i * ro.pitch, src + i * 73728, hb, raw + i * 8); } };
        int next = 0;
#pragma unroll 1
        for (int i = -1; i < ST; i++) {
          if (i >= 0) {
#pragma unroll 1
            for (uint32_t tries = 0;; tries++) {
              mbar_wait_u(raw + i * 8, tries & 1);
              if (tid == 288 && i < 2) PROF(38 + i);
              const uint32_t pa = dst + i * ro.pitch + lane * 32 + (lane >> 2) * 4;
              uint32_t m = 1;
#pragma unroll
              for (int j = 0; j < 12; j++) m = min(m, lds32(pa + (j < 9 || ro.kind ? j : 0) * 1024));
              if (__all_sync(0xffffffffu, m)) break;
              if (lane == 0) PROF(26);
              fetch_h(i);
            }
            if (elect_one()) asm volatile("mbarrier.complete_tx.relaxed.cta.shared::cta.b64 [%0], %1;" ::"r"(bars + B_FULL + i * 8), "r"(hb) : "memory");
          }
#pragma unroll 1
          for (const int end = min(next + 2, ST); next < end; next++) {
            if (i < 0) spin_until(t_start, TN(H0) + next * TN(HD));
            fetch_h(next);
            if (next == 0 && tid == 288) PROF(3);
          }
          if (i < 0 && warp == 10) named_arrive(10, 64);
        }
      }
      if (ro.kind == 0) {
        mbar_wait_u(bars + B_KVGO, 0);
        const int cs = ro.cs, grp = (cs / 3) * 2 + warp - 9, cb0 = (cs % 3) * 3;
        const uint32_t kin_s = sb + ST * PITCH_S + (warp - 9) * KVW, kout = kin_s + 2 * KVIN + lane * 176, fb = bars + B_KFULL + (warp - 9) * 16;
        auto fetch = [&](int i) {
          if (elect_one()) {
            mbar_expect(fb + (i & 1) * 8, KVIN);
            tma2d_stream(kin_s + (i & 1) * KVIN, &tmK, (cb0 + i) * 64, grp * 32 - 4, fb + (i & 1) * 8, pol);
            tma2d_stream(kin_s + (i & 1) * KVIN + 4608, &tmV, (cb0 + i) * 64, grp * 32 - 1, fb + (i & 1) * 8, pol);
          }
        };
        if (warp == 10) spin_until(clock_now(), TN(KVSTAG));
        fetch(0);
        uint4 shk = ldg128(shiftk + (cb0 * 64 + lane * 2) * 4);
        const uint32_t dskip = ldg16(ssmD + conv_chan(cs, lane < NCONV ? lane : 0));
#pragma unroll 1
        for (int i = 0; i < 3; i++) {
          const uint32_t w0 = __byte_perm(shk.x, shk.z, 0x5410), w1 = __byte_perm(shk.x, shk.z, 0x7632);
          const uint32_t w2 = __byte_perm(shk.y, shk.w, 0x5410), w3 = __byte_perm(shk.y, shk.w, 0x7632);
          const uint32_t ka = kin_s + (i & 1) * KVIN + lane * 4;
          mbar_wait_u(fb + (i & 1) * 8, i >> 1);
          if (tid == 288 && i < 2) PROF(30 + i);
          if (i < 2) fetch(i + 1);
          shk = ldg128(i < 2 ? shiftk + ((cb0 + i + 1) * 64 + lane * 2) * 4 : ssmk + (size_t)conv_chan(cs, lane < NCONV ? lane : 0) * S_);
          uint32_t kr[20], x[17];
          auto rows = [&](uint32_t from, int j0) {
#pragma unroll
            for (int j = j0; j < j0 + 4; j++) { kr[j] = lds32(from + j * 128); if (j >= 3) x[j - 3] = lds32(from + 4608 + (j - 3) * 128); }
          };
          rows(ka, 0); rows(ka, 4); rows(ka, 8);
          x[0] = hmul2(hfma2(kr[3], w0, hfma2(kr[2], w1, hfma2(kr[1], w2, hmul2(kr[0], w3)))), x[0]);
          if (i) { if (elect_one()) bulk_wait_read(); __syncwarp(); }
#pragma unroll 1
          for (int o = 0; o < 4; o++) {
            const uint32_t from = ka + (o < 3 ? o : 2) * 1024, to = kout + o * 32;
#pragma unroll
            for (int m = 0; m < 8; m += 4) {
#pragma unroll
              for (int j = m + 1; j < m + 5; j++) x[j] = hmul2(hfma2(kr[j + 3], w0, hfma2(kr[j + 2], w1, hfma2(kr[j + 1], w2, hmul2(kr[j], w3)))), x[j]);
#pragma unroll
              for (int c = 0; c < 2; c++) {
                const uint32_t sel = c ? 0x7632 : 0x5410;
                const uint32_t a0 = __byte_perm(x[m + 1], x[m], sel), a1 = __byte_perm(x[m + 2], x[m + 1], sel);
                const uint32_t a2 = __byte_perm(x[m + 3], x[m + 2], sel), a3 = __byte_perm(x[m + 4], x[m + 3], sel);
                sts128(to + c * 5632 + m * 4, a0, a1, a2, a3);
                asm volatile("{\n.reg .pred p;\nsetp.eq.u32 p, %5, 3;\n@p st.shared.v4.u32 [%0], {%1, %2, %3, %4};\n}" ::"r"(to + c * 5632 + m * 4 + 32), "r"(a0), "r"(a1), "r"(a2), "r"(a3), "r"(o) : "memory");
              }
#pragma unroll
              for (int j = m + 12; j < m + 16; j++) { kr[j] = lds32_if(from + j * 128, o < 3); x[j - 3] = lds32_if(from + 4608 + (j - 3) * 128, o < 3); }
            }
#pragma unroll
            for (int j = 1; j < 12; j++) kr[j] = kr[j + 8];
#pragma unroll
            for (int j = 0; j < 9; j++) x[j] = x[j + 8];
          }
          fence_async_smem();
          __syncwarp();
          if (i && elect_one()) { bulk_wait_all(); flag_add(gs->flags, FL_KV + i - 1, 1); }
#pragma unroll 1
          for (int k = 0; k < 64 / KVROWS; k++) {
            if (k) spin_until(clock_now(), TN(KVGAP));
            if (elect_one()) { tma4d_store(&tmKV, (cb0 + i) * 32 + ((k * KVROWS) & 31), (k * KVROWS) >> 5, grp, kin_s + 2 * KVIN + k * KVROWS * 176); bulk_commit(); }
          }
        }
        shk.x = __byte_perm(pack_bf16(bf_lo(shk.x) + bf_lo(dskip), 0.f), shk.x, 0x7610);
        const uint32_t look = flag_ld(gs->flags, FL_KV + warp - 9);
        if (elect_one()) {
          bulk_wait_all();
          flag_add(gs->flags, FL_KV + 2, 1);
          bulk_prefetch(ssmk + (size_t)conv_chan(cs, 2 * (warp - 9)) * S_, 2 * S_ * 2, pol);
          if (warp == 9) PROFG(2);
        }
        __syncwarp();
#pragma unroll 1
        for (int i = warp == 9 ? 0 : 2; i < (warp == 9 ? 2 : NCONV); i++) {
          const int b = i & 3, d = conv_chan(cs, i);
          const uint32_t base = conv_buf(sb, b), cf = bars + B_CFULL + b * 8;
          if (!(i & 1)) wait_counter(gs->flags, FL_KV + (i >> 1), 192u, i < 4 ? look : 0u, 200);
          if (i == 0 || i == 2) mbar_wait_u(bars + B_CVGO, 0);
          if (i == 0 && lane == 0) PROF(23);
          if (i == 3) {
            mbar_wait_u(bars + B_G1DONE, 0);
            if (elect_one()) bulk_prefetch(ssmk + (size_t)conv_chan(cs, 4) * S_, 2 * S_ * 2, pol);
          }
          if (i >= 4) mbar_wait_u(bars + B_CEMPTY + b * 8, 0);
          if (lane == i) sts128(base + CH_OFF, shk.x, shk.y, shk.z, shk.w);
          if (lane >= 27) sts128(base + (lane >= 29 ? CH_OFF + (lane - 32) * 16 : CT_OFF + (lane - 27) * 16), 0u, 0u, 0u, 0u);
          fence_async_smem();
          __syncwarp();
          if (elect_one()) {
            mbar_expect(cf, 4080 + KVT - 32);
            bulk_g2s(base + CT_OFF + 32, gs->kv + (size_t)d * KVT, KVT - 32, cf);
            bulk_g2s_stream(base + CH_OFF + 16, ssmk + (size_t)d * S_ + 8, 4080, cf, pol);
          }
        }
      }
      if (warp == 9) {
        if (elect_one()) {
          const uint32_t bsz = ro.pitch - ASZ;
#pragma unroll 1
          for (int w = 0; w < 2; w++) {
            const uint32_t src = sb + (ro.kind ? (w ? (36 % ST) * PITCH_B + ASZ : ST * PITCH_B) : ((32 % ST) + w) * PITCH_S + ASZ);
            mbar_wait_u(bars + B_USTG + w * 8, 0);
            bulk_s2g(gs->u + (size_t)(2 * ro.g1_mt + w) * D_ * 128 + ro.g1_nt * bsz, src, bsz);
            bulk_commit();
            if (ro.kind && w == 0) gate_arrive(gs->flags, TN(GDELAY) - 512);
            bulk_wait_read();
            mbar_arrive(bars + B_UDONE + w * 8);
            bulk_wait_all();
            flag_add(gs->flags, FL_U + ro.half * 3 + (ro.kind ? 2 : w), 1);
            PROFG(5 + 12 * w);
          }
          if (ro.kind == 0) {
#pragma unroll 1
            for (int i = 0; i < NCONV; i++) {
              mbar_wait_u(bars + B_SFULL + (i & 1) * 8, (i >> 1) & 1);
              bulk_s2g(gs->z + (size_t)chan_pos(conv_chan(ro.cs, i)) * S_, sb + CSTG_OFF + (i & 1) * 4096, 4096);
              bulk_commit();
              if (i == NCONV - 3) gate_arrive(gs->flags, 0);
              bulk_wait_read();
              mbar_arrive(bars + B_SEMPTY + (i & 1) * 8);
            }
            bulk_wait_all();
            flag_add(gs->flags, FL_Z, 1);
            PROFG(6);
          }
        }
      } else if (ro.kind != 2) {
        mbar_wait_u(bars + B_UDONE, 0);
        uint2 gate;
#pragma unroll 1
        for (uint32_t spins = 0;; spins++) {
          asm volatile("ld.relaxed.gpu.global.v2.u32 {%0, %1}, [%2];" : "=r"(gate.x), "=r"(gate.y) : "l"(gs->flags + FL_GATE * 32) : "memory");
          if (gate.x == NCTA) break;
          __nanosleep(100);
          if (spins > SPIN_LIMIT) asm volatile("trap;");
        }
        if (lane == 0) PROF(46);
#pragma unroll 1
        for (int w = 0; w < 2; w++) {
          while (time_now() - gate.y < TN(GDELAY) + w * TN(GDELAY1)) {}
          if (lane == 0) mbar_arrive(bars + B_G2GO + w * 8);
          if (lane == 0 && w == 0) PROF(24);
        }
        wait_counter(gs->flags, FL_Z, 96u, 0, 300);
        spin_until(clock_now(), TN(ZDELAY) + TN(ZRAMP) * cta);
        if (elect_one()) {
          mbar_expect(bars + B_ZFULL, 18432);
          tma2d(sb + ST * ro.pitch, &tmZ, ro.g2_m, ro.dt * 144 + ro.half * 72, bars + B_ZFULL);
          tma2d(sb + ST * ro.pitch + 9216, &tmZ, ro.g2_m + 64, ro.dt * 144 + ro.half * 72, bars + B_ZFULL);
          PROFG(7);
        }
        polling_done(gs->flags, lane);
      }
    }
  } else {
    asm volatile("setmaxnreg.inc.sync.aligned.u32 224;");
    const int wi = warp & 3, g = lane >> 2, qd = lane & 3, wt = tid & 127;
    const bool leader = wt == 0;
    Pipe p{{0, 0}, 0, false, 0};
    asm volatile("barrier.cluster.wait.aligned;" ::: "memory");
    int kind;
    {
      const Role ro = get_role(roles);
      kind = ro.kind;
      const int f0 = ro.g1_mt * 128 + wg * 64 + wi * 16 + g;
      uint32_t bias0 = ldg16(b1 + f0), bias1 = ldg16(b1 + f0 + 8);
      const uint32_t so = ((lane >> 4) * 8 + (lane & 7)) * 128 + (((2 * wi + ((lane >> 3) & 1)) ^ (lane & 7)) << 4);
      if (kind) {
        float acc[96];
        gemm_run<1, LEAD_B>(acc, 32, 0, p, sb, PITCH_B, wg, leader);
        pipe_drain(p, bars, leader);
        if (wg) mbar_wait_u(bars + B_EMPTY + (36 % ST) * 8, ((36 / ST) & 1) ^ 1);
        if (leader) PROF(4 + 10 * wg);
        uint32_t sa = sb + (wg ? (36 % ST) * PITCH_B + ASZ : ST * PITCH_B) + so;
#pragma unroll 1
        for (int c = 0; c < 4; c++, sa += 6144) {
          gelu_store<24>(acc, bias0, bias1, sa, [](int) {});
#pragma unroll
          for (int i = 0; i < 72; i++) acc[i] = acc[i + 24];
        }
        fence_async_smem();
        __syncwarp();
        if (lane == 0) mbar_arrive(bars + B_USTG + wg * 8);
        if (leader) PROF(15 + wg);
      } else {
        const int cB = (g >> 1) & 1, cA = g >> 2, b = 2 * wi + (g & 1);
        const uint32_t toff = pin(CT_OFF + (40 * (2 * cA + cB) + 8 + b - 2 * qd) * 4);
        uint32_t a[16][4];
        auto load_a = [&](uint32_t base, int t, uint32_t on) {
          const uint32_t pt = base + toff + (t >> 1) * 1280 + (t & 1) * 64;
          a[t][0] = lds32_if(pt + 32, on); a[t][1] = lds32_if(pt + 672, on); a[t][2] = lds32_if(pt, on); a[t][3] = lds32_if(pt + 640, on);
        };
        {
          float acc[72];
          gemm_run<1, LEAD_S>(acc, 32, 0, p, sb, PITCH_S, wg, leader);
          if (wg == 1) named_arrive(6, 256);
          mbar_wait_u(bars + B_EMPTY + ((32 % ST) + wg) * 8, ((32 / ST) & 1) ^ 1);
          mbar_wait_u(bars + B_CFULL + wg * 8, 0);
          pipe_drain(p, bars, leader);
          if (leader) mbar_arrive(bars + B_G1DONE);
          if (leader) PROF(4 + 10 * wg);
          if (tid == 128) PROFC(48);
          gelu_store<72>(acc, bias0, bias1, sb + ((32 % ST) + wg) * PITCH_S + ASZ + so, [&](int t) { if (t < 8) load_a(conv_buf(sb, wg), t, 1); });
          fence_async_smem();
          __syncwarp();
          if (lane == 0) mbar_arrive(bars + B_USTG + wg * 8);
          if (leader) PROF(15 + wg);
        }
        const int phi = 2 * cA + (qd >> 1) + cB, pp = cB ? (phi & 3) : ((phi + 3) & 3);
        const int srcB = pin(((pp >> 1) << 4) | ((cB ^ 1) << 3) | ((g & 1) << 2) | ((pp & 1) << 1) | (qd & 1));
        const bool pB1 = cB && phi < 4, pB2 = cB && phi == 4;
        const int word = (8 * cB + 2 * (phi & 3) + (qd & 1)) * 8 + b;
        const uint32_t sto = pin(sb + CSTG_OFF + wg * 4096 + (word ^ (((word >> 5) & 3) << 1)) * 4);
#pragma unroll 1
        for (int i = wg; i < NCONV; i += 2) {
          const uint32_t base = conv_buf(sb, i & 3), next = conv_buf(sb, (i + 2) & 3);
          const uint64_t dH = mkdesc(base + CH_OFF, 16, 128, 0);
          float y[8][16];
          named_bar(6 + wg, 256);
          wg_fence();
#pragma unroll
          for (int t = 0; t < 16; t++) {
            if (t >= 8 && t % CFENCE == 0) wg_fence();
            if (t == CTURN) named_arrive(7 - wg, 256);
#pragma unroll
            for (int cb = t >> 1; cb < 8; cb++) {
              wgmma_rs_n32(y[cb], a[t][0], a[t][1], a[t][2], a[t][3], dH + (32 * cb - 32 * (t >> 1) - 2 * (t & 1) - 1), t);
              const int n = 8 * t - (t >> 1) * ((t - 1) >> 1) - (t >> 1) + cb + 1;
              if (n % CPER == 0 && n / CPER <= 8) load_a(base, 7 + n / CPER, 1);
            }
            if (t == 7 && CEARLY) wg_commit();
          }
          wg_commit();
          const bool more = i + 2 < NCONV;
          if (more) mbar_wait_u(bars + B_CFULL + ((i + 2) & 3) * 8, (i + 2) >> 2);
          mbar_wait_u(bars + B_SEMPTY + wg * 8, ((i >> 1) & 1) ^ 1);
          if (CEARLY) wg_wait<1>();
#pragma unroll
          for (int t = 0; t < CEARLY; t++) load_a(next, t, more);
          wg_wait<0>();
          if (lane == 0) mbar_arrive(bars + B_CEMPTY + (i & 3) * 8);
          if (leader) PROF(40 + i);
          uint32_t P[16], Q[16], R[16], o[8];
#pragma unroll
          for (int j = 0; j < 32; j++) {
            if ((j & 3) == 0 && (j >> 2) >= CEARLY) load_a(next, j >> 2, more);
            float v0 = y[j >> 2][4 * (j & 3)], v1 = y[j >> 2][4 * (j & 3) + 1];
            if (j >= 2) { v0 += y[(j - 2) >> 2][4 * ((j - 2) & 3) + 2]; v1 += y[(j - 2) >> 2][4 * ((j - 2) & 3) + 3]; }
            if (j & 1) R[j >> 1] = shfl_ordered(pack_bf16(v0, v1), lane ^ 16);
            else P[j >> 1] = pack_bf16(v0, v1);
          }
#pragma unroll
          for (int m = 0; m < 16; m++) Q[m] = hadd2(P[m], cA ? R[m] : (m ? R[m - 1] : 0u));
#pragma unroll
          for (int m = 0; m < 8; m++) o[m] = shfl_ordered(pB1 ? Q[2 * m] : (pB2 ? (m ? Q[2 * m - 1] : 0u) : Q[2 * m + 1]), srcB);
#pragma unroll
          for (int m = 0; m < 8; m++) sts32(sto + m * 512, hadd2(pB1 ? Q[2 * m + 1] : Q[2 * m], o[m]));
          fence_async_smem();
          __syncwarp();
          if (lane == 0) mbar_arrive(bars + B_SFULL + wg * 8);
          if (leader && i == 5) PROF(53);
        }
        if (wg == 0) named_bar(6, 256);
      }
    }
    if (kind != 2) {
      const Role ro = get_role(roles);
      const uint32_t pitch = ro.pitch;
      const int s0 = ro.g2_m + wg * 64 + wi * 16 + g;
      const size_t go = (size_t)s0 * D_ + ro.dt * 128 + ro.half * 64 + qd * 8, go8 = (size_t)s0 * D_ + 512 + ro.dt * 16 + ro.half * 8 + qd * 2;
      uint32_t x[2][9], sg[2][9];
      float acc[72];
      mbar_wait_u(bars + B_G2GO + wg * 8, 0);
      gemm_run<0, 0>(acc, XAT + 2 * wg, 0, p, sb, pitch, wg, leader);
#pragma unroll
      for (int J = 0; J < 4; J++) {
        const uint4 v = ldg128(q + go + (J & 1) * 8 * D_ + (J >> 1) * 32);
        x[J & 1][4 * (J >> 1)] = v.x; x[J & 1][4 * (J >> 1) + 1] = v.y; x[J & 1][4 * (J >> 1) + 2] = v.z; x[J & 1][4 * (J >> 1) + 3] = v.w;
      }
      x[0][8] = ldg32(q + go8); x[1][8] = ldg32(q + go8 + 8 * D_);
      const uint4 st0 = ld_l2(gs->stats + s0), st1 = ld_l2(gs->stats + s0 + 8);
      const uint32_t braw0 = ldg16(b2 + s0), braw1 = ldg16(b2 + s0 + 8);
      gemm_run<0, 0>(acc, 20 - XAT, 1, p, sb, pitch, wg, leader);
      {
        const int zw = 8 * wi + (g ^ ((((ro.g2_m >> 6) + wg) & 3) << 1));
        const uint32_t za = sb + ST * pitch + wg * 9216 + qd * 256 + (zw & 3) * 4;
        mbar_wait_u(bars + B_ZFULL, 0);
#pragma unroll
        for (int j = 0; j < 9; j++) {
          sg[0][j] = lds32(za + j * 1024 + (((zw >> 2) ^ (2 * qd)) << 4));
          sg[1][j] = lds32(za + j * 1024 + 128 + (((zw >> 2) ^ (2 * qd + 1)) << 4));
        }
      }
      gemm_run<0, 0>(acc, 1, 1, p, sb, pitch, wg, leader);
#pragma unroll
      for (int j = 0; j < 9; j++) {
        const uint32_t z0 = __byte_perm(sg[0][j], sg[1][j], 0x5410), z1 = __byte_perm(sg[0][j], sg[1][j], 0x7632);
        sg[0][j] = hmul2(ln_apply(x[0][j], st0), z0);
        sg[1][j] = hmul2(ln_apply(x[1][j], st1), z1);
        asm volatile("" : "+r"(sg[0][j]), "+r"(sg[1][j]));
      }
      gemm_run<0, SKEW>(acc, 15 - LAG - 2 * wg, 1, p, sb, pitch, wg, leader);
      const uint32_t rofs = (68 % ST) * pitch + wg * 9216 + wt * 16;
      const uint32_t rdst = mapa(sb + rofs, ro.half ^ 1), rbar = mapa(bars + B_RFULL + wg * 8, ro.half ^ 1);
      pipe_drain(p, bars, leader);
      if (leader) PROF(9 + 10 * wg);
      if (tid == 128) PROFC(50);
      float cs[36], ck[36];
      split_acc(acc, cs, ck);
      gemm2_part<0>(cs, sb, pitch, wg);
      const float hb0 = fmaf(bf_lo(braw0), 0.5f, __uint_as_float(st0.w)), hb1 = fmaf(bf_lo(braw1), 0.5f, __uint_as_float(st1.w));
      mbar_wait(bars + B_GO, 0);
      wg_wait<0>();
      if (leader) PROF(54 + wg);
#pragma unroll
      for (int i = 0; i < 5; i++) {
        const float* c = &cs[8 * i];
        const uint32_t v0 = pack_bf16(fmaf(c[0], 0.5f, hb0), fmaf(c[1], 0.5f, hb0)), v1 = pack_bf16(fmaf(c[2], 0.5f, hb1), fmaf(c[3], 0.5f, hb1));
        if (i < 4) st_async4(rdst + i * 2048, v0, v1, pack_bf16(fmaf(c[4], 0.5f, hb0), fmaf(c[5], 0.5f, hb0)), pack_bf16(fmaf(c[6], 0.5f, hb1), fmaf(c[7], 0.5f, hb1)), rbar);
        else st_async2(rdst + 8192 - wt * 8, v0, v1, rbar);
      }
      if (wg == 1) named_bar(7, 256);
      gemm2_part<72>(ck, sb, pitch, wg);
      uint32_t rp[18];
      mbar_wait(bars + B_RFULL + wg * 8, 0);
#pragma unroll
      for (int m = 0; m < 4; m++) {
        const uint4 v = lds128(sb + rofs + m * 2048);
        rp[4 * m] = v.x; rp[4 * m + 1] = v.y; rp[4 * m + 2] = v.z; rp[4 * m + 3] = v.w;
      }
      { const uint2 v = lds64(sb + rofs + 8192 - wt * 8); rp[16] = v.x; rp[17] = v.y; }
      __nv_bfloat16* o = out + go;
      wg_wait<0>();
      if (leader) PROF(10 + 10 * wg);
      float h[2][4], t[2][4], half = 0.5f;
#pragma unroll
      for (int j = 0; j <= 9; j++) {
        if (j < 9) {
          const uint32_t ra = rp[2 * j], rb = rp[2 * j + 1];
          if (j >= 2) half = fmaf(t[j & 1][3], 0.f, 0.5f);
          h[j & 1][0] = fmaf(ck[4 * j], half, bf_lo(ra)); h[j & 1][1] = fmaf(ck[4 * j + 1], half, bf_hi(ra));
          h[j & 1][2] = fmaf(ck[4 * j + 2], half, bf_lo(rb)); h[j & 1][3] = fmaf(ck[4 * j + 3], half, bf_hi(rb));
#pragma unroll
          for (int u = 0; u < 4; u++) t[j & 1][u] = tanh_ordered(h[j & 1][u]);
        }
        if (j > 0) {
          const int k = j - 1;
          const float* hh = h[k & 1];
          const float* tt = t[k & 1];
          x[0][k] = hfma2(sg[0][k], pack_bf16(fmaf(hh[0], tt[0], hh[0]), fmaf(hh[1], tt[1], hh[1])), x[0][k]);
          x[1][k] = hfma2(sg[1][k], pack_bf16(fmaf(hh[2], tt[2], hh[2]), fmaf(hh[3], tt[3], hh[3])), x[1][k]);
          if ((k & 3) == 3) {
            *(uint4*)(o + (k >> 2) * 32) = make_uint4(x[0][k - 3], x[0][k - 2], x[0][k - 1], x[0][k]);
            *(uint4*)(o + 8 * D_ + (k >> 2) * 32) = make_uint4(x[1][k - 3], x[1][k - 2], x[1][k - 1], x[1][k]);
          }
        }
      }
      *(uint32_t*)(out + go8) = x[0][8];
      *(uint32_t*)(out + go8 + 8 * D_) = x[1][8];
      if (leader) PROF(11 + 7 * wg);
      if (tid == 128) PROFC(51);
    }
  }
}

typedef CUresult (*EncodeFn)(CUtensorMap*, CUtensorMapDataType, cuuint32_t, void*, const cuuint64_t*, const cuuint64_t*, const cuuint32_t*,
                             const cuuint32_t*, CUtensorMapInterleave, CUtensorMapSwizzle, CUtensorMapL2promotion, CUtensorMapFloatOOBfill);

uint32_t role_of_pair(int t) {
  int grp, i;
  if (t < 32) { const int j = t & 7; i = t >> 3; grp = j < 6 ? 1 + j : 12 + 2 * (j - 6); }
  else if (t < 60) { const int j = (t - 32) % 7; i = (t - 32) / 7; grp = j < 5 ? 7 + j : 13 + 2 * (j - 5); }
  else if (t < 62) return 2u | (uint32_t)(14 + 3 * (t - 60)) << 8 | 2u << 16;
  else { grp = 0; i = t - 62; }
  if (grp < 12) return (uint32_t)(i << 2 | grp << 4 | grp << 8 | i << 16);
  const int u = (grp & 1) * 4 + i;
  return (uint32_t)(1 | i << 2 | grp << 4 | (12 + 3 * ((grp - 12) >> 1) + u / 3) << 8 | (u % 3) << 16);
}

}

extern "C" void kernel_launch(void* const* d_in, const int* in_sizes, int n_in, void* d_out, int out_size) {
  (void)in_sizes; (void)n_in; (void)out_size;
  EncodeFn enc = nullptr;
  cudaDriverEntryPointQueryResult qr;
  cudaGetDriverEntryPoint("cuTensorMapEncodeTiled", (void**)&enc, cudaEnableDefault, &qr);
  Scratch* gs = nullptr;
  cudaGetSymbolAddress((void**)&gs, g_scratch);
  void *zp = gs->z, *hp = gs->h, *kvp = gs->kv;
  CUtensorMap tmW1, tmW2, tmZ, tmH, tmK, tmV, tmKV;
  for (int w = 0; w < 2; w++) {
    cuuint64_t gd[2] = {D_, S_};
    cuuint64_t st[1] = {D_ * 2};
    cuuint32_t bx[2] = {64, w ? 33u : 36u};
    cuuint32_t es[2] = {1, 1};
    enc(w ? &tmV : &tmK, CU_TENSOR_MAP_DATA_TYPE_BFLOAT16, 2, d_in[1 + w], gd, st, bx, es, CU_TENSOR_MAP_INTERLEAVE_NONE, CU_TENSOR_MAP_SWIZZLE_NONE,
        CU_TENSOR_MAP_L2_PROMOTION_L2_128B, CU_TENSOR_MAP_FLOAT_OOB_FILL_NONE);
  }
  {
    cuuint64_t gd[4] = {40, D_ / 2, 2, 64};
    cuuint64_t st[3] = {2 * KVT, KVT, 160};
    cuuint32_t bx[4] = {44, KVROWS, 1, 1};
    cuuint32_t es[4] = {1, 1, 1, 1};
    enc(&tmKV, CU_TENSOR_MAP_DATA_TYPE_UINT32, 4, kvp, gd, st, bx, es, CU_TENSOR_MAP_INTERLEAVE_NONE, CU_TENSOR_MAP_SWIZZLE_NONE,
        CU_TENSOR_MAP_L2_PROMOTION_NONE, CU_TENSOR_MAP_FLOAT_OOB_FILL_NONE);
  }
  {
    cuuint64_t gd[3] = {64, 32 * 72, 8};
    cuuint64_t st[2] = {1024, 128};
    cuuint32_t bx[3] = {64, 72, 2};
    cuuint32_t es[3] = {1, 1, 1};
    enc(&tmH, CU_TENSOR_MAP_DATA_TYPE_BFLOAT16, 3, hp, gd, st, bx, es, CU_TENSOR_MAP_INTERLEAVE_NONE, CU_TENSOR_MAP_SWIZZLE_128B,
        CU_TENSOR_MAP_L2_PROMOTION_NONE, CU_TENSOR_MAP_FLOAT_OOB_FILL_NONE);
  }
  for (int w = 0; w < 2; w++) {
    const cuuint64_t M = w ? S_ : F_, K = w ? F_ : S_;
    cuuint64_t gd[3] = {64, K, M / 64};
    cuuint64_t st[2] = {M * 2, 128};
    cuuint32_t bx[3] = {64, 64, 2};
    cuuint32_t es[3] = {1, 1, 1};
    enc(w ? &tmW2 : &tmW1, CU_TENSOR_MAP_DATA_TYPE_BFLOAT16, 3, d_in[w ? 9 : 7], gd, st, bx, es, CU_TENSOR_MAP_INTERLEAVE_NONE,
        CU_TENSOR_MAP_SWIZZLE_128B, CU_TENSOR_MAP_L2_PROMOTION_L2_256B, CU_TENSOR_MAP_FLOAT_OOB_FILL_NONE);
  }
  {
    cuuint64_t gd[2] = {S_, D_};
    cuuint64_t st[1] = {S_ * 2};
    cuuint32_t bx[2] = {64, 72};
    cuuint32_t es[2] = {1, 1};
    enc(&tmZ, CU_TENSOR_MAP_DATA_TYPE_BFLOAT16, 2, zp, gd, st, bx, es, CU_TENSOR_MAP_INTERLEAVE_NONE, CU_TENSOR_MAP_SWIZZLE_128B,
        CU_TENSOR_MAP_L2_PROMOTION_L2_256B, CU_TENSOR_MAP_FLOAT_OOB_FILL_NONE);
  }
  RoleMap roles;
  int dev = 0, sms = 0;
  cudaGetDevice(&dev);
  cudaDeviceGetAttribute(&sms, cudaDevAttrMultiProcessorCount, dev);
  roles.by_sm = sms == NCTA;
  for (int k = 0; k < NCTA / 2; k++) roles.role[k] = role_of_pair(k);
  cudaFuncSetAttribute(fused_kernel, cudaFuncAttributeMaxDynamicSharedMemorySize, SMEM_BYTES);
  fused_kernel<<<NCTA, 384, SMEM_BYTES>>>((const __nv_bfloat16*)d_in[0], gs, (const __nv_bfloat16*)d_in[8], (const __nv_bfloat16*)d_in[3],
                                          (const __nv_bfloat16*)d_in[4], (const __nv_bfloat16*)d_in[5], tmW1, tmW2, tmZ, tmH, tmK, tmV, tmKV,
                                          roles, (const __nv_bfloat16*)d_in[10], (__nv_bfloat16*)d_out);
}
```

```cpp
#include <cuda_runtime.h>
#include <cuda_bf16.h>
#include <cuda.h>
#include <stdint.h>

namespace {

constexpr int S_ = 2048, D_ = 576, F_ = 4608;
constexpr int NCTA = 132, NG2 = 128, NCONV = 6;
constexpr int ST = 5, ASZ = 16384, PITCH_S = ASZ + 144 * 128, PITCH_B = ASZ + 192 * 128;
constexpr int KVIN = (36 + 33) * 128, KVW = 2 * KVIN + 64 * 176;
constexpr int BAR_OFF = ST * PITCH_S + 2 * KVW;
constexpr int SMEM_BYTES = BAR_OFF + 512;
constexpr int KVROWS = 16, LNROT = 120;
constexpr int SKEW = 1;
constexpr int LEAD_S = 3, LEAD_B = 2;
constexpr int CTURN = 14, CPER = 4, CEARLY = 0, CFENCE = 8;
constexpr int TURN = 4, KPRE = 2;
constexpr int XAT = 12;
constexpr int LAG = 4;
constexpr int CBUF = 14464, CH_OFF = 128, CT_OFF = 4224, KVT = 10240;
constexpr int CSTG_OFF = ST * PITCH_S + 3 * CBUF;
constexpr uint32_t SPIN_LIMIT = 1u << 22;

constexpr int FL_H = 0, FL_U = 32, FL_KV = 38, FL_Z = 41, FL_GATE = 42, FL_DONE = 43, FL_N = 44;
struct Scratch {
  uint32_t flags[64 * 32];
  uint4 stats[S_];
  uint8_t h[32 * 72 * 1024];
  uint8_t u[72 * D_ * 128];
  uint8_t kv[D_ * KVT];
  __nv_bfloat16 z[D_ * S_];
};
__device__ __align__(1024) Scratch g_scratch;
extern __shared__ __align__(1024) uint8_t smem_raw[];
#define TUNABLES(X) X(W9, 1200) X(QLATE, 20) X(QDELAY, 400) X(QRAMP, 5) X(A0, 1200) X(AD, 300) X(AN, 5) X(AL, 0) X(H0, 3500) X(HD, 400) X(KVGAP, 100) X(KVSTAG, 1200) X(KVGO, 6) X(CVGO, 31) X(GDELAY, 608) X(GDELAY1, 256) X(ZDELAY, 3000) X(ZRAMP, 40) X(NPF, 0) X(PFGAP, 600)
#define X(k, v) constexpr int T_##k = v;
TUNABLES(X)
#undef X
#define TN(k) T_##k
struct RoleMap { uint32_t role[NCTA / 2]; uint32_t by_sm; };
#define PROF(i) do {} while (0)
#define PROFG(i) do {} while (0)
#define PROFC(i) do {} while (0)

template<int TB> __device__ __forceinline__ void wgmma_ss(float (&d)[96], uint32_t da, uint32_t db, int sd) {
  asm volatile("{\n.reg .pred p;\n.reg .b64 a, b;\nsetp.ne.b32 p, %98, 0;\nmov.b64 a, {%96, %100};\nmov.b64 b, {%97, %101};\n"
    "wgmma.mma_async.sync.aligned.m64n192k16.f32.bf16.bf16 {%0, %1, %2, %3, %4, %5, %6, %7, %8, %9, %10, %11, %12, %13, %14, %15, %16, %17, %18, %19, %20, %21, %22, %23, %24, %25, %26, %27, %28, %29, %30, %31, %32, %33, %34, %35, %36, %37, %38, %39, %40, %41, %42, %43, %44, %45, %46, %47, %48, %49, %50, %51, %52, %53, %54, %55, %56, %57, %58, %59, %60, %61, %62, %63, %64, %65, %66, %67, %68, %69, %70, %71, %72, %73, %74, %75, %76, %77, %78, %79, %80, %81, %82, %83, %84, %85, %86, %87, %88, %89, %90, %91, %92, %93, %94, %95}, a, b, p, 1, 1, 1, %99;\n}\n"
    : "+f"(d[0]), "+f"(d[1]), "+f"(d[2]), "+f"(d[3]), "+f"(d[4]), "+f"(d[5]), "+f"(d[6]), "+f"(d[7]), "+f"(d[8]), "+f"(d[9]), "+f"(d[10]), "+f"(d[11]), "+f"(d[12]), "+f"(d[13]), "+f"(d[14]), "+f"(d[15]), "+f"(d[16]), "+f"(d[17]), "+f"(d[18]), "+f"(d[19]), "+f"(d[20]), "+f"(d[21]), "+f"(d[22]), "+f"(d[23]), "+f"(d[24]), "+f"(d[25]), "+f"(d[26]), "+f"(d[27]), "+f"(d[28]), "+f"(d[29]), "+f"(d[30]), "+f"(d[31]), "+f"(d[32]), "+f"(d[33]), "+f"(d[34]), "+f"(d[35]), "+f"(d[36]), "+f"(d[37]), "+f"(d[38]), "+f"(d[39]), "+f"(d[40]), "+f"(d[41]), "+f"(d[42]), "+f"(d[43]), "+f"(d[44]), "+f"(d[45]), "+f"(d[46]), "+f"(d[47]), "+f"(d[48]), "+f"(d[49]), "+f"(d[50]), "+f"(d[51]), "+f"(d[52]), "+f"(d[53]), "+f"(d[54]), "+f"(d[55]), "+f"(d[56]), "+f"(d[57]), "+f"(d[58]), "+f"(d[59]), "+f"(d[60]), "+f"(d[61]), "+f"(d[62]), "+f"(d[63]), "+f"(d[64]), "+f"(d[65]), "+f"(d[66]), "+f"(d[67]), "+f"(d[68]), "+f"(d[69]), "+f"(d[70]), "+f"(d[71]), "+f"(d[72]), "+f"(d[73]), "+f"(d[74]), "+f"(d[75]), "+f"(d[76]), "+f"(d[77]), "+f"(d[78]), "+f"(d[79]), "+f"(d[80]), "+f"(d[81]), "+f"(d[82]), "+f"(d[83]), "+f"(d[84]), "+f"(d[85]), "+f"(d[86]), "+f"(d[87]), "+f"(d[88]), "+f"(d[89]), "+f"(d[90]), "+f"(d[91]), "+f"(d[92]), "+f"(d[93]), "+f"(d[94]), "+f"(d[95])
    : "r"(da), "r"(db), "r"(sd), "n"(TB), "r"(0x40000040u), "r"(TB ? 0x40u : 0x40000040u));
}
template<int TB> __device__ __forceinline__ void wgmma_ss(float (&d)[72], uint32_t da, uint32_t db, int sd) {
  asm volatile("{\n.reg .pred p;\n.reg .b64 a, b;\nsetp.ne.b32 p, %74, 0;\nmov.b64 a, {%72, %76};\nmov.b64 b, {%73, %77};\n"
    "wgmma.mma_async.sync.aligned.m64n144k16.f32.bf16.bf16 {%0, %1, %2, %3, %4, %5, %6, %7, %8, %9, %10, %11, %12, %13, %14, %15, %16, %17, %18, %19, %20, %21, %22, %23, %24, %25, %26, %27, %28, %29, %30, %31, %32, %33, %34, %35, %36, %37, %38, %39, %40, %41, %42, %43, %44, %45, %46, %47, %48, %49, %50, %51, %52, %53, %54, %55, %56, %57, %58, %59, %60, %61, %62, %63, %64, %65, %66, %67, %68, %69, %70, %71}, a, b, p, 1, 1, 1, %75;\n}\n"
    : "+f"(d[0]), "+f"(d[1]), "+f"(d[2]), "+f"(d[3]), "+f"(d[4]), "+f"(d[5]), "+f"(d[6]), "+f"(d[7]), "+f"(d[8]), "+f"(d[9]), "+f"(d[10]), "+f"(d[11]), "+f"(d[12]), "+f"(d[13]), "+f"(d[14]), "+f"(d[15]), "+f"(d[16]), "+f"(d[17]), "+f"(d[18]), "+f"(d[19]), "+f"(d[20]), "+f"(d[21]), "+f"(d[22]), "+f"(d[23]), "+f"(d[24]), "+f"(d[25]), "+f"(d[26]), "+f"(d[27]), "+f"(d[28]), "+f"(d[29]), "+f"(d[30]), "+f"(d[31]), "+f"(d[32]), "+f"(d[33]), "+f"(d[34]), "+f"(d[35]), "+f"(d[36]), "+f"(d[37]), "+f"(d[38]), "+f"(d[39]), "+f"(d[40]), "+f"(d[41]), "+f"(d[42]), "+f"(d[43]), "+f"(d[44]), "+f"(d[45]), "+f"(d[46]), "+f"(d[47]), "+f"(d[48]), "+f"(d[49]), "+f"(d[50]), "+f"(d[51]), "+f"(d[52]), "+f"(d[53]), "+f"(d[54]), "+f"(d[55]), "+f"(d[56]), "+f"(d[57]), "+f"(d[58]), "+f"(d[59]), "+f"(d[60]), "+f"(d[61]), "+f"(d[62]), "+f"(d[63]), "+f"(d[64]), "+f"(d[65]), "+f"(d[66]), "+f"(d[67]), "+f"(d[68]), "+f"(d[69]), "+f"(d[70]), "+f"(d[71])
    : "r"(da), "r"(db), "r"(sd), "n"(TB), "r"(0x40000040u), "r"(TB ? 0x40u : 0x40000040u));
}
template<int TB> __device__ __forceinline__ void wgmma_ss(float (&d)[36], uint32_t da, uint32_t db, int sd) {
  asm volatile("{\n.reg .pred p;\n.reg .b64 a, b;\nsetp.ne.b32 p, %38, 0;\nmov.b64 a, {%36, %40};\nmov.b64 b, {%37, %41};\n"
    "wgmma.mma_async.sync.aligned.m64n72k16.f32.bf16.bf16 {%0, %1, %2, %3, %4, %5, %6, %7, %8, %9, %10, %11, %12, %13, %14, %15, %16, %17, %18, %19, %20, %21, %22, %23, %24, %25, %26, %27, %28, %29, %30, %31, %32, %33, %34, %35}, a, b, p, 1, 1, 1, %39;\n}\n"
    : "+f"(d[0]), "+f"(d[1]), "+f"(d[2]), "+f"(d[3]), "+f"(d[4]), "+f"(d[5]), "+f"(d[6]), "+f"(d[7]), "+f"(d[8]), "+f"(d[9]), "+f"(d[10]), "+f"(d[11]), "+f"(d[12]), "+f"(d[13]), "+f"(d[14]), "+f"(d[15]), "+f"(d[16]), "+f"(d[17]), "+f"(d[18]), "+f"(d[19]), "+f"(d[20]), "+f"(d[21]), "+f"(d[22]), "+f"(d[23]), "+f"(d[24]), "+f"(d[25]), "+f"(d[26]), "+f"(d[27]), "+f"(d[28]), "+f"(d[29]), "+f"(d[30]), "+f"(d[31]), "+f"(d[32]), "+f"(d[33]), "+f"(d[34]), "+f"(d[35])
    : "r"(da), "r"(db), "r"(sd), "n"(TB), "r"(0x40000040u), "r"(TB ? 0x40u : 0x40000040u));
}
__device__ __forceinline__ void wgmma_rs_n32(float (&d)[16], uint32_t a0, uint32_t a1, uint32_t a2, uint32_t a3, uint64_t db, int sd) {
  asm volatile("{\n.reg .pred p;\nsetp.ne.b32 p, %21, 0;\n"
    "wgmma.mma_async.sync.aligned.m64n32k16.f32.bf16.bf16 {%0, %1, %2, %3, %4, %5, %6, %7, %8, %9, %10, %11, %12, %13, %14, %15}, {%16, %17, %18, %19}, %20, p, 1, 1, 0;\n}\n"
    : "+f"(d[0]), "+f"(d[1]), "+f"(d[2]), "+f"(d[3]), "+f"(d[4]), "+f"(d[5]), "+f"(d[6]), "+f"(d[7]), "+f"(d[8]), "+f"(d[9]), "+f"(d[10]), "+f"(d[11]), "+f"(d[12]), "+f"(d[13]), "+f"(d[14]), "+f"(d[15])
    : "r"(a0), "r"(a1), "r"(a2), "r"(a3), "l"(db), "r"(sd));
}

__device__ __forceinline__ void wg_fence() { asm volatile("wgmma.fence.sync.aligned;" ::: "memory"); }
__device__ __forceinline__ void wg_commit() { asm volatile("wgmma.commit_group.sync.aligned;" ::: "memory"); }
template <int n> __device__ __forceinline__ void wg_wait() { asm volatile("wgmma.wait_group.sync.aligned %0;" ::"n"(n) : "memory"); }
__device__ __forceinline__ uint64_t mkdesc(uint32_t addr, uint32_t lbo, uint32_t sbo, uint32_t sw) {
  return (uint64_t)((addr & 0x3FFFF) >> 4) | ((uint64_t)(lbo >> 4) << 16) | ((uint64_t)(sbo >> 4) << 32) | ((uint64_t)sw << 62);
}
__device__ __forceinline__ void mbar_init(uint32_t a, int c) { asm volatile("mbarrier.init.shared::cta.b64 [%0], %1;" ::"r"(a), "r"(c)); }
__device__ __forceinline__ void mbar_expect(uint32_t a, uint32_t b) { asm volatile("mbarrier.arrive.expect_tx.shared::cta.b64 _, [%0], %1;" ::"r"(a), "r"(b) : "memory"); }
__device__ __forceinline__ void mbar_arrive(uint32_t a) { asm volatile("mbarrier.arrive.shared::cta.b64 _, [%0];" ::"r"(a) : "memory"); }
__device__ __forceinline__ void mbar_arrive_cluster(uint32_t raddr) { asm volatile("mbarrier.arrive.shared::cluster.b64 _, [%0];" ::"r"(raddr) : "memory"); }
__device__ __forceinline__ uint32_t mapa(uint32_t a, uint32_t cta) { uint32_t r; asm("mapa.shared::cluster.u32 %0, %1, %2;" : "=r"(r) : "r"(a), "r"(cta)); return r; }
__device__ __forceinline__ void mbar_wait(uint32_t a, uint32_t ph) {
  asm volatile(
      "{\n.reg .pred p;\n.reg .u32 c;\nmov.u32 c, 0;\n"
      "WAIT_LOOP:\nmbarrier.try_wait.parity.shared::cta.b64 p, [%0], %1;\n@p bra WAIT_DONE;\n"
      "add.u32 c, c, 1;\nsetp.lt.u32 p, c, %2;\n@p bra WAIT_LOOP;\ntrap;\nWAIT_DONE:\n}" ::"r"(a), "r"(ph), "n"(SPIN_LIMIT) : "memory");
}
__device__ __forceinline__ void mbar_wait_u(uint32_t a, uint32_t ph) {
  asm volatile("{\n.reg .pred p;\nWAIT_LOOP:\nmbarrier.try_wait.parity.shared::cta.b64 p, [%0], %1;\n@!p bra WAIT_LOOP;\n}" ::"r"(a), "r"(ph) : "memory");
}
__device__ __forceinline__ uint32_t desc_lo(uint32_t addr, uint32_t lbo) { return ((addr & 0x3FFFF) >> 4) | ((lbo >> 4) << 16); }
__device__ __forceinline__ void tma2d(uint32_t dst, const CUtensorMap* m, int c0, int c1, uint32_t bar) {
  asm volatile("cp.async.bulk.tensor.2d.shared::cluster.global.mbarrier::complete_tx::bytes [%0], [%1, {%3, %4}], [%2];" ::"r"(dst), "l"(m), "r"(bar), "r"(c0), "r"(c1) : "memory");
}
__device__ __forceinline__ void bulk_g2s(uint32_t dst, const void* src, uint32_t sz, uint32_t bar) {
  asm volatile("cp.async.bulk.shared::cluster.global.mbarrier::complete_tx::bytes [%0], [%1], %2, [%3];" ::"r"(dst), "l"(src), "r"(sz), "r"(bar) : "memory");
}
__device__ __forceinline__ void bulk_s2g(void* dst, uint32_t src, uint32_t sz) {
  asm volatile("cp.async.bulk.global.shared::cta.bulk_group [%0], [%1], %2;" ::"l"(dst), "r"(src), "r"(sz) : "memory");
}
__device__ __forceinline__ uint64_t stream_policy() {
  uint64_t p;
  asm volatile("createpolicy.fractional.L2::evict_first.b64 %0, 1.0;" : "=l"(p));
  return p;
}
__device__ __forceinline__ void tma_weights(uint32_t dst, const CUtensorMap* m, int k0, int mchunk, uint32_t bar, uint64_t pol) {
  asm volatile("cp.async.bulk.tensor.3d.shared::cluster.global.mbarrier::complete_tx::bytes.L2::cache_hint [%0], [%1, {%6, %3, %4}], [%2], %5;"
               ::"r"(dst), "l"(m), "r"(bar), "r"(k0), "r"(mchunk), "l"(pol), "r"(0) : "memory");
}
__device__ __forceinline__ void tma_weights_prefetch(const CUtensorMap* m, int k0, int mchunk, uint64_t pol) {
  asm volatile("cp.async.bulk.prefetch.tensor.3d.L2.global.L2::cache_hint [%0, {%4, %1, %2}], %3;" ::"l"(m), "r"(k0), "r"(mchunk), "l"(pol), "r"(0) : "memory");
}
__device__ __forceinline__ bool elect_one() {
  uint32_t p;
  asm volatile("{\n.reg .pred P;\nelect.sync _|P, 0xffffffff;\nselp.u32 %0, 1, 0, P;\n}" : "=r"(p));
  return p;
}
__device__ __forceinline__ void bulk_g2s_stream(uint32_t dst, const void* src, uint32_t sz, uint32_t bar, uint64_t pol) {
  asm volatile("cp.async.bulk.shared::cluster.global.mbarrier::complete_tx::bytes.L2::cache_hint [%0], [%1], %2, [%3], %4;"
               ::"r"(dst), "l"(src), "r"(sz), "r"(bar), "l"(pol) : "memory");
}
__device__ __forceinline__ void tma3d_store(const CUtensorMap* m, int c1, int c2, uint32_t src) {
  asm volatile("cp.async.bulk.tensor.3d.global.shared::cta.bulk_group [%0, {%4, %2, %3}], [%1];" ::"l"(m), "r"(src), "r"(c1), "r"(c2), "r"(0) : "memory");
}
__device__ __forceinline__ void tma2d_stream(uint32_t dst, const CUtensorMap* m, int c0, int c1, uint32_t bar, uint64_t pol) {
  asm volatile("cp.async.bulk.tensor.2d.shared::cluster.global.mbarrier::complete_tx::bytes.L2::cache_hint [%0], [%1, {%3, %4}], [%2], %5;"
               ::"r"(dst), "l"(m), "r"(bar), "r"(c0), "r"(c1), "l"(pol) : "memory");
}
__device__ __forceinline__ void tma4d_store(const CUtensorMap* m, int c1, int c2, int c3, uint32_t src) {
  asm volatile("cp.async.bulk.tensor.4d.global.shared::cta.bulk_group [%0, {%5, %2, %3, %4}], [%1];" ::"l"(m), "r"(src), "r"(c1), "r"(c2), "r"(c3), "r"(0) : "memory");
}
__device__ __forceinline__ void bulk_commit() { asm volatile("cp.async.bulk.commit_group;" ::: "memory"); }
__device__ __forceinline__ void bulk_wait_all() { asm volatile("cp.async.bulk.wait_group 0;" ::: "memory"); }
__device__ __forceinline__ void fence_async_smem() { asm volatile("fence.proxy.async.shared::cta;" ::: "memory"); }
__device__ __forceinline__ void fence_async_global() { asm volatile("fence.proxy.async.global;" ::: "memory"); }
__device__ __forceinline__ void named_bar(int id, int n) { asm volatile("bar.sync %0, %1;" ::"r"(id), "r"(n) : "memory"); }
__device__ __forceinline__ void named_arrive(int id, int n) { asm volatile("bar.arrive %0, %1;" ::"r"(id), "r"(n) : "memory"); }
__device__ __forceinline__ void flag_add(uint32_t* f, int i, uint32_t v) { asm volatile("red.relaxed.gpu.global.add.u32 [%0], %1;" ::"l"(f + i * 32), "r"(v) : "memory"); }
__device__ __forceinline__ uint32_t flag_ld(uint32_t* f, int i) { uint32_t v; asm volatile("ld.relaxed.gpu.global.u32 %0, [%1];" : "=r"(v) : "l"(f + i * 32) : "memory"); return v; }
__device__ __forceinline__ void prefetch_map(const CUtensorMap* m) { asm volatile("prefetch.tensormap [%0];" ::"l"(m) : "memory"); }
__device__ __forceinline__ void stsm4_t(uint32_t a, uint32_t r0, uint32_t r1, uint32_t r2, uint32_t r3) {
  asm volatile("stmatrix.sync.aligned.m8n8.x4.trans.shared.b16 [%0], {%1, %2, %3, %4};" ::"r"(a), "r"(r0), "r"(r1), "r"(r2), "r"(r3) : "memory");
}
__device__ __forceinline__ uint32_t lds32(uint32_t a) { uint32_t v; asm volatile("ld.shared.u32 %0, [%1];" : "=r"(v) : "r"(a) : "memory"); return v; }
__device__ __forceinline__ void sts32(uint32_t a, uint32_t v) { asm volatile("st.shared.u32 [%0], %1;" ::"r"(a), "r"(v) : "memory"); }
__device__ __forceinline__ uint4 ld_l2(const uint4* p) { uint4 v; asm volatile("ld.relaxed.gpu.global.v4.u32 {%0, %1, %2, %3}, [%4];" : "=r"(v.x), "=r"(v.y), "=r"(v.z), "=r"(v.w) : "l"(p) : "memory"); return v; }
__device__ __forceinline__ void sts128(uint32_t a, uint32_t x, uint32_t y, uint32_t z, uint32_t w) { asm volatile("st.shared.v4.u32 [%0], {%1, %2, %3, %4};" ::"r"(a), "r"(x), "r"(y), "r"(z), "r"(w) : "memory"); }
__device__ __forceinline__ uint4 lds128(uint32_t a) { uint4 v; asm volatile("ld.shared.v4.u32 {%0, %1, %2, %3}, [%4];" : "=r"(v.x), "=r"(v.y), "=r"(v.z), "=r"(v.w) : "r"(a) : "memory"); return v; }
__device__ __forceinline__ void st_async4(uint32_t raddr, uint32_t a, uint32_t b, uint32_t c, uint32_t d, uint32_t rbar) {
  asm volatile("st.async.weak.shared::cluster.mbarrier::complete_tx::bytes.v4.b32 [%0], {%1, %2, %3, %4}, [%5];" ::"r"(raddr), "r"(a), "r"(b), "r"(c), "r"(d), "r"(rbar) : "memory");
}
__device__ __forceinline__ uint32_t pack_bf16(float lo, float hi) { uint32_t r; asm("cvt.rn.bf16x2.f32 %0, %1, %2;" : "=r"(r) : "f"(hi), "f"(lo)); return r; }
__device__ __forceinline__ float bf_lo(uint32_t v) { return __uint_as_float(v << 16); }
__device__ __forceinline__ float bf_hi(uint32_t v) { return __uint_as_float(v & 0xffff0000u); }
__device__ __forceinline__ float bf_round(float x) { return bf_lo(pack_bf16(x, 0.f)); }
__device__ __forceinline__ uint32_t hmul2(uint32_t a, uint32_t b) { uint32_t r; asm("mul.rn.bf16x2 %0, %1, %2;" : "=r"(r) : "r"(a), "r"(b)); return r; }
__device__ __forceinline__ uint32_t hsub2(uint32_t a, uint32_t b) { uint32_t r; asm("sub.rn.bf16x2 %0, %1, %2;" : "=r"(r) : "r"(a), "r"(b)); return r; }
__device__ __forceinline__ uint32_t hfma2(uint32_t a, uint32_t b, uint32_t c) { uint32_t r; asm("fma.rn.bf16x2 %0, %1, %2, %3;" : "=r"(r) : "r"(a), "r"(b), "r"(c)); return r; }
__device__ __forceinline__ uint4 ldg128(const void* p) { uint4 v; asm volatile("ld.global.nc.v4.u32 {%0, %1, %2, %3}, [%4];" : "=r"(v.x), "=r"(v.y), "=r"(v.z), "=r"(v.w) : "l"(p)); return v; }
__device__ __forceinline__ uint32_t ldg16(const void* p) { uint32_t v; asm volatile("ld.global.nc.u16 %0, [%1];" : "=r"(v) : "l"(p)); return v; }
__device__ __forceinline__ float tanh_ordered(float x) { float y; asm volatile("tanh.approx.f32 %0, %1;" : "=f"(y) : "f"(x)); return y; }
__device__ __forceinline__ void mma16816(float (&d)[4], uint32_t a0, uint32_t a1, uint32_t a2, uint32_t a3, uint32_t b0, uint32_t b1) {
  asm("mma.sync.aligned.m16n8k16.row.col.f32.bf16.bf16.f32 {%0, %1, %2, %3}, {%4, %5, %6, %7}, {%8, %9}, {%0, %1, %2, %3};"
      : "+f"(d[0]), "+f"(d[1]), "+f"(d[2]), "+f"(d[3]) : "r"(a0), "r"(a1), "r"(a2), "r"(a3), "r"(b0), "r"(b1));
}
__device__ __forceinline__ uint32_t hadd2(uint32_t a, uint32_t b) { uint32_t r; asm("add.rn.bf16x2 %0, %1, %2;" : "=r"(r) : "r"(a), "r"(b)); return r; }
__device__ __forceinline__ uint32_t ldg32(const void* p) { uint32_t v; asm volatile("ld.global.nc.L1::no_allocate.u32 %0, [%1];" : "=r"(v) : "l"(p)); return v; }
__device__ __forceinline__ uint2 lds64(uint32_t a) { uint2 v; asm volatile("ld.shared.v2.u32 {%0, %1}, [%2];" : "=r"(v.x), "=r"(v.y) : "r"(a) : "memory"); return v; }
__device__ __forceinline__ uint32_t lds32_if(uint32_t a, uint32_t on) {
  uint32_t v;
  asm volatile("{\n.reg .pred p;\nsetp.ne.u32 p, %2, 0;\n@p ld.shared.u32 %0, [%1];\n}" : "=r"(v) : "r"(a), "r"(on) : "memory");
  return v;
}
__device__ __forceinline__ uint32_t clock_now() { uint32_t t; asm volatile("mov.u32 %0, %%clock;" : "=r"(t)); return t; }
__device__ __forceinline__ uint32_t time_now() { uint32_t t; asm volatile("mov.u32 %0, %%globaltimer_lo;" : "=r"(t)); return t; }
__device__ __forceinline__ void spin_until(uint32_t t0, uint32_t n) { while (clock_now() - t0 < n) {} }
__device__ __forceinline__ uint2 ldg64_if(const void* p, uint32_t on) {
  uint2 v;
  asm volatile("{\n.reg .pred p;\nsetp.ne.u32 p, %3, 0;\n@p ld.global.nc.v2.u32 {%0, %1}, [%2];\n}" : "=r"(v.x), "=r"(v.y) : "l"(p), "r"(on));
  return v;
}
template <class T> __device__ __forceinline__ T pin(T v) { asm volatile("" : "+r"(v)); return v; }
__device__ __forceinline__ void st_async2(uint32_t raddr, uint32_t a, uint32_t b, uint32_t rbar) {
  asm volatile("st.async.weak.shared::cluster.mbarrier::complete_tx::bytes.v2.b32 [%0], {%1, %2}, [%3];" ::"r"(raddr), "r"(a), "r"(b), "r"(rbar) : "memory");
}
__device__ __forceinline__ void bulk_prefetch(const void* src, uint32_t sz, uint64_t pol) {
  asm volatile("cp.async.bulk.prefetch.L2.global.L2::cache_hint [%0], %1, %2;" ::"l"(src), "r"(sz), "l"(pol) : "memory");
}
__device__ __forceinline__ void bulk_wait_read() { asm volatile("cp.async.bulk.wait_group.read 0;" ::: "memory"); }
__device__ __forceinline__ uint32_t shfl_ordered(uint32_t v, int src) { uint32_t r; asm volatile("shfl.sync.idx.b32 %0, %1, %2, 0x1f, 0xffffffff;" : "=r"(r) : "r"(v), "r"(src)); return r; }
__device__ __forceinline__ int chan_pos(int d) {
  return d < 512 ? 72 * (d >> 6) + ((d & 33) | ((d & 6) << 2) | ((d >> 2) & 6)) : 72 * ((d - 512) >> 3) + 64 + (d & 7);
}

struct Ring {
  uint32_t s, ph;
  __device__ __forceinline__ void next() { if (++s == ST) { s = 0; ph ^= 1; } }
};
constexpr int B_FULL = 0, B_GO = 40, B_CFULL = 48, B_SEMPTY = 80, B_ZFULL = 96, B_RFULL = 104, B_UDONE = 120, B_KFULL = 136, B_RAW = 168, B_CVGO = 248, B_PEER = 256, B_G2GO = 264,
              B_EMPTY = 280, B_KVGO = 320, B_G1DONE = 328,
              B_CEMPTY = 336, B_SFULL = 368, B_USTG = 384, B_END = 400;

__device__ __forceinline__ void poll_once(uint32_t* f, uint32_t& ready, int idx, uint32_t want, bool active) {
  bool ok = false;
  if (active) ok = flag_ld(f, idx) == want;
  const uint32_t seen = __ballot_sync(0xffffffffu, ok);
  if (seen & ~ready) fence_async_global();
  ready |= seen;
}
__device__ __forceinline__ void poll_bits(uint32_t* f, uint32_t& ready, uint32_t bits, int idx, uint32_t want, bool active) {
  for (uint32_t spins = 0; (ready & bits) != bits; spins++) {
    poll_once(f, ready, idx, want, active);
    if (spins > SPIN_LIMIT) asm volatile("trap;");
  }
}
__device__ __forceinline__ void wait_counter(uint32_t* f, int idx, uint32_t want, uint32_t first, uint32_t nap) {
#pragma unroll 1
  for (uint32_t spins = 0; first != want; spins++) {
    if (spins) __nanosleep(nap);
    first = flag_ld(f, idx);
    if (spins > SPIN_LIMIT) asm volatile("trap;");
  }
  fence_async_global();
}

__device__ __forceinline__ void gate_arrive(uint32_t* f, uint32_t back) {
  asm volatile("red.relaxed.gpu.global.max.u32 [%0], %1;" ::"l"(f + FL_GATE * 32 + 1), "r"(time_now() - back) : "memory");
  flag_add(f, FL_GATE, 1);
}

__device__ __forceinline__ float ln_rinv(float var) {
  float rt, rinv;
  asm("sqrt.approx.ftz.f32 %0, %1;" : "=f"(rt) : "f"(bf_round(bf_round(var) + 1e-5f)));
  asm("rcp.approx.ftz.f32 %0, %1;" : "=f"(rinv) : "f"(bf_round(rt)));
  return rinv;
}
__device__ __forceinline__ uint32_t ln_apply(uint32_t x, const uint4& st) {
  const uint32_t d = hsub2(x, st.x);
  return hfma2(d, st.y, hmul2(d, st.z));
}

__device__ __forceinline__ void polling_done(uint32_t* f, int lane) {
  unsigned old = 0;
  if (lane == 0) asm volatile("atom.relaxed.gpu.global.add.u32 %0, [%1], 1;" : "=r"(old) : "l"(f + FL_DONE * 32) : "memory");
  old = __shfl_sync(0xffffffffu, old, 0);
  if (old == NCTA + NG2 - 1) {
#pragma unroll 1
    for (int i = lane; i < FL_N; i += 32) *(uint2*)(f + i * 32) = make_uint2(0u, 0u);
  }
}

struct Pipe { Ring r; uint32_t prev; bool pending; int cnt; };
__device__ __forceinline__ void pipe_drain(Pipe& p, uint32_t bars, bool leader) {
  wg_wait<0>();
  if (leader) mbar_arrive(bars + B_EMPTY + p.prev * 8);
  p.pending = false;
}
template <int TB, int LEAD, int R>
__device__ __forceinline__ void gemm_run(float (&acc)[R], int n, int accumulate, Pipe& p, uint32_t sb, uint32_t pitch, int wg, bool leader) {
  const uint32_t bars = sb + BAR_OFF;
  const uint32_t dA0 = desc_lo(sb + wg * 8192, 8192), dB0 = desc_lo(sb + ASZ, TB ? 128 : 16);
  constexpr int KB_STEP = TB ? 16 : 2;
#pragma unroll 1
  for (int kb = 0; kb < n; kb++) {
    if (LEAD && kb == n - LEAD && wg == 1) { if (TB) pipe_drain(p, bars, leader); named_bar(8, 256); }
    mbar_wait(bars + B_FULL + p.r.s * 8, p.r.ph);
    if (kb == 0 && !accumulate && threadIdx.x == 0) { PROF(21 + TB); PROFC(49 - 2 * TB); }
    const uint32_t dA = dA0 + p.r.s * (pitch >> 4), dB = dB0 + p.r.s * (pitch >> 4);
    wg_fence();
    wgmma_ss<TB>(acc, dA, dB, accumulate | kb);
#pragma unroll
    for (int k = 1; k < 4; k++) wgmma_ss<TB>(acc, dA + k * 128, dB + k * KB_STEP, 1);
    wg_commit();
    wg_wait<1>();
    if (p.pending && leader) mbar_arrive(bars + B_EMPTY + p.prev * 8);
    p.pending = true;
    p.prev = p.r.s;
    p.r.next();
  }
  if (LEAD && wg == 0) named_arrive(8, 256);
}

template <int BROW0, int I0, int I1>
__device__ __forceinline__ void gemm2_part(float (&c)[36], uint32_t sb, uint32_t pitch, int wg) {
  const uint32_t dA0 = desc_lo(sb + wg * 8192, 8192), dB0 = desc_lo(sb + ASZ + BROW0 * 128, 16);
  wg_fence();
#pragma unroll
  for (int i = I0; i < I1; i++) {
    const int step = 68 - LAG + (i >> 2);
    if ((i & 3) == 0 && BROW0 == 0) mbar_wait_u(sb + BAR_OFF + B_FULL + (step % ST) * 8, (step / ST) & 1);
    if (i == 4 * LAG - TURN && BROW0 && wg == 0) named_arrive(7, 256);
    wgmma_ss<0>(c, dA0 + (step % ST) * (pitch >> 4) + (i & 3) * 128, dB0 + (step % ST) * (pitch >> 4) + (i & 3) * 2, 1);
  }
  wg_commit();
}
__device__ __forceinline__ void split_acc(const float (&acc)[72], float (&a)[36], float (&b)[36]) {
#pragma unroll
  for (int i = 0; i < 36; i++) { asm volatile("mov.b32 %0, %1;" : "=f"(a[i]) : "f"(acc[i])); asm volatile("mov.b32 %0, %1;" : "=f"(b[i]) : "f"(acc[36 + i])); }
}
template <int NV, int R, class Slice>
__device__ __forceinline__ void gelu_store(const float (&acc)[R], uint32_t bias0, uint32_t bias1, uint32_t sa, Slice slice) {
  const float hbias0 = 0.5f * bf_lo(pin(bias0)), hbias1 = 0.5f * bf_lo(pin(bias1));
  float hx[2][4], t[2][4], half = 0.5f;
  uint32_t pk[4];
#pragma unroll
  for (int j = 0; j <= NV / 4; j++) {
    if (j < NV / 4) {
      if (j >= 2) half = fmaf(t[j & 1][1], 0.f, 0.5f);
#pragma unroll
      for (int u = 0; u < 4; u++) {
        hx[j & 1][u] = fmaf(acc[4 * j + u], half, (u & 2) ? hbias1 : hbias0);
        t[j & 1][u] = tanh_ordered(hx[j & 1][u] * fmaf(hx[j & 1][u] * hx[j & 1][u], 0.2854192651f, 1.5957691216f));
      }
    }
    if (j > 0) {
      const float *hh = hx[(j - 1) & 1], *tt = t[(j - 1) & 1];
      pk[2 * ((j - 1) & 1)] = pack_bf16(fmaf(hh[0], tt[0], hh[0]), fmaf(hh[1], tt[1], hh[1]));
      pk[2 * ((j - 1) & 1) + 1] = pack_bf16(fmaf(hh[2], tt[2], hh[2]), fmaf(hh[3], tt[3], hh[3]));
      if (!(j & 1)) { stsm4_t(sa + (j - 2) * 1024, pk[0], pk[1], pk[2], pk[3]); slice(j / 2 - 1); }
    }
  }
}
struct Role { int half, kind, g2_m, dt, g1_mt, g1_nt, cs; uint32_t pitch; };
__device__ __forceinline__ Role get_role(const RoleMap& roles) {
  uint32_t b, sm;
  asm volatile("mov.u32 %0, %%ctaid.x;" : "=r"(b));
  asm volatile("mov.u32 %0, %%smid;" : "=r"(sm));
  const uint32_t w = roles.role[(roles.by_sm ? sm : b) >> 1];
  const int half = b & 1, kind = w & 3, m = (w >> 4) & 15, dt = (w >> 2) & 3;
  return Role{half, kind, m * 128, dt, half * 18 + (int)((w >> 8) & 31), (int)(w >> 16), (m * 4 + dt) * 2 + half, kind ? (uint32_t)PITCH_B : (uint32_t)PITCH_S};
}
__device__ __forceinline__ int g2_block(int half, int j) { return half * 36 + (j < 12 ? 2 * j : j < 24 ? 2 * j - 23 : j); }
__device__ __forceinline__ int conv_chan(int cs, int i) { return (3 * (cs >> 5) + (i >> 1)) * 64 + ((2 * cs) & 63) + (i & 1); }
__device__ __forceinline__ uint32_t conv_buf(uint32_t sb, int b) { return sb + (b == 3 ? (36 % ST) * PITCH_S : ST * PITCH_S + b * CBUF); }

__global__ void __cluster_dims__(2, 1, 1) __launch_bounds__(384, 1)
fused_kernel(const __nv_bfloat16* __restrict__ q, Scratch* __restrict__ gs, const __nv_bfloat16* __restrict__ b1,
             const __nv_bfloat16* __restrict__ shiftk, const __nv_bfloat16* __restrict__ ssmk, const __nv_bfloat16* __restrict__ ssmD,
             const __grid_constant__ CUtensorMap tmW1, const __grid_constant__ CUtensorMap tmW2, const __grid_constant__ CUtensorMap tmZ,
             const __grid_constant__ CUtensorMap tmH, const __grid_constant__ CUtensorMap tmK, const __grid_constant__ CUtensorMap tmV,
             const __grid_constant__ CUtensorMap tmKV, const __grid_constant__ RoleMap roles, const __nv_bfloat16* __restrict__ b2,
             __nv_bfloat16* __restrict__ out) {
  const int cta = blockIdx.x;
  const int tid = threadIdx.x;
  if (tid == 288) PROFG(0);

  const uint32_t t_start = clock_now();
  if (tid == 256) { prefetch_map(&tmW1); prefetch_map(&tmH); }
  const int lc = (cta + LNROT) & 127;
  const uint32_t do_ln = cta < 128 && tid < 256;
  const int ln_row = lc * 16 + ((tid >> 4) & 15), l16 = tid & 15;
  uint2 xr[9];
  if (do_ln && lc >= TN(QLATE)) spin_until(t_start, TN(QDELAY) + TN(QRAMP) * lc);
#pragma unroll
  for (int i = 0; i < 9; i++) xr[i] = ldg64_if(q + (size_t)ln_row * D_ + i * 64 + l16 * 4, do_ln);
  if (tid == 0) PROF(32);
  const int warp = __shfl_sync(0xffffffffu, tid >> 5, 0);
  const uint32_t sb = __shfl_sync(0xffffffffu, (uint32_t)__cvta_generic_to_shared(smem_raw), 0);
  const uint32_t bars = sb + BAR_OFF;
  const int lane = tid & 31;
  const int wg = warp >> 2;
  constexpr int LN_OFF = ST * PITCH_B;

  if (warp < 8 || warp == 11) {
    asm volatile("barrier.cluster.arrive.relaxed.aligned;" ::: "memory");
    const int hq = (lane & 16) >> 3, hb = (lane & 16) + hq;
    float da[3][4] = {};
#pragma unroll
    for (int i = 0; i < 9; i++) mma16816(da[i % 3], xr[i].x, 0x3f803f80u, xr[i].y, 0x3f803f80u, xr[i].x, xr[i].y);
    const float r1 = ((da[0][2] + da[0][3]) + (da[1][2] + da[1][3])) + (da[2][2] + da[2][3]);
    const float r2 = (lane & 4) ? (da[0][1] + da[1][1]) + da[2][1] : (da[0][0] + da[1][0]) + da[2][0];
    const float s1 = __shfl_sync(0xffffffffu, r1, hq) + __shfl_sync(0xffffffffu, r1, hq + 1);
    const float s2 = (__shfl_sync(0xffffffffu, r2, hb) + __shfl_sync(0xffffffffu, r2, hb + 4)) + (__shfl_sync(0xffffffffu, r2, hb + 9) + __shfl_sync(0xffffffffu, r2, hb + 13));
    if (tid == 0) { asm volatile("" ::"f"(s2) : "memory"); PROF(27); }
    const float mean = s1 * (1.f / D_), var = fmaxf(fmaf(-mean, mean, s2 * (1.f / D_)), 0.f);
    const float rinv = ln_rinv(var), rinv2 = ln_rinv(var * rinv * rinv), scale = rinv * rinv2, shift = -bf_round((mean - bf_round(mean)) * rinv) * rinv2;
    const uint32_t m2 = pack_bf16(mean, mean), hi2 = pack_bf16(scale, scale), lo2 = pack_bf16(scale - bf_lo(hi2), scale - bf_lo(hi2)), sh2 = pack_bf16(shift, shift);
    const uint32_t hi1 = pack_bf16(rinv, rinv);
    asm volatile("{\n.reg .pred p;\nsetp.eq.u32 p, %5, 0;\n@p st.shared.v4.u32 [%0], {%1, %2, %3, %4};\n}" ::"r"(sb + LN_OFF + 18432 + tid), "r"(m2), "r"(hi1),
                 "r"(pack_bf16(rinv - bf_lo(hi1), rinv - bf_lo(hi1))), "r"(0u), "r"(tid & 0x10f) : "memory");
    const uint32_t g0 = 4 * (l16 >> 3) + 2 * (l16 & 1), hrow = sb + LN_OFF + ((tid >> 7) & 1) * 9216 + (tid & 0x70);
    const uint32_t hs0 = hrow + g0 * 128 + ((l16 >> 1) & 3) * 4, hs8 = ((hrow + (l16 >> 1) * 1152) ^ ((l16 >> 1) << 4)) + 1024 + (l16 & 1) * 8;
    uint32_t w[18];
#pragma unroll
    for (int i = 0; i < 18; i++) {
      const uint32_t d = hsub2((i & 1) ? xr[i >> 1].y : xr[i >> 1].x, m2);
      asm("max.u32 %0, %1, 1;" : "=r"(w[i]) : "r"(hfma2(d, hi2, hfma2(d, lo2, sh2))));
    }
#pragma unroll
    for (int i = 0; i < 16; i++) {
      const int gi = 9 * (i >> 1) + (i & 1);
      asm volatile("{\n.reg .pred p;\nsetp.ne.u32 p, %2, 0;\n@p st.shared.u32 [%0], %1;\n}" ::"r"((hs0 ^ ((g0 * 16 + (gi & 7) * 16) & 0x70)) + gi * 128), "r"(w[i]), "r"(do_ln) : "memory");
    }
    asm volatile("{\n.reg .pred p;\nsetp.ne.u32 p, %3, 0;\n@p st.shared.v2.u32 [%0], {%1, %2};\n}" ::"r"(hs8), "r"(w[16]), "r"(w[17]), "r"(do_ln) : "memory");
    if (tid == 0) PROF(13);
    fence_async_smem();
    if (warp < 8) named_arrive(0, 288);
    else {
      named_bar(0, 288);
      if (cta < 128 && elect_one()) {
        tma3d_store(&tmH, (lc >> 2) * 72, (lc & 3) * 2, sb + LN_OFF);
        PROF(29);
        bulk_s2g(gs->stats + lc * 16, sb + LN_OFF + 18432, 256);
        bulk_commit();
      }
      __syncwarp();
    }
  } else if (warp != 8) {
    spin_until(t_start, TN(W9));
  }

  if (wg == 2) {
    asm volatile("setmaxnreg.dec.sync.aligned.u32 56;");
    if (warp != 11) {
      if (elect_one()) {
        if (warp == 8) {
#pragma unroll
          for (int o = 0; o < B_GO; o += 8) mbar_init(bars + o, 1);
        } else if (warp == 9) {
#pragma unroll
          for (int o = B_GO; o < B_RAW + 40; o += 8) mbar_init(bars + o, 1);
        } else {
#pragma unroll
          for (int o = B_RAW + 40; o < B_END; o += 8) mbar_init(bars + o, o < B_EMPTY ? 1 : o < B_CEMPTY ? 2 : 4);
        }
        asm volatile("fence.mbarrier_init.release.cluster;" ::: "memory");
      }
      __syncwarp();
      asm volatile("barrier.cluster.arrive.relaxed.aligned;" ::: "memory");
      if (warp == 9) { prefetch_map(&tmK); prefetch_map(&tmV); prefetch_map(&tmKV); prefetch_map(&tmW2); prefetch_map(&tmZ); }
      if (tid == 256) PROF(35);
    }
    const Role ro = get_role(roles);
    if (warp != 8) asm volatile("barrier.cluster.wait.aligned;" ::: "memory");
    if (warp == 11) {
      if (elect_one()) {
        bulk_wait_all();
        if (cta < 128) flag_add(gs->flags, FL_H + (lc >> 2), 1);
        mbar_arrive(bars + B_KVGO);
        PROFG(1);
      }
      __syncwarp();
      Ring r{0, 1};
      uint32_t ready = 0;
      const uint32_t bsz = ro.pitch - ASZ;
      const uint8_t* src = gs->h + ro.g1_nt * bsz + ST * 73728;
      named_bar(10, 64);
#pragma unroll 1
      for (int i = ST; i < 32; i++) {
        poll_bits(gs->flags, ready, i == 31 ? 0xffffffffu : 1u << i, FL_H + lane, 4u, true);
        mbar_wait(bars + B_EMPTY + r.s * 8, r.ph ^ 1);
        if (elect_one()) bulk_g2s(sb + r.s * ro.pitch + ASZ, src, bsz, bars + B_FULL + r.s * 8);
        if (i == ST && lane == 0) PROF(25);
        if (i == TN(KVGO) && lane == 0) mbar_arrive(bars + B_KVGO);
        if (i == TN(CVGO) && lane == 0) mbar_arrive(bars + B_CVGO);
        src += 73728;
        r.next();
      }
      if (ro.kind != 2) {
        uint32_t look = 0;
#pragma unroll 1
        for (int j = 0; j < 36; j++) {
          const uint8_t* su = gs->u + ((size_t)g2_block(ro.half, j) * D_ + ro.dt * 144) * 128;
          if (j == 0 || j == 12 || j == 24) wait_counter(gs->flags, FL_U + ro.half * 3 + j / 12, j == 24 ? 36u : 48u, look, 100);
          if (ro.kind ? j == 4 : j < 2) mbar_wait_u(bars + B_UDONE + (j ? 8 : 0), 0);
          mbar_wait(bars + B_EMPTY + r.s * 8, r.ph ^ 1);
          if (elect_one()) {
            bulk_g2s(sb + r.s * ro.pitch + ASZ, su + (ro.half ^ 1) * 9216, 9216, bars + B_FULL + r.s * 8);
            bulk_g2s(sb + r.s * ro.pitch + ASZ + 9216, su + ro.half * 9216, 9216, bars + B_FULL + r.s * 8);
          }
          if (j == 9 || j == 21) look = flag_ld(gs->flags, FL_U + ro.half * 3 + j / 12 + 1);
          if (j == 0 && lane == 0) PROF(8);
          r.next();
        }
#pragma unroll 1
        for (int o = lane; o < ST * 73728 / 16 / NG2; o += 32) ((uint4*)gs->h)[ro.cs * (ST * 73728 / 16 / NG2) + o] = make_uint4(0u, 0u, 0u, 0u);
      }
      polling_done(gs->flags, lane);
    } else if (warp == 8) {
      const uint64_t pol = stream_policy();
      Ring r{0, 0};
#pragma unroll 1
      for (int i = 0; i < 32; i++) {
        if (i < ST) spin_until(t_start, TN(A0) + i * TN(AD) + (i >= TN(AN) ? TN(AL) : 0));
        if (i == ST) {
          asm volatile("barrier.cluster.wait.aligned;" ::: "memory");
          if (roles.by_sm) {
            uint32_t sm;
            asm volatile("mov.u32 %0, %%smid;" : "=r"(sm));
            if (elect_one()) { mbar_expect(bars + B_PEER, 8); st_async2(mapa(bars + B_END, ro.half ^ 1), sm, sm, mapa(bars + B_PEER, ro.half ^ 1)); }
            mbar_wait_u(bars + B_PEER, 0);
            if ((lds32(bars + B_END) ^ sm) != 1 || sm >= NCTA) asm volatile("trap;");
          }
        }
        if (i >= ST) mbar_wait(bars + B_EMPTY + r.s * 8, r.ph ^ 1);
        if (elect_one()) {
          mbar_expect(bars + B_FULL + r.s * 8, ro.pitch);
          tma_weights(sb + r.s * ro.pitch, &tmW1, i * 64, ro.g1_mt * 2, bars + B_FULL + r.s * 8, pol);
        }
        r.next();
      }
      if (ro.kind != 2) {
#pragma unroll 1
        for (int j = 0; j < 36; j++) {
          if (j == 4) {
#pragma unroll 1
            for (int k = 0; k < TN(NPF); k++) {
              spin_until(clock_now(), TN(PFGAP));
              const int jj = 4 + 4 * k + ro.dt;
              if (elect_one() && jj < 36) tma_weights_prefetch(&tmW2, g2_block(ro.half, jj) * 64, ro.g2_m >> 6, pol);
            }
            if (ro.kind == 0) mbar_wait_u(bars + B_CEMPTY + 24, 0);
          }
          mbar_wait(bars + B_EMPTY + r.s * 8, r.ph ^ 1);
          if (elect_one()) {
            mbar_expect(bars + B_FULL + r.s * 8, PITCH_S);
            tma_weights(sb + r.s * ro.pitch, &tmW2, g2_block(ro.half, j) * 64, ro.g2_m >> 6, bars + B_FULL + r.s * 8, pol);
          }
          r.next();
        }
        if (lane < 2) mbar_expect(bars + B_RFULL + lane * 8, 9216);
        __syncwarp();
        mbar_wait(bars + B_EMPTY + r.s * 8, r.ph ^ 1);
        if (lane == 0) mbar_arrive_cluster(mapa(bars + B_GO, ro.half ^ 1));
      }
      if (lane == 0) PROF(28);
    } else {
      const uint64_t pol = stream_policy();
      {
        const uint32_t hb = (ro.pitch - ASZ) >> 1, raw = bars + B_RAW + (warp - 9) * 40, dst = sb + ASZ + (warp - 9) * hb;
        const uint8_t* src = gs->h + (2 * ro.g1_nt + warp - 9) * hb;
        auto fetch_h = [&](int i) { if (elect_one()) { mbar_expect(raw + i * 8, hb); bulk_g2s(dst + i * ro.pitch, src + i * 73728, hb, raw + i * 8); } };
        int next = 0;
#pragma unroll 1
        for (int i = -1; i < ST; i++) {
          if (i >= 0) {
#pragma unroll 1
            for (uint32_t tries = 0;; tries++) {
              mbar_wait_u(raw + i * 8, tries & 1);
              if (tid == 288 && i < 2) PROF(38 + i);
              const uint32_t pa = dst + i * ro.pitch + lane * 32 + (lane >> 2) * 4;
              uint32_t m = 1;
#pragma unroll
              for (int j = 0; j < 12; j++) m = min(m, lds32(pa + (j < 9 || ro.kind ? j : 0) * 1024));
              if (__all_sync(0xffffffffu, m)) break;
              if (lane == 0) PROF(26);
              fetch_h(i);
            }
            if (elect_one()) asm volatile("mbarrier.complete_tx.relaxed.cta.shared::cta.b64 [%0], %1;" ::"r"(bars + B_FULL + i * 8), "r"(hb) : "memory");
          }
#pragma unroll 1
          for (const int end = min(next + 2, ST); next < end; next++) {
            if (i < 0) spin_until(t_start, TN(H0) + next * TN(HD));
            fetch_h(next);
            if (next == 0 && tid == 288) PROF(3);
          }
          if (i < 0 && warp == 10) named_arrive(10, 64);
        }
      }
      if (ro.kind == 0) {
        mbar_wait_u(bars + B_KVGO, 0);
        const int cs = ro.cs, grp = (cs / 3) * 2 + warp - 9, cb0 = (cs % 3) * 3;
        const uint32_t kin_s = sb + ST * PITCH_S + (warp - 9) * KVW, kout = kin_s + 2 * KVIN + lane * 176, fb = bars + B_KFULL + (warp - 9) * 16;
        auto fetch = [&](int i) {
          if (elect_one()) {
            mbar_expect(fb + (i & 1) * 8, KVIN);
            tma2d_stream(kin_s + (i & 1) * KVIN, &tmK, (cb0 + i) * 64, grp * 32 - 4, fb + (i & 1) * 8, pol);
            tma2d_stream(kin_s + (i & 1) * KVIN + 4608, &tmV, (cb0 + i) * 64, grp * 32 - 1, fb + (i & 1) * 8, pol);
          }
        };
        if (warp == 10) spin_until(clock_now(), TN(KVSTAG));
        fetch(0);
        uint4 shk = ldg128(shiftk + (cb0 * 64 + lane * 2) * 4);
        const uint32_t dskip = ldg16(ssmD + conv_chan(cs, lane < NCONV ? lane : 0));
#pragma unroll 1
        for (int i = 0; i < 3; i++) {
          const uint32_t w0 = __byte_perm(shk.x, shk.z, 0x5410), w1 = __byte_perm(shk.x, shk.z, 0x7632);
          const uint32_t w2 = __byte_perm(shk.y, shk.w, 0x5410), w3 = __byte_perm(shk.y, shk.w, 0x7632);
          const uint32_t ka = kin_s + (i & 1) * KVIN + lane * 4;
          mbar_wait_u(fb + (i & 1) * 8, i >> 1);
          if (tid == 288 && i < 2) PROF(30 + i);
          if (i < 2) fetch(i + 1);
          shk = ldg128(i < 2 ? shiftk + ((cb0 + i + 1) * 64 + lane * 2) * 4 : ssmk + (size_t)conv_chan(cs, lane < NCONV ? lane : 0) * S_);
          uint32_t kr[20], x[17];
          auto rows = [&](uint32_t from, int j0) {
#pragma unroll
            for (int j = j0; j < j0 + 4; j++) { kr[j] = lds32(from + j * 128); if (j >= 3) x[j - 3] = lds32(from + 4608 + (j - 3) * 128); }
          };
          rows(ka, 0); rows(ka, 4); rows(ka, 8);
          x[0] = hmul2(hfma2(kr[3], w0, hfma2(kr[2], w1, hfma2(kr[1], w2, hmul2(kr[0], w3)))), x[0]);
          if (i) { if (elect_one()) bulk_wait_read(); __syncwarp(); }
#pragma unroll 1
          for (int o = 0; o < 4; o++) {
            const uint32_t from = ka + (o < 3 ? o : 2) * 1024, to = kout + o * 32;
#pragma unroll
            for (int m = 0; m < 8; m += 4) {
#pragma unroll
              for (int j = m + 1; j < m + 5; j++) x[j] = hmul2(hfma2(kr[j + 3], w0, hfma2(kr[j + 2], w1, hfma2(kr[j + 1], w2, hmul2(kr[j], w3)))), x[j]);
#pragma unroll
              for (int c = 0; c < 2; c++) {
                const uint32_t sel = c ? 0x7632 : 0x5410;
                const uint32_t a0 = __byte_perm(x[m + 1], x[m], sel), a1 = __byte_perm(x[m + 2], x[m + 1], sel);
                const uint32_t a2 = __byte_perm(x[m + 3], x[m + 2], sel), a3 = __byte_perm(x[m + 4], x[m + 3], sel);
                sts128(to + c * 5632 + m * 4, a0, a1, a2, a3);
                asm volatile("{\n.reg .pred p;\nsetp.eq.u32 p, %5, 3;\n@p st.shared.v4.u32 [%0], {%1, %2, %3, %4};\n}" ::"r"(to + c * 5632 + m * 4 + 32), "r"(a0), "r"(a1), "r"(a2), "r"(a3), "r"(o) : "memory");
              }
#pragma unroll
              for (int j = m + 12; j < m + 16; j++) { kr[j] = lds32_if(from + j * 128, o < 3); x[j - 3] = lds32_if(from + 4608 + (j - 3) * 128, o < 3); }
            }
#pragma unroll
            for (int j = 1; j < 12; j++) kr[j] = kr[j + 8];
#pragma unroll
            for (int j = 0; j < 9; j++) x[j] = x[j + 8];
          }
          fence_async_smem();
          __syncwarp();
          if (i && elect_one()) { bulk_wait_all(); flag_add(gs->flags, FL_KV + i - 1, 1); }
#pragma unroll 1
          for (int k = 0; k < 64 / KVROWS; k++) {
            if (k) spin_until(clock_now(), TN(KVGAP));
            if (elect_one()) { tma4d_store(&tmKV, (cb0 + i) * 32 + ((k * KVROWS) & 31), (k * KVROWS) >> 5, grp, kin_s + 2 * KVIN + k * KVROWS * 176); bulk_commit(); }
          }
        }
        shk.x = __byte_perm(pack_bf16(bf_lo(shk.x) + bf_lo(dskip), 0.f), shk.x, 0x7610);
        const uint32_t look = flag_ld(gs->flags, FL_KV + warp - 9);
        if (elect_one()) {
          bulk_wait_all();
          flag_add(gs->flags, FL_KV + 2, 1);
          bulk_prefetch(ssmk + (size_t)conv_chan(cs, 2 * (warp - 9)) * S_, 2 * S_ * 2, pol);
          if (warp == 9) PROFG(2);
        }
        __syncwarp();
#pragma unroll 1
        for (int i = warp == 9 ? 0 : 2; i < (warp == 9 ? 2 : NCONV); i++) {
          const int b = i & 3, d = conv_chan(cs, i);
          const uint32_t base = conv_buf(sb, b), cf = bars + B_CFULL + b * 8;
          if (!(i & 1)) wait_counter(gs->flags, FL_KV + (i >> 1), 192u, i < 4 ? look : 0u, 200);
          if (i == 0 || i == 2) mbar_wait_u(bars + B_CVGO, 0);
          if (i == 0 && lane == 0) PROF(23);
          if (i == 3) {
            mbar_wait_u(bars + B_G1DONE, 0);
            if (elect_one()) bulk_prefetch(ssmk + (size_t)conv_chan(cs, 4) * S_, 2 * S_ * 2, pol);
          }
          if (i >= 4) mbar_wait_u(bars + B_CEMPTY + b * 8, 0);
          if (lane == i) sts128(base + CH_OFF, shk.x, shk.y, shk.z, shk.w);
          if (lane >= 27) sts128(base + (lane >= 29 ? CH_OFF + (lane - 32) * 16 : CT_OFF + (lane - 27) * 16), 0u, 0u, 0u, 0u);
          fence_async_smem();
          __syncwarp();
          if (elect_one()) {
            mbar_expect(cf, 4080 + KVT - 32);
            bulk_g2s(base + CT_OFF + 32, gs->kv + (size_t)d * KVT, KVT - 32, cf);
            bulk_g2s_stream(base + CH_OFF + 16, ssmk + (size_t)d * S_ + 8, 4080, cf, pol);
          }
        }
      }
      if (warp == 9) {
        if (elect_one()) {
          const uint32_t bsz = ro.pitch - ASZ;
#pragma unroll 1
          for (int w = 0; w < 2; w++) {
            const uint32_t src = sb + (ro.kind ? (w ? (36 % ST) * PITCH_B + ASZ : ST * PITCH_B) : ((32 % ST) + w) * PITCH_S + ASZ);
            mbar_wait_u(bars + B_USTG + w * 8, 0);
            bulk_s2g(gs->u + (size_t)(2 * ro.g1_mt + w) * D_ * 128 + ro.g1_nt * bsz, src, bsz);
            bulk_commit();
            if (ro.kind && w == 0) gate_arrive(gs->flags, TN(GDELAY) - 512);
            bulk_wait_read();
            mbar_arrive(bars + B_UDONE + w * 8);
            bulk_wait_all();
            flag_add(gs->flags, FL_U + ro.half * 3 + (ro.kind ? 2 : w), 1);
            PROFG(5 + 12 * w);
          }
          if (ro.kind == 0) {
#pragma unroll 1
            for (int i = 0; i < NCONV; i++) {
              mbar_wait_u(bars + B_SFULL + (i & 1) * 8, (i >> 1) & 1);
              bulk_s2g(gs->z + (size_t)chan_pos(conv_chan(ro.cs, i)) * S_, sb + CSTG_OFF + (i & 1) * 4096, 4096);
              bulk_commit();
              if (i == NCONV - 3) gate_arrive(gs->flags, 0);
              bulk_wait_read();
              mbar_arrive(bars + B_SEMPTY + (i & 1) * 8);
            }
            bulk_wait_all();
            flag_add(gs->flags, FL_Z, 1);
            PROFG(6);
          }
        }
      } else if (ro.kind != 2) {
        mbar_wait_u(bars + B_UDONE, 0);
        uint2 gate;
#pragma unroll 1
        for (uint32_t spins = 0;; spins++) {
          asm volatile("ld.relaxed.gpu.global.v2.u32 {%0, %1}, [%2];" : "=r"(gate.x), "=r"(gate.y) : "l"(gs->flags + FL_GATE * 32) : "memory");
          if (gate.x == NCTA) break;
          __nanosleep(100);
          if (spins > SPIN_LIMIT) asm volatile("trap;");
        }
        if (lane == 0) PROF(46);
#pragma unroll 1
        for (int w = 0; w < 2; w++) {
          while (time_now() - gate.y < TN(GDELAY) + w * TN(GDELAY1)) {}
          if (lane == 0) mbar_arrive(bars + B_G2GO + w * 8);
          if (lane == 0 && w == 0) PROF(24);
        }
        wait_counter(gs->flags, FL_Z, 96u, 0, 300);
        spin_until(clock_now(), TN(ZDELAY) + TN(ZRAMP) * cta);
        if (elect_one()) {
          mbar_expect(bars + B_ZFULL, 18432);
          tma2d(sb + ST * ro.pitch, &tmZ, ro.g2_m, ro.dt * 144 + ro.half * 72, bars + B_ZFULL);
          tma2d(sb + ST * ro.pitch + 9216, &tmZ, ro.g2_m + 64, ro.dt * 144 + ro.half * 72, bars + B_ZFULL);
          PROFG(7);
        }
        polling_done(gs->flags, lane);
      }
    }
  } else {
    asm volatile("setmaxnreg.inc.sync.aligned.u32 224;");
    const int wi = warp & 3, g = lane >> 2, qd = lane & 3, wt = tid & 127;
    const bool leader = wt == 0;
    Pipe p{{0, 0}, 0, false, 0};
    asm volatile("barrier.cluster.wait.aligned;" ::: "memory");
    int kind;
    {
      const Role ro = get_role(roles);
      kind = ro.kind;
      const int f0 = ro.g1_mt * 128 + wg * 64 + wi * 16 + g;
      uint32_t bias0 = ldg16(b1 + f0), bias1 = ldg16(b1 + f0 + 8);
      const uint32_t so = ((lane >> 4) * 8 + (lane & 7)) * 128 + (((2 * wi + ((lane >> 3) & 1)) ^ (lane & 7)) << 4);
      if (kind) {
        float acc[96];
        gemm_run<1, LEAD_B>(acc, 32, 0, p, sb, PITCH_B, wg, leader);
        pipe_drain(p, bars, leader);
        if (wg) mbar_wait_u(bars + B_EMPTY + (36 % ST) * 8, ((36 / ST) & 1) ^ 1);
        if (leader) PROF(4 + 10 * wg);
        uint32_t sa = sb + (wg ? (36 % ST) * PITCH_B + ASZ : ST * PITCH_B) + so;
#pragma unroll 1
        for (int c = 0; c < 4; c++, sa += 6144) {
          gelu_store<24>(acc, bias0, bias1, sa, [](int) {});
#pragma unroll
          for (int i = 0; i < 72; i++) acc[i] = acc[i + 24];
        }
        fence_async_smem();
        __syncwarp();
        if (lane == 0) mbar_arrive(bars + B_USTG + wg * 8);
        if (leader) PROF(15 + wg);
      } else {
        const int cB = (g >> 1) & 1, cA = g >> 2, b = 2 * wi + (g & 1);
        const uint32_t toff = pin(CT_OFF + (40 * (2 * cA + cB) + 8 + b - 2 * qd) * 4);
        uint32_t a[16][4];
        auto load_a = [&](uint32_t base, int t, uint32_t on) {
          const uint32_t pt = base + toff + (t >> 1) * 1280 + (t & 1) * 64;
          a[t][0] = lds32_if(pt + 32, on); a[t][1] = lds32_if(pt + 672, on); a[t][2] = lds32_if(pt, on); a[t][3] = lds32_if(pt + 640, on);
        };
        {
          float acc[72];
          gemm_run<1, LEAD_S>(acc, 32, 0, p, sb, PITCH_S, wg, leader);
          if (wg == 1) named_arrive(6, 256);
          mbar_wait_u(bars + B_EMPTY + ((32 % ST) + wg) * 8, ((32 / ST) & 1) ^ 1);
          mbar_wait_u(bars + B_CFULL + wg * 8, 0);
          pipe_drain(p, bars, leader);
          if (leader) mbar_arrive(bars + B_G1DONE);
          if (leader) PROF(4 + 10 * wg);
          if (tid == 128) PROFC(48);
          gelu_store<72>(acc, bias0, bias1, sb + ((32 % ST) + wg) * PITCH_S + ASZ + so, [&](int t) { if (t < 8) load_a(conv_buf(sb, wg), t, 1); });
          fence_async_smem();
          __syncwarp();
          if (lane == 0) mbar_arrive(bars + B_USTG + wg * 8);
          if (leader) PROF(15 + wg);
        }
        const int phi = 2 * cA + (qd >> 1) + cB, pp = cB ? (phi & 3) : ((phi + 3) & 3);
        const int srcB = pin(((pp >> 1) << 4) | ((cB ^ 1) << 3) | ((g & 1) << 2) | ((pp & 1) << 1) | (qd & 1));
        const bool pB1 = cB && phi < 4, pB2 = cB && phi == 4;
        const int word = (8 * cB + 2 * (phi & 3) + (qd & 1)) * 8 + b;
        const uint32_t sto = pin(sb + CSTG_OFF + wg * 4096 + (word ^ (((word >> 5) & 3) << 1)) * 4);
#pragma unroll 1
        for (int i = wg; i < NCONV; i += 2) {
          const uint32_t base = conv_buf(sb, i & 3), next = conv_buf(sb, (i + 2) & 3);
          const uint64_t dH = mkdesc(base + CH_OFF, 16, 128, 0);
          float y[8][16];
          named_bar(6 + wg, 256);
          wg_fence();
#pragma unroll
          for (int t = 0; t < 16; t++) {
            if (t >= 8 && t % CFENCE == 0) wg_fence();
            if (t == CTURN) named_arrive(7 - wg, 256);
#pragma unroll
            for (int cb = t >> 1; cb < 8; cb++) {
              wgmma_rs_n32(y[cb], a[t][0], a[t][1], a[t][2], a[t][3], dH + (32 * cb - 32 * (t >> 1) - 2 * (t & 1) - 1), t);
              const int n = 8 * t - (t >> 1) * ((t - 1) >> 1) - (t >> 1) + cb + 1;
              if (n % CPER == 0 && n / CPER <= 8) load_a(base, 7 + n / CPER, 1);
            }
            if (t == 7 && CEARLY) wg_commit();
          }
          wg_commit();
          const bool more = i + 2 < NCONV;
          if (more) mbar_wait_u(bars + B_CFULL + ((i + 2) & 3) * 8, (i + 2) >> 2);
          mbar_wait_u(bars + B_SEMPTY + wg * 8, ((i >> 1) & 1) ^ 1);
          if (CEARLY) wg_wait<1>();
#pragma unroll
          for (int t = 0; t < CEARLY; t++) load_a(next, t, more);
          wg_wait<0>();
          if (lane == 0) mbar_arrive(bars + B_CEMPTY + (i & 3) * 8);
          if (leader) PROF(40 + i);
          uint32_t P[16], Q[16], R[16], o[8];
#pragma unroll
          for (int j = 0; j < 32; j++) {
            if ((j & 3) == 0 && (j >> 2) >= CEARLY) load_a(next, j >> 2, more);
            float v0 = y[j >> 2][4 * (j & 3)], v1 = y[j >> 2][4 * (j & 3) + 1];
            if (j >= 2) { v0 += y[(j - 2) >> 2][4 * ((j - 2) & 3) + 2]; v1 += y[(j - 2) >> 2][4 * ((j - 2) & 3) + 3]; }
            if (j & 1) R[j >> 1] = shfl_ordered(pack_bf16(v0, v1), lane ^ 16);
            else P[j >> 1] = pack_bf16(v0, v1);
          }
#pragma unroll
          for (int m = 0; m < 16; m++) Q[m] = hadd2(P[m], cA ? R[m] : (m ? R[m - 1] : 0u));
#pragma unroll
          for (int m = 0; m < 8; m++) o[m] = shfl_ordered(pB1 ? Q[2 * m] : (pB2 ? (m ? Q[2 * m - 1] : 0u) : Q[2 * m + 1]), srcB);
#pragma unroll
          for (int m = 0; m < 8; m++) sts32(sto + m * 512, hadd2(pB1 ? Q[2 * m + 1] : Q[2 * m], o[m]));
          fence_async_smem();
          __syncwarp();
          if (lane == 0) mbar_arrive(bars + B_SFULL + wg * 8);
          if (leader && i == 5) PROF(53);
        }
        if (wg == 0) named_bar(6, 256);
      }
    }
    if (kind != 2) {
      const Role ro = get_role(roles);
      const uint32_t pitch = ro.pitch;
      const int s0 = ro.g2_m + wg * 64 + wi * 16 + g;
      const size_t go = (size_t)s0 * D_ + ro.dt * 128 + ro.half * 64 + qd * 8, go8 = (size_t)s0 * D_ + 512 + ro.dt * 16 + ro.half * 8 + qd * 2;
      uint32_t x[2][9], sg[2][9];
      float acc[72];
      mbar_wait_u(bars + B_G2GO + wg * 8, 0);
      gemm_run<0, 0>(acc, XAT + 2 * wg, 0, p, sb, pitch, wg, leader);
#pragma unroll
      for (int J = 0; J < 4; J++) {
        const uint4 v = ldg128(q + go + (J & 1) * 8 * D_ + (J >> 1) * 32);
        x[J & 1][4 * (J >> 1)] = v.x; x[J & 1][4 * (J >> 1) + 1] = v.y; x[J & 1][4 * (J >> 1) + 2] = v.z; x[J & 1][4 * (J >> 1) + 3] = v.w;
      }
      x[0][8] = ldg32(q + go8); x[1][8] = ldg32(q + go8 + 8 * D_);
      const uint4 st0 = ld_l2(gs->stats + s0), st1 = ld_l2(gs->stats + s0 + 8);
      const uint32_t braw0 = ldg16(b2 + s0), braw1 = ldg16(b2 + s0 + 8);
      gemm_run<0, 0>(acc, 20 - XAT, 1, p, sb, pitch, wg, leader);
      {
        const int zw = 8 * wi + (g ^ ((((ro.g2_m >> 6) + wg) & 3) << 1));
        const uint32_t za = sb + ST * pitch + wg * 9216 + qd * 256 + (zw & 3) * 4;
        mbar_wait_u(bars + B_ZFULL, 0);
#pragma unroll
        for (int j = 0; j < 9; j++) {
          sg[0][j] = lds32(za + j * 1024 + (((zw >> 2) ^ (2 * qd)) << 4));
          sg[1][j] = lds32(za + j * 1024 + 128 + (((zw >> 2) ^ (2 * qd + 1)) << 4));
        }
      }
      gemm_run<0, 0>(acc, 1, 1, p, sb, pitch, wg, leader);
#pragma unroll
      for (int j = 0; j < 9; j++) {
        const uint32_t z0 = __byte_perm(sg[0][j], sg[1][j], 0x5410), z1 = __byte_perm(sg[0][j], sg[1][j], 0x7632);
        sg[0][j] = hmul2(ln_apply(x[0][j], st0), z0);
        sg[1][j] = hmul2(ln_apply(x[1][j], st1), z1);
        asm volatile("" : "+r"(sg[0][j]), "+r"(sg[1][j]));
      }
      gemm_run<0, SKEW>(acc, 15 - LAG - 2 * wg, 1, p, sb, pitch, wg, leader);
      const uint32_t rbuf = sb + (68 % ST) * pitch + warp * 2304;
      const uint32_t rdst = mapa(rbuf, ro.half ^ 1), rbar = mapa(bars + B_RFULL + wg * 8, ro.half ^ 1);
      pipe_drain(p, bars, leader);
      if (leader) PROF(9 + 10 * wg);
      if (tid == 128) PROFC(50);
      float cs[36], ck[36];
      split_acc(acc, cs, ck);
      gemm2_part<0, 0, 4 * LAG>(cs, sb, pitch, wg);
      if (KPRE) gemm2_part<72, 0, KPRE>(ck, sb, pitch, wg);
      const float hb0 = fmaf(bf_lo(braw0), 0.5f, __uint_as_float(st0.w)), hb1 = fmaf(bf_lo(braw1), 0.5f, __uint_as_float(st1.w));
      mbar_wait(bars + B_GO, 0);
      wg_wait<KPRE ? 1 : 0>();
      if (leader) PROF(54 + wg);
#pragma unroll
      for (int i = 0; i < 5; i++) {
        const float* c = &cs[8 * i];
        const uint32_t v0 = pack_bf16(fmaf(c[0], 0.5f, hb0), fmaf(c[1], 0.5f, hb0)), v1 = pack_bf16(fmaf(c[2], 0.5f, hb1), fmaf(c[3], 0.5f, hb1));
        if (i < 4) st_async4(rdst + i * 512 + lane * 16, v0, v1, pack_bf16(fmaf(c[4], 0.5f, hb0), fmaf(c[5], 0.5f, hb0)), pack_bf16(fmaf(c[6], 0.5f, hb1), fmaf(c[7], 0.5f, hb1)), rbar);
        else st_async2(rdst + 2048 + lane * 8, v0, v1, rbar);
      }
      if (wg == 1) named_bar(7, 256);
      gemm2_part<72, KPRE, 4 * LAG>(ck, sb, pitch, wg);
      uint32_t rp[18];
      mbar_wait(bars + B_RFULL + wg * 8, 0);
#pragma unroll
      for (int m = 0; m < 4; m++) {
        const uint4 v = lds128(rbuf + m * 512 + lane * 16);
        rp[4 * m] = v.x; rp[4 * m + 1] = v.y; rp[4 * m + 2] = v.z; rp[4 * m + 3] = v.w;
      }
      { const uint2 v = lds64(rbuf + 2048 + lane * 8); rp[16] = v.x; rp[17] = v.y; }
      __nv_bfloat16* o = out + go;
      wg_wait<0>();
      if (leader) PROF(10 + 10 * wg);
      float h[2][4], t[2][4], half = 0.5f;
#pragma unroll
      for (int j = 0; j <= 9; j++) {
        if (j < 9) {
          const uint32_t ra = rp[2 * j], rb = rp[2 * j + 1];
          if (j >= 2) half = fmaf(t[j & 1][3], 0.f, 0.5f);
          h[j & 1][0] = fmaf(ck[4 * j], half, bf_lo(ra)); h[j & 1][1] = fmaf(ck[4 * j + 1], half, bf_hi(ra));
          h[j & 1][2] = fmaf(ck[4 * j + 2], half, bf_lo(rb)); h[j & 1][3] = fmaf(ck[4 * j + 3], half, bf_hi(rb));
#pragma unroll
          for (int u = 0; u < 4; u++) t[j & 1][u] = tanh_ordered(h[j & 1][u]);
        }
        if (j > 0) {
          const int k = j - 1;
          const float* hh = h[k & 1];
          const float* tt = t[k & 1];
          x[0][k] = hfma2(sg[0][k], pack_bf16(fmaf(hh[0], tt[0], hh[0]), fmaf(hh[1], tt[1], hh[1])), x[0][k]);
          x[1][k] = hfma2(sg[1][k], pack_bf16(fmaf(hh[2], tt[2], hh[2]), fmaf(hh[3], tt[3], hh[3])), x[1][k]);
          if ((k & 3) == 3) {
            *(uint4*)(o + (k >> 2) * 32) = make_uint4(x[0][k - 3], x[0][k - 2], x[0][k - 1], x[0][k]);
            *(uint4*)(o + 8 * D_ + (k >> 2) * 32) = make_uint4(x[1][k - 3], x[1][k - 2], x[1][k - 1], x[1][k]);
          }
        }
      }
      *(uint32_t*)(out + go8) = x[0][8];
      *(uint32_t*)(out + go8 + 8 * D_) = x[1][8];
      if (leader) PROF(11 + 7 * wg);
      if (tid == 128) PROFC(51);
    }
  }
}

typedef CUresult (*EncodeFn)(CUtensorMap*, CUtensorMapDataType, cuuint32_t, void*, const cuuint64_t*, const cuuint64_t*, const cuuint32_t*,
                             const cuuint32_t*, CUtensorMapInterleave, CUtensorMapSwizzle, CUtensorMapL2promotion, CUtensorMapFloatOOBfill);

uint32_t role_of_pair(int t) {
  int grp, i;
  if (t < 32) { const int j = t & 7; i = t >> 3; grp = j < 6 ? 1 + j : 12 + 2 * (j - 6); }
  else if (t < 60) { const int j = (t - 32) % 7; i = (t - 32) / 7; grp = j < 5 ? 7 + j : 13 + 2 * (j - 5); }
  else if (t < 62) return 2u | (uint32_t)(14 + 3 * (t - 60)) << 8 | 2u << 16;
  else { grp = 0; i = t - 62; }
  if (grp < 12) return (uint32_t)(i << 2 | grp << 4 | grp << 8 | i << 16);
  const int u = (grp & 1) * 4 + i;
  return (uint32_t)(1 | i << 2 | grp << 4 | (12 + 3 * ((grp - 12) >> 1) + u / 3) << 8 | (u % 3) << 16);
}

}

extern "C" void kernel_launch(void* const* d_in, const int* in_sizes, int n_in, void* d_out, int out_size) {
  (void)in_sizes; (void)n_in; (void)out_size;
  EncodeFn enc = nullptr;
  cudaDriverEntryPointQueryResult qr;
  cudaGetDriverEntryPoint("cuTensorMapEncodeTiled", (void**)&enc, cudaEnableDefault, &qr);
  Scratch* gs = nullptr;
  cudaGetSymbolAddress((void**)&gs, g_scratch);
  void *zp = gs->z, *hp = gs->h, *kvp = gs->kv;
  CUtensorMap tmW1, tmW2, tmZ, tmH, tmK, tmV, tmKV;
  for (int w = 0; w < 2; w++) {
    cuuint64_t gd[2] = {D_, S_};
    cuuint64_t st[1] = {D_ * 2};
    cuuint32_t bx[2] = {64, w ? 33u : 36u};
    cuuint32_t es[2] = {1, 1};
    enc(w ? &tmV : &tmK, CU_TENSOR_MAP_DATA_TYPE_BFLOAT16, 2, d_in[1 + w], gd, st, bx, es, CU_TENSOR_MAP_INTERLEAVE_NONE, CU_TENSOR_MAP_SWIZZLE_NONE,
        CU_TENSOR_MAP_L2_PROMOTION_L2_128B, CU_TENSOR_MAP_FLOAT_OOB_FILL_NONE);
  }
  {
    cuuint64_t gd[4] = {40, D_ / 2, 2, 64};
    cuuint64_t st[3] = {2 * KVT, KVT, 160};
    cuuint32_t bx[4] = {44, KVROWS, 1, 1};
    cuuint32_t es[4] = {1, 1, 1, 1};
    enc(&tmKV, CU_TENSOR_MAP_DATA_TYPE_UINT32, 4, kvp, gd, st, bx, es, CU_TENSOR_MAP_INTERLEAVE_NONE, CU_TENSOR_MAP_SWIZZLE_NONE,
        CU_TENSOR_MAP_L2_PROMOTION_NONE, CU_TENSOR_MAP_FLOAT_OOB_FILL_NONE);
  }
  {
    cuuint64_t gd[3] = {64, 32 * 72, 8};
    cuuint64_t st[2] = {1024, 128};
    cuuint32_t bx[3] = {64, 72, 2};
    cuuint32_t es[3] = {1, 1, 1};
    enc(&tmH, CU_TENSOR_MAP_DATA_TYPE_BFLOAT16, 3, hp, gd, st, bx, es, CU_TENSOR_MAP_INTERLEAVE_NONE, CU_TENSOR_MAP_SWIZZLE_128B,
        CU_TENSOR_MAP_L2_PROMOTION_NONE, CU_TENSOR_MAP_FLOAT_OOB_FILL_NONE);
  }
  for (int w = 0; w < 2; w++) {
    const cuuint64_t M = w ? S_ : F_, K = w ? F_ : S_;
    cuuint64_t gd[3] = {64, K, M / 64};
    cuuint64_t st[2] = {M * 2, 128};
    cuuint32_t bx[3] = {64, 64, 2};
    cuuint32_t es[3] = {1, 1, 1};
    enc(w ? &tmW2 : &tmW1, CU_TENSOR_MAP_DATA_TYPE_BFLOAT16, 3, d_in[w ? 9 : 7], gd, st, bx, es, CU_TENSOR_MAP_INTERLEAVE_NONE,
        CU_TENSOR_MAP_SWIZZLE_128B, CU_TENSOR_MAP_L2_PROMOTION_L2_256B, CU_TENSOR_MAP_FLOAT_OOB_FILL_NONE);
  }
  {
    cuuint64_t gd[2] = {S_, D_};
    cuuint64_t st[1] = {S_ * 2};
    cuuint32_t bx[2] = {64, 72};
    cuuint32_t es[2] = {1, 1};
    enc(&tmZ, CU_TENSOR_MAP_DATA_TYPE_BFLOAT16, 2, zp, gd, st, bx, es, CU_TENSOR_MAP_INTERLEAVE_NONE, CU_TENSOR_MAP_SWIZZLE_128B,
        CU_TENSOR_MAP_L2_PROMOTION_L2_256B, CU_TENSOR_MAP_FLOAT_OOB_FILL_NONE);
  }
  RoleMap roles;
  int dev = 0, sms = 0;
  cudaGetDevice(&dev);
  cudaDeviceGetAttribute(&sms, cudaDevAttrMultiProcessorCount, dev);
  roles.by_sm = sms == NCTA;
  for (int k = 0; k < NCTA / 2; k++) roles.role[k] = role_of_pair(k);
  cudaFuncSetAttribute(fused_kernel, cudaFuncAttributeMaxDynamicSharedMemorySize, SMEM_BYTES);
  fused_kernel<<<NCTA, 384, SMEM_BYTES>>>((const __nv_bfloat16*)d_in[0], gs, (const __nv_bfloat16*)d_in[8], (const __nv_bfloat16*)d_in[3],
                                          (const __nv_bfloat16*)d_in[4], (const __nv_bfloat16*)d_in[5], tmW1, tmW2, tmZ, tmH, tmK, tmV, tmKV,
                                          roles, (const __nv_bfloat16*)d_in[10], (__nv_bfloat16*)d_out);
}
```

```cpp
#include <cuda_runtime.h>
#include <cuda_bf16.h>
#include <cuda.h>
#include <stdint.h>

namespace {

constexpr int S_ = 2048, D_ = 576, F_ = 4608;
constexpr int NCTA = 132, NG2 = 128, NCONV = 6;
constexpr int ST = 5, ASZ = 16384, PITCH_S = ASZ + 144 * 128, PITCH_B = ASZ + 192 * 128;
constexpr int KVIN = (36 + 33) * 128, KVW = 2 * KVIN + 64 * 176;
constexpr int BAR_OFF = ST * PITCH_S + 2 * KVW;
constexpr int SMEM_BYTES = BAR_OFF + 512;
constexpr int KVROWS = 16, LNROT = 120;
constexpr int SKEW = 1;
constexpr int LEAD_S = 3, LEAD_B = 2;
constexpr int CTURN = 14, CPER = 4, CEARLY = 0, CFENCE = 8;
constexpr int TURN = 4, KPRE = 2;
constexpr int XAT = 12;
constexpr int LAG = 4;
constexpr int CBUF = 14464, CH_OFF = 128, CT_OFF = 4224, KVT = 10240;
constexpr int CSTG_OFF = ST * PITCH_S + 3 * CBUF;
constexpr uint32_t SPIN_LIMIT = 1u << 22;

constexpr int FL_H = 0, FL_U = 32, FL_KV = 38, FL_Z = 41, FL_GATE = 42, FL_DONE = 43, FL_N = 44;
struct Scratch {
  uint32_t flags[64 * 32];
  uint4 stats[S_];
  uint8_t h[32 * 72 * 1024];
  uint8_t u[72 * D_ * 128];
  uint8_t kv[D_ * KVT];
  __nv_bfloat16 z[D_ * S_];
};
__device__ __align__(1024) Scratch g_scratch;
extern __shared__ __align__(1024) uint8_t smem_raw[];
#define TUNABLES(X) X(W9, 1200) X(QLATE, 40) X(QDELAY, 400) X(QRAMP, 5) X(A0, 1200) X(AD, 300) X(AN, 5) X(AL, 0) X(BA, 0) X(BH, 0) X(G1GO, 0) X(H0, 3100) X(HD, 400) X(KVGAP, 100) X(KVSTAG, 1200) X(KVGO, 6) X(CVGO, 31) X(GDELAY, 608) X(GDELAY1, 256) X(ZDELAY, 3000) X(ZRAMP, 40) X(NPF, 0) X(PFGAP, 600)
#define X(k, v) constexpr int T_##k = v;
TUNABLES(X)
#undef X
#define TN(k) T_##k
struct RoleMap { uint32_t role[NCTA / 2]; uint32_t by_sm; };
#define PROF(i) do {} while (0)
#define PROFG(i) do {} while (0)
#define PROFC(i) do {} while (0)

template<int TB> __device__ __forceinline__ void wgmma_ss(float (&d)[96], uint32_t da, uint32_t db, int sd) {
  asm volatile("{\n.reg .pred p;\n.reg .b64 a, b;\nsetp.ne.b32 p, %98, 0;\nmov.b64 a, {%96, %100};\nmov.b64 b, {%97, %101};\n"
    "wgmma.mma_async.sync.aligned.m64n192k16.f32.bf16.bf16 {%0, %1, %2, %3, %4, %5, %6, %7, %8, %9, %10, %11, %12, %13, %14, %15, %16, %17, %18, %19, %20, %21, %22, %23, %24, %25, %26, %27, %28, %29, %30, %31, %32, %33, %34, %35, %36, %37, %38, %39, %40, %41, %42, %43, %44, %45, %46, %47, %48, %49, %50, %51, %52, %53, %54, %55, %56, %57, %58, %59, %60, %61, %62, %63, %64, %65, %66, %67, %68, %69, %70, %71, %72, %73, %74, %75, %76, %77, %78, %79, %80, %81, %82, %83, %84, %85, %86, %87, %88, %89, %90, %91, %92, %93, %94, %95}, a, b, p, 1, 1, 1, %99;\n}\n"
    : "+f"(d[0]), "+f"(d[1]), "+f"(d[2]), "+f"(d[3]), "+f"(d[4]), "+f"(d[5]), "+f"(d[6]), "+f"(d[7]), "+f"(d[8]), "+f"(d[9]), "+f"(d[10]), "+f"(d[11]), "+f"(d[12]), "+f"(d[13]), "+f"(d[14]), "+f"(d[15]), "+f"(d[16]), "+f"(d[17]), "+f"(d[18]), "+f"(d[19]), "+f"(d[20]), "+f"(d[21]), "+f"(d[22]), "+f"(d[23]), "+f"(d[24]), "+f"(d[25]), "+f"(d[26]), "+f"(d[27]), "+f"(d[28]), "+f"(d[29]), "+f"(d[30]), "+f"(d[31]), "+f"(d[32]), "+f"(d[33]), "+f"(d[34]), "+f"(d[35]), "+f"(d[36]), "+f"(d[37]), "+f"(d[38]), "+f"(d[39]), "+f"(d[40]), "+f"(d[41]), "+f"(d[42]), "+f"(d[43]), "+f"(d[44]), "+f"(d[45]), "+f"(d[46]), "+f"(d[47]), "+f"(d[48]), "+f"(d[49]), "+f"(d[50]), "+f"(d[51]), "+f"(d[52]), "+f"(d[53]), "+f"(d[54]), "+f"(d[55]), "+f"(d[56]), "+f"(d[57]), "+f"(d[58]), "+f"(d[59]), "+f"(d[60]), "+f"(d[61]), "+f"(d[62]), "+f"(d[63]), "+f"(d[64]), "+f"(d[65]), "+f"(d[66]), "+f"(d[67]), "+f"(d[68]), "+f"(d[69]), "+f"(d[70]), "+f"(d[71]), "+f"(d[72]), "+f"(d[73]), "+f"(d[74]), "+f"(d[75]), "+f"(d[76]), "+f"(d[77]), "+f"(d[78]), "+f"(d[79]), "+f"(d[80]), "+f"(d[81]), "+f"(d[82]), "+f"(d[83]), "+f"(d[84]), "+f"(d[85]), "+f"(d[86]), "+f"(d[87]), "+f"(d[88]), "+f"(d[89]), "+f"(d[90]), "+f"(d[91]), "+f"(d[92]), "+f"(d[93]), "+f"(d[94]), "+f"(d[95])
    : "r"(da), "r"(db), "r"(sd), "n"(TB), "r"(0x40000040u), "r"(TB ? 0x40u : 0x40000040u));
}
template<int TB> __device__ __forceinline__ void wgmma_ss(float (&d)[72], uint32_t da, uint32_t db, int sd) {
  asm volatile("{\n.reg .pred p;\n.reg .b64 a, b;\nsetp.ne.b32 p, %74, 0;\nmov.b64 a, {%72, %76};\nmov.b64 b, {%73, %77};\n"
    "wgmma.mma_async.sync.aligned.m64n144k16.f32.bf16.bf16 {%0, %1, %2, %3, %4, %5, %6, %7, %8, %9, %10, %11, %12, %13, %14, %15, %16, %17, %18, %19, %20, %21, %22, %23, %24, %25, %26, %27, %28, %29, %30, %31, %32, %33, %34, %35, %36, %37, %38, %39, %40, %41, %42, %43, %44, %45, %46, %47, %48, %49, %50, %51, %52, %53, %54, %55, %56, %57, %58, %59, %60, %61, %62, %63, %64, %65, %66, %67, %68, %69, %70, %71}, a, b, p, 1, 1, 1, %75;\n}\n"
    : "+f"(d[0]), "+f"(d[1]), "+f"(d[2]), "+f"(d[3]), "+f"(d[4]), "+f"(d[5]), "+f"(d[6]), "+f"(d[7]), "+f"(d[8]), "+f"(d[9]), "+f"(d[10]), "+f"(d[11]), "+f"(d[12]), "+f"(d[13]), "+f"(d[14]), "+f"(d[15]), "+f"(d[16]), "+f"(d[17]), "+f"(d[18]), "+f"(d[19]), "+f"(d[20]), "+f"(d[21]), "+f"(d[22]), "+f"(d[23]), "+f"(d[24]), "+f"(d[25]), "+f"(d[26]), "+f"(d[27]), "+f"(d[28]), "+f"(d[29]), "+f"(d[30]), "+f"(d[31]), "+f"(d[32]), "+f"(d[33]), "+f"(d[34]), "+f"(d[35]), "+f"(d[36]), "+f"(d[37]), "+f"(d[38]), "+f"(d[39]), "+f"(d[40]), "+f"(d[41]), "+f"(d[42]), "+f"(d[43]), "+f"(d[44]), "+f"(d[45]), "+f"(d[46]), "+f"(d[47]), "+f"(d[48]), "+f"(d[49]), "+f"(d[50]), "+f"(d[51]), "+f"(d[52]), "+f"(d[53]), "+f"(d[54]), "+f"(d[55]), "+f"(d[56]), "+f"(d[57]), "+f"(d[58]), "+f"(d[59]), "+f"(d[60]), "+f"(d[61]), "+f"(d[62]), "+f"(d[63]), "+f"(d[64]), "+f"(d[65]), "+f"(d[66]), "+f"(d[67]), "+f"(d[68]), "+f"(d[69]), "+f"(d[70]), "+f"(d[71])
    : "r"(da), "r"(db), "r"(sd), "n"(TB), "r"(0x40000040u), "r"(TB ? 0x40u : 0x40000040u));
}
template<int TB> __device__ __forceinline__ void wgmma_ss(float (&d)[36], uint32_t da, uint32_t db, int sd) {
  asm volatile("{\n.reg .pred p;\n.reg .b64 a, b;\nsetp.ne.b32 p, %38, 0;\nmov.b64 a, {%36, %40};\nmov.b64 b, {%37, %41};\n"
    "wgmma.mma_async.sync.aligned.m64n72k16.f32.bf16.bf16 {%0, %1, %2, %3, %4, %5, %6, %7, %8, %9, %10, %11, %12, %13, %14, %15, %16, %17, %18, %19, %20, %21, %22, %23, %24, %25, %26, %27, %28, %29, %30, %31, %32, %33, %34, %35}, a, b, p, 1, 1, 1, %39;\n}\n"
    : "+f"(d[0]), "+f"(d[1]), "+f"(d[2]), "+f"(d[3]), "+f"(d[4]), "+f"(d[5]), "+f"(d[6]), "+f"(d[7]), "+f"(d[8]), "+f"(d[9]), "+f"(d[10]), "+f"(d[11]), "+f"(d[12]), "+f"(d[13]), "+f"(d[14]), "+f"(d[15]), "+f"(d[16]), "+f"(d[17]), "+f"(d[18]), "+f"(d[19]), "+f"(d[20]), "+f"(d[21]), "+f"(d[22]), "+f"(d[23]), "+f"(d[24]), "+f"(d[25]), "+f"(d[26]), "+f"(d[27]), "+f"(d[28]), "+f"(d[29]), "+f"(d[30]), "+f"(d[31]), "+f"(d[32]), "+f"(d[33]), "+f"(d[34]), "+f"(d[35])
    : "r"(da), "r"(db), "r"(sd), "n"(TB), "r"(0x40000040u), "r"(TB ? 0x40u : 0x40000040u));
}
__device__ __forceinline__ void wgmma_rs_n32(float (&d)[16], uint32_t a0, uint32_t a1, uint32_t a2, uint32_t a3, uint64_t db, int sd) {
  asm volatile("{\n.reg .pred p;\nsetp.ne.b32 p, %21, 0;\n"
    "wgmma.mma_async.sync.aligned.m64n32k16.f32.bf16.bf16 {%0, %1, %2, %3, %4, %5, %6, %7, %8, %9, %10, %11, %12, %13, %14, %15}, {%16, %17, %18, %19}, %20, p, 1, 1, 0;\n}\n"
    : "+f"(d[0]), "+f"(d[1]), "+f"(d[2]), "+f"(d[3]), "+f"(d[4]), "+f"(d[5]), "+f"(d[6]), "+f"(d[7]), "+f"(d[8]), "+f"(d[9]), "+f"(d[10]), "+f"(d[11]), "+f"(d[12]), "+f"(d[13]), "+f"(d[14]), "+f"(d[15])
    : "r"(a0), "r"(a1), "r"(a2), "r"(a3), "l"(db), "r"(sd));
}

__device__ __forceinline__ void wg_fence() { asm volatile("wgmma.fence.sync.aligned;" ::: "memory"); }
__device__ __forceinline__ void wg_commit() { asm volatile("wgmma.commit_group.sync.aligned;" ::: "memory"); }
template <int n> __device__ __forceinline__ void wg_wait() { asm volatile("wgmma.wait_group.sync.aligned %0;" ::"n"(n) : "memory"); }
__device__ __forceinline__ uint64_t mkdesc(uint32_t addr, uint32_t lbo, uint32_t sbo, uint32_t sw) {
  return (uint64_t)((addr & 0x3FFFF) >> 4) | ((uint64_t)(lbo >> 4) << 16) | ((uint64_t)(sbo >> 4) << 32) | ((uint64_t)sw << 62);
}
__device__ __forceinline__ void mbar_init(uint32_t a, int c) { asm volatile("mbarrier.init.shared::cta.b64 [%0], %1;" ::"r"(a), "r"(c)); }
__device__ __forceinline__ void mbar_expect(uint32_t a, uint32_t b) { asm volatile("mbarrier.arrive.expect_tx.shared::cta.b64 _, [%0], %1;" ::"r"(a), "r"(b) : "memory"); }
__device__ __forceinline__ void mbar_arrive(uint32_t a) { asm volatile("mbarrier.arrive.shared::cta.b64 _, [%0];" ::"r"(a) : "memory"); }
__device__ __forceinline__ void mbar_arrive_cluster(uint32_t raddr) { asm volatile("mbarrier.arrive.shared::cluster.b64 _, [%0];" ::"r"(raddr) : "memory"); }
__device__ __forceinline__ uint32_t mapa(uint32_t a, uint32_t cta) { uint32_t r; asm("mapa.shared::cluster.u32 %0, %1, %2;" : "=r"(r) : "r"(a), "r"(cta)); return r; }
__device__ __forceinline__ void mbar_wait(uint32_t a, uint32_t ph) {
  asm volatile(
      "{\n.reg .pred p;\n.reg .u32 c;\nmov.u32 c, 0;\n"
      "WAIT_LOOP:\nmbarrier.try_wait.parity.shared::cta.b64 p, [%0], %1;\n@p bra WAIT_DONE;\n"
      "add.u32 c, c, 1;\nsetp.lt.u32 p, c, %2;\n@p bra WAIT_LOOP;\ntrap;\nWAIT_DONE:\n}" ::"r"(a), "r"(ph), "n"(SPIN_LIMIT) : "memory");
}
__device__ __forceinline__ void mbar_wait_u(uint32_t a, uint32_t ph) {
  asm volatile("{\n.reg .pred p;\nWAIT_LOOP:\nmbarrier.try_wait.parity.shared::cta.b64 p, [%0], %1;\n@!p bra WAIT_LOOP;\n}" ::"r"(a), "r"(ph) : "memory");
}
__device__ __forceinline__ uint32_t desc_lo(uint32_t addr, uint32_t lbo) { return ((addr & 0x3FFFF) >> 4) | ((lbo >> 4) << 16); }
__device__ __forceinline__ void tma2d(uint32_t dst, const CUtensorMap* m, int c0, int c1, uint32_t bar) {
  asm volatile("cp.async.bulk.tensor.2d.shared::cluster.global.mbarrier::complete_tx::bytes [%0], [%1, {%3, %4}], [%2];" ::"r"(dst), "l"(m), "r"(bar), "r"(c0), "r"(c1) : "memory");
}
__device__ __forceinline__ void bulk_g2s(uint32_t dst, const void* src, uint32_t sz, uint32_t bar) {
  asm volatile("cp.async.bulk.shared::cluster.global.mbarrier::complete_tx::bytes [%0], [%1], %2, [%3];" ::"r"(dst), "l"(src), "r"(sz), "r"(bar) : "memory");
}
__device__ __forceinline__ void bulk_s2g(void* dst, uint32_t src, uint32_t sz) {
  asm volatile("cp.async.bulk.global.shared::cta.bulk_group [%0], [%1], %2;" ::"l"(dst), "r"(src), "r"(sz) : "memory");
}
__device__ __forceinline__ uint64_t stream_policy() {
  uint64_t p;
  asm volatile("createpolicy.fractional.L2::evict_first.b64 %0, 1.0;" : "=l"(p));
  return p;
}
__device__ __forceinline__ void tma_weights(uint32_t dst, const CUtensorMap* m, int k0, int mchunk, uint32_t bar, uint64_t pol) {
  asm volatile("cp.async.bulk.tensor.3d.shared::cluster.global.mbarrier::complete_tx::bytes.L2::cache_hint [%0], [%1, {%6, %3, %4}], [%2], %5;"
               ::"r"(dst), "l"(m), "r"(bar), "r"(k0), "r"(mchunk), "l"(pol), "r"(0) : "memory");
}
__device__ __forceinline__ void tma_weights_prefetch(const CUtensorMap* m, int k0, int mchunk, uint64_t pol) {
  asm volatile("cp.async.bulk.prefetch.tensor.3d.L2.global.L2::cache_hint [%0, {%4, %1, %2}], %3;" ::"l"(m), "r"(k0), "r"(mchunk), "l"(pol), "r"(0) : "memory");
}
__device__ __forceinline__ bool elect_one() {
  uint32_t p;
  asm volatile("{\n.reg .pred P;\nelect.sync _|P, 0xffffffff;\nselp.u32 %0, 1, 0, P;\n}" : "=r"(p));
  return p;
}
__device__ __forceinline__ void bulk_g2s_stream(uint32_t dst, const void* src, uint32_t sz, uint32_t bar, uint64_t pol) {
  asm volatile("cp.async.bulk.shared::cluster.global.mbarrier::complete_tx::bytes.L2::cache_hint [%0], [%1], %2, [%3], %4;"
               ::"r"(dst), "l"(src), "r"(sz), "r"(bar), "l"(pol) : "memory");
}
__device__ __forceinline__ void tma3d_store(const CUtensorMap* m, int c1, int c2, uint32_t src) {
  asm volatile("cp.async.bulk.tensor.3d.global.shared::cta.bulk_group [%0, {%4, %2, %3}], [%1];" ::"l"(m), "r"(src), "r"(c1), "r"(c2), "r"(0) : "memory");
}
__device__ __forceinline__ void tma2d_stream(uint32_t dst, const CUtensorMap* m, int c0, int c1, uint32_t bar, uint64_t pol) {
  asm volatile("cp.async.bulk.tensor.2d.shared::cluster.global.mbarrier::complete_tx::bytes.L2::cache_hint [%0], [%1, {%3, %4}], [%2], %5;"
               ::"r"(dst), "l"(m), "r"(bar), "r"(c0), "r"(c1), "l"(pol) : "memory");
}
__device__ __forceinline__ void tma4d_store(const CUtensorMap* m, int c1, int c2, int c3, uint32_t src) {
  asm volatile("cp.async.bulk.tensor.4d.global.shared::cta.bulk_group [%0, {%5, %2, %3, %4}], [%1];" ::"l"(m), "r"(src), "r"(c1), "r"(c2), "r"(c3), "r"(0) : "memory");
}
__device__ __forceinline__ void bulk_commit() { asm volatile("cp.async.bulk.commit_group;" ::: "memory"); }
__device__ __forceinline__ void bulk_wait_all() { asm volatile("cp.async.bulk.wait_group 0;" ::: "memory"); }
__device__ __forceinline__ void fence_async_smem() { asm volatile("fence.proxy.async.shared::cta;" ::: "memory"); }
__device__ __forceinline__ void fence_async_global() { asm volatile("fence.proxy.async.global;" ::: "memory"); }
__device__ __forceinline__ void named_bar(int id, int n) { asm volatile("bar.sync %0, %1;" ::"r"(id), "r"(n) : "memory"); }
__device__ __forceinline__ void named_arrive(int id, int n) { asm volatile("bar.arrive %0, %1;" ::"r"(id), "r"(n) : "memory"); }
__device__ __forceinline__ void flag_add(uint32_t* f, int i, uint32_t v) { asm volatile("red.relaxed.gpu.global.add.u32 [%0], %1;" ::"l"(f + i * 32), "r"(v) : "memory"); }
__device__ __forceinline__ uint32_t flag_ld(uint32_t* f, int i) { uint32_t v; asm volatile("ld.relaxed.gpu.global.u32 %0, [%1];" : "=r"(v) : "l"(f + i * 32) : "memory"); return v; }
__device__ __forceinline__ void prefetch_map(const CUtensorMap* m) { asm volatile("prefetch.tensormap [%0];" ::"l"(m) : "memory"); }
__device__ __forceinline__ void stsm4_t(uint32_t a, uint32_t r0, uint32_t r1, uint32_t r2, uint32_t r3) {
  asm volatile("stmatrix.sync.aligned.m8n8.x4.trans.shared.b16 [%0], {%1, %2, %3, %4};" ::"r"(a), "r"(r0), "r"(r1), "r"(r2), "r"(r3) : "memory");
}
__device__ __forceinline__ uint32_t lds32(uint32_t a) { uint32_t v; asm volatile("ld.shared.u32 %0, [%1];" : "=r"(v) : "r"(a) : "memory"); return v; }
__device__ __forceinline__ void sts32(uint32_t a, uint32_t v) { asm volatile("st.shared.u32 [%0], %1;" ::"r"(a), "r"(v) : "memory"); }
__device__ __forceinline__ uint4 ld_l2(const uint4* p) { uint4 v; asm volatile("ld.relaxed.gpu.global.v4.u32 {%0, %1, %2, %3}, [%4];" : "=r"(v.x), "=r"(v.y), "=r"(v.z), "=r"(v.w) : "l"(p) : "memory"); return v; }
__device__ __forceinline__ void sts128(uint32_t a, uint32_t x, uint32_t y, uint32_t z, uint32_t w) { asm volatile("st.shared.v4.u32 [%0], {%1, %2, %3, %4};" ::"r"(a), "r"(x), "r"(y), "r"(z), "r"(w) : "memory"); }
__device__ __forceinline__ uint4 lds128(uint32_t a) { uint4 v; asm volatile("ld.shared.v4.u32 {%0, %1, %2, %3}, [%4];" : "=r"(v.x), "=r"(v.y), "=r"(v.z), "=r"(v.w) : "r"(a) : "memory"); return v; }
__device__ __forceinline__ void st_async4(uint32_t raddr, uint32_t a, uint32_t b, uint32_t c, uint32_t d, uint32_t rbar) {
  asm volatile("st.async.weak.shared::cluster.mbarrier::complete_tx::bytes.v4.b32 [%0], {%1, %2, %3, %4}, [%5];" ::"r"(raddr), "r"(a), "r"(b), "r"(c), "r"(d), "r"(rbar) : "memory");
}
__device__ __forceinline__ uint32_t pack_bf16(float lo, float hi) { uint32_t r; asm("cvt.rn.bf16x2.f32 %0, %1, %2;" : "=r"(r) : "f"(hi), "f"(lo)); return r; }
__device__ __forceinline__ float bf_lo(uint32_t v) { return __uint_as_float(v << 16); }
__device__ __forceinline__ float bf_hi(uint32_t v) { return __uint_as_float(v & 0xffff0000u); }
__device__ __forceinline__ float bf_round(float x) { return bf_lo(pack_bf16(x, 0.f)); }
__device__ __forceinline__ uint32_t hmul2(uint32_t a, uint32_t b) { uint32_t r; asm("mul.rn.bf16x2 %0, %1, %2;" : "=r"(r) : "r"(a), "r"(b)); return r; }
__device__ __forceinline__ uint32_t hsub2(uint32_t a, uint32_t b) { uint32_t r; asm("sub.rn.bf16x2 %0, %1, %2;" : "=r"(r) : "r"(a), "r"(b)); return r; }
__device__ __forceinline__ uint32_t hfma2(uint32_t a, uint32_t b, uint32_t c) { uint32_t r; asm("fma.rn.bf16x2 %0, %1, %2, %3;" : "=r"(r) : "r"(a), "r"(b), "r"(c)); return r; }
__device__ __forceinline__ uint4 ldg128(const void* p) { uint4 v; asm volatile("ld.global.nc.v4.u32 {%0, %1, %2, %3}, [%4];" : "=r"(v.x), "=r"(v.y), "=r"(v.z), "=r"(v.w) : "l"(p)); return v; }
__device__ __forceinline__ uint32_t ldg16(const void* p) { uint32_t v; asm volatile("ld.global.nc.u16 %0, [%1];" : "=r"(v) : "l"(p)); return v; }
__device__ __forceinline__ float tanh_ordered(float x) { float y; asm volatile("tanh.approx.f32 %0, %1;" : "=f"(y) : "f"(x)); return y; }
__device__ __forceinline__ void mma16816(float (&d)[4], uint32_t a0, uint32_t a1, uint32_t a2, uint32_t a3, uint32_t b0, uint32_t b1) {
  asm("mma.sync.aligned.m16n8k16.row.col.f32.bf16.bf16.f32 {%0, %1, %2, %3}, {%4, %5, %6, %7}, {%8, %9}, {%0, %1, %2, %3};"
      : "+f"(d[0]), "+f"(d[1]), "+f"(d[2]), "+f"(d[3]) : "r"(a0), "r"(a1), "r"(a2), "r"(a3), "r"(b0), "r"(b1));
}
__device__ __forceinline__ uint32_t hadd2(uint32_t a, uint32_t b) { uint32_t r; asm("add.rn.bf16x2 %0, %1, %2;" : "=r"(r) : "r"(a), "r"(b)); return r; }
__device__ __forceinline__ uint32_t ldg32(const void* p) { uint32_t v; asm volatile("ld.global.nc.L1::no_allocate.u32 %0, [%1];" : "=r"(v) : "l"(p)); return v; }
__device__ __forceinline__ uint2 lds64(uint32_t a) { uint2 v; asm volatile("ld.shared.v2.u32 {%0, %1}, [%2];" : "=r"(v.x), "=r"(v.y) : "r"(a) : "memory"); return v; }
__device__ __forceinline__ uint32_t lds32_if(uint32_t a, uint32_t on) {
  uint32_t v;
  asm volatile("{\n.reg .pred p;\nsetp.ne.u32 p, %2, 0;\n@p ld.shared.u32 %0, [%1];\n}" : "=r"(v) : "r"(a), "r"(on) : "memory");
  return v;
}
__device__ __forceinline__ uint32_t clock_now() { uint32_t t; asm volatile("mov.u32 %0, %%clock;" : "=r"(t)); return t; }
__device__ __forceinline__ uint32_t time_now() { uint32_t t; asm volatile("mov.u32 %0, %%globaltimer_lo;" : "=r"(t)); return t; }
__device__ __forceinline__ void spin_until(uint32_t t0, uint32_t n) { while (clock_now() - t0 < n) {} }
__device__ __forceinline__ uint2 ldg64_if(const void* p, uint32_t on) {
  uint2 v;
  asm volatile("{\n.reg .pred p;\nsetp.ne.u32 p, %3, 0;\n@p ld.global.nc.v2.u32 {%0, %1}, [%2];\n}" : "=r"(v.x), "=r"(v.y) : "l"(p), "r"(on));
  return v;
}
template <class T> __device__ __forceinline__ T pin(T v) { asm volatile("" : "+r"(v)); return v; }
__device__ __forceinline__ void st_async2(uint32_t raddr, uint32_t a, uint32_t b, uint32_t rbar) {
  asm volatile("st.async.weak.shared::cluster.mbarrier::complete_tx::bytes.v2.b32 [%0], {%1, %2}, [%3];" ::"r"(raddr), "r"(a), "r"(b), "r"(rbar) : "memory");
}
__device__ __forceinline__ void bulk_prefetch(const void* src, uint32_t sz, uint64_t pol) {
  asm volatile("cp.async.bulk.prefetch.L2.global.L2::cache_hint [%0], %1, %2;" ::"l"(src), "r"(sz), "l"(pol) : "memory");
}
__device__ __forceinline__ void bulk_wait_read() { asm volatile("cp.async.bulk.wait_group.read 0;" ::: "memory"); }
__device__ __forceinline__ uint32_t shfl_ordered(uint32_t v, int src) { uint32_t r; asm volatile("shfl.sync.idx.b32 %0, %1, %2, 0x1f, 0xffffffff;" : "=r"(r) : "r"(v), "r"(src)); return r; }
__device__ __forceinline__ int chan_pos(int d) {
  return d < 512 ? 72 * (d >> 6) + ((d & 33) | ((d & 6) << 2) | ((d >> 2) & 6)) : 72 * ((d - 512) >> 3) + 64 + (d & 7);
}

struct Ring {
  uint32_t s, ph;
  __device__ __forceinline__ void next() { if (++s == ST) { s = 0; ph ^= 1; } }
};
constexpr int B_FULL = 0, B_GO = 40, B_CFULL = 48, B_SEMPTY = 80, B_ZFULL = 96, B_RFULL = 104, B_UDONE = 120, B_KFULL = 136, B_RAW = 168, B_CVGO = 248, B_PEER = 256, B_G2GO = 264,
              B_EMPTY = 280, B_KVGO = 320, B_G1DONE = 328,
              B_CEMPTY = 336, B_SFULL = 368, B_USTG = 384, B_END = 400;

__device__ __forceinline__ void poll_once(uint32_t* f, uint32_t& ready, int idx, uint32_t want, bool active) {
  bool ok = false;
  if (active) ok = flag_ld(f, idx) == want;
  const uint32_t seen = __ballot_sync(0xffffffffu, ok);
  if (seen & ~ready) fence_async_global();
  ready |= seen;
}
__device__ __forceinline__ void poll_bits(uint32_t* f, uint32_t& ready, uint32_t bits, int idx, uint32_t want, bool active) {
  for (uint32_t spins = 0; (ready & bits) != bits; spins++) {
    poll_once(f, ready, idx, want, active);
    if (spins > SPIN_LIMIT) asm volatile("trap;");
  }
}
__device__ __forceinline__ void wait_counter(uint32_t* f, int idx, uint32_t want, uint32_t first, uint32_t nap) {
#pragma unroll 1
  for (uint32_t spins = 0; first != want; spins++) {
    if (spins) __nanosleep(nap);
    first = flag_ld(f, idx);
    if (spins > SPIN_LIMIT) asm volatile("trap;");
  }
  fence_async_global();
}

__device__ __forceinline__ void gate_arrive(uint32_t* f, uint32_t back) {
  asm volatile("red.relaxed.gpu.global.max.u32 [%0], %1;" ::"l"(f + FL_GATE * 32 + 1), "r"(time_now() - back) : "memory");
  flag_add(f, FL_GATE, 1);
}

__device__ __forceinline__ float ln_rinv(float var) {
  float rt, rinv;
  asm("sqrt.approx.ftz.f32 %0, %1;" : "=f"(rt) : "f"(bf_round(bf_round(var) + 1e-5f)));
  asm("rcp.approx.ftz.f32 %0, %1;" : "=f"(rinv) : "f"(bf_round(rt)));
  return rinv;
}
__device__ __forceinline__ uint32_t ln_apply(uint32_t x, const uint4& st) {
  const uint32_t d = hsub2(x, st.x);
  return hfma2(d, st.y, hmul2(d, st.z));
}

__device__ __forceinline__ void polling_done(uint32_t* f, int lane) {
  unsigned old = 0;
  if (lane == 0) asm volatile("atom.relaxed.gpu.global.add.u32 %0, [%1], 1;" : "=r"(old) : "l"(f + FL_DONE * 32) : "memory");
  old = __shfl_sync(0xffffffffu, old, 0);
  if (old == NCTA + NG2 - 1) {
#pragma unroll 1
    for (int i = lane; i < FL_N; i += 32) *(uint2*)(f + i * 32) = make_uint2(0u, 0u);
  }
}

struct Pipe { Ring r; uint32_t prev; bool pending; int cnt; };
__device__ __forceinline__ void pipe_drain(Pipe& p, uint32_t bars, bool leader) {
  wg_wait<0>();
  if (leader) mbar_arrive(bars + B_EMPTY + p.prev * 8);
  p.pending = false;
}
template <int TB, int LEAD, int R>
__device__ __forceinline__ void gemm_run(float (&acc)[R], int n, int accumulate, Pipe& p, uint32_t sb, uint32_t pitch, int wg, bool leader) {
  const uint32_t bars = sb + BAR_OFF;
  const uint32_t dA0 = desc_lo(sb + wg * 8192, 8192), dB0 = desc_lo(sb + ASZ, TB ? 128 : 16);
  constexpr int KB_STEP = TB ? 16 : 2;
#pragma unroll 1
  for (int kb = 0; kb < n; kb++) {
    if (LEAD && kb == n - LEAD && wg == 1) { if (TB) pipe_drain(p, bars, leader); named_bar(8, 256); }
    mbar_wait(bars + B_FULL + p.r.s * 8, p.r.ph);
    if (kb == 0 && !accumulate && threadIdx.x == 0) { PROF(21 + TB); PROFC(49 - 2 * TB); }
    const uint32_t dA = dA0 + p.r.s * (pitch >> 4), dB = dB0 + p.r.s * (pitch >> 4);
    wg_fence();
    wgmma_ss<TB>(acc, dA, dB, accumulate | kb);
#pragma unroll
    for (int k = 1; k < 4; k++) wgmma_ss<TB>(acc, dA + k * 128, dB + k * KB_STEP, 1);
    wg_commit();
    wg_wait<1>();
    if (p.pending && leader) mbar_arrive(bars + B_EMPTY + p.prev * 8);
    p.pending = true;
    p.prev = p.r.s;
    p.r.next();
  }
  if (LEAD && wg == 0) named_arrive(8, 256);
}

template <int BROW0, int I0, int I1>
__device__ __forceinline__ void gemm2_part(float (&c)[36], uint32_t sb, uint32_t pitch, int wg) {
  const uint32_t dA0 = desc_lo(sb + wg * 8192, 8192), dB0 = desc_lo(sb + ASZ + BROW0 * 128, 16);
  wg_fence();
#pragma unroll
  for (int i = I0; i < I1; i++) {
    const int step = 68 - LAG + (i >> 2);
    if ((i & 3) == 0 && BROW0 == 0) mbar_wait_u(sb + BAR_OFF + B_FULL + (step % ST) * 8, (step / ST) & 1);
    if (i == 4 * LAG - TURN && BROW0 && wg == 0) named_arrive(7, 256);
    wgmma_ss<0>(c, dA0 + (step % ST) * (pitch >> 4) + (i & 3) * 128, dB0 + (step % ST) * (pitch >> 4) + (i & 3) * 2, 1);
  }
  wg_commit();
}
__device__ __forceinline__ void split_acc(const float (&acc)[72], float (&a)[36], float (&b)[36]) {
#pragma unroll
  for (int i = 0; i < 36; i++) { asm volatile("mov.b32 %0, %1;" : "=f"(a[i]) : "f"(acc[i])); asm volatile("mov.b32 %0, %1;" : "=f"(b[i]) : "f"(acc[36 + i])); }
}
template <int NV, int R, class Slice>
__device__ __forceinline__ void gelu_store(const float (&acc)[R], uint32_t bias0, uint32_t bias1, uint32_t sa, Slice slice) {
  const float hbias0 = 0.5f * bf_lo(pin(bias0)), hbias1 = 0.5f * bf_lo(pin(bias1));
  float hx[2][4], t[2][4], half = 0.5f;
  uint32_t pk[4];
#pragma unroll
  for (int j = 0; j <= NV / 4; j++) {
    if (j < NV / 4) {
      if (j >= 2) half = fmaf(t[j & 1][1], 0.f, 0.5f);
#pragma unroll
      for (int u = 0; u < 4; u++) {
        hx[j & 1][u] = fmaf(acc[4 * j + u], half, (u & 2) ? hbias1 : hbias0);
        t[j & 1][u] = tanh_ordered(hx[j & 1][u] * fmaf(hx[j & 1][u] * hx[j & 1][u], 0.2854192651f, 1.5957691216f));
      }
    }
    if (j > 0) {
      const float *hh = hx[(j - 1) & 1], *tt = t[(j - 1) & 1];
      pk[2 * ((j - 1) & 1)] = pack_bf16(fmaf(hh[0], tt[0], hh[0]), fmaf(hh[1], tt[1], hh[1]));
      pk[2 * ((j - 1) & 1) + 1] = pack_bf16(fmaf(hh[2], tt[2], hh[2]), fmaf(hh[3], tt[3], hh[3]));
      if (!(j & 1)) { stsm4_t(sa + (j - 2) * 1024, pk[0], pk[1], pk[2], pk[3]); slice(j / 2 - 1); }
    }
  }
}
struct Role { int half, kind, g2_m, dt, g1_mt, g1_nt, cs; uint32_t pitch; };
__device__ __forceinline__ Role get_role(const RoleMap& roles) {
  uint32_t b, sm;
  asm volatile("mov.u32 %0, %%ctaid.x;" : "=r"(b));
  asm volatile("mov.u32 %0, %%smid;" : "=r"(sm));
  const uint32_t w = roles.role[(roles.by_sm ? sm : b) >> 1];
  const int half = b & 1, kind = w & 3, m = (w >> 4) & 15, dt = (w >> 2) & 3;
  return Role{half, kind, m * 128, dt, half * 18 + (int)((w >> 8) & 31), (int)(w >> 16), (m * 4 + dt) * 2 + half, kind ? (uint32_t)PITCH_B : (uint32_t)PITCH_S};
}
__device__ __forceinline__ int g2_block(int half, int j) { return half * 36 + (j < 12 ? 2 * j : j < 24 ? 2 * j - 23 : j); }
__device__ __forceinline__ int conv_chan(int cs, int i) { return (3 * (cs >> 5) + (i >> 1)) * 64 + ((2 * cs) & 63) + (i & 1); }
__device__ __forceinline__ uint32_t conv_buf(uint32_t sb, int b) { return sb + (b == 3 ? (36 % ST) * PITCH_S : ST * PITCH_S + b * CBUF); }

__global__ void __cluster_dims__(2, 1, 1) __launch_bounds__(384, 1)
fused_kernel(const __nv_bfloat16* __restrict__ q, Scratch* __restrict__ gs, const __nv_bfloat16* __restrict__ b1,
             const __nv_bfloat16* __restrict__ shiftk, const __nv_bfloat16* __restrict__ ssmk, const __nv_bfloat16* __restrict__ ssmD,
             const __grid_constant__ CUtensorMap tmW1, const __grid_constant__ CUtensorMap tmW2, const __grid_constant__ CUtensorMap tmZ,
             const __grid_constant__ CUtensorMap tmH, const __grid_constant__ CUtensorMap tmK, const __grid_constant__ CUtensorMap tmV,
             const __grid_constant__ CUtensorMap tmKV, const __grid_constant__ RoleMap roles, const __nv_bfloat16* __restrict__ b2,
             __nv_bfloat16* __restrict__ out) {
  const int cta = blockIdx.x;
  const int tid = threadIdx.x;
  if (tid == 288) PROFG(0);

  const uint32_t t_start = clock_now();
  if (tid == 256) { prefetch_map(&tmW1); prefetch_map(&tmH); }
  const int lc = (cta + LNROT) & 127;
  const uint32_t do_ln = cta < 128 && tid < 256;
  const int oct = lc + (tid & 128), ln_row = oct * 8 + ((tid >> 4) & 7), l16 = tid & 15;
  uint2 xr[9];
  if (do_ln && oct >= TN(QLATE)) spin_until(t_start, TN(QDELAY) + TN(QRAMP) * oct / 2);
#pragma unroll
  for (int i = 0; i < 9; i++) xr[i] = ldg64_if(q + (size_t)ln_row * D_ + i * 64 + l16 * 4, do_ln);
  if (tid == 0) PROF(32);
  const int warp = __shfl_sync(0xffffffffu, tid >> 5, 0);
  const uint32_t sb = __shfl_sync(0xffffffffu, (uint32_t)__cvta_generic_to_shared(smem_raw), 0);
  const uint32_t bars = sb + BAR_OFF;
  const int lane = tid & 31;
  const int wg = warp >> 2;
  constexpr int LN_OFF = ST * PITCH_B;

  if (warp < 8 || warp == 11) {
    asm volatile("barrier.cluster.arrive.relaxed.aligned;" ::: "memory");
    const int hq = (lane & 16) >> 3, hb = (lane & 16) + hq;
    float da[3][4] = {};
#pragma unroll
    for (int i = 0; i < 9; i++) mma16816(da[i % 3], xr[i].x, 0x3f803f80u, xr[i].y, 0x3f803f80u, xr[i].x, xr[i].y);
    const float r1 = ((da[0][2] + da[0][3]) + (da[1][2] + da[1][3])) + (da[2][2] + da[2][3]);
    const float r2 = (lane & 4) ? (da[0][1] + da[1][1]) + da[2][1] : (da[0][0] + da[1][0]) + da[2][0];
    const float s1 = __shfl_sync(0xffffffffu, r1, hq) + __shfl_sync(0xffffffffu, r1, hq + 1);
    const float s2 = (__shfl_sync(0xffffffffu, r2, hb) + __shfl_sync(0xffffffffu, r2, hb + 4)) + (__shfl_sync(0xffffffffu, r2, hb + 9) + __shfl_sync(0xffffffffu, r2, hb + 13));
    if (tid == 0) { asm volatile("" ::"f"(s2) : "memory"); PROF(27); }
    const float mean = s1 * (1.f / D_), var = fmaxf(fmaf(-mean, mean, s2 * (1.f / D_)), 0.f);
    const float rinv = ln_rinv(var), rinv2 = ln_rinv(var * rinv * rinv), scale = rinv * rinv2, shift = -bf_round((mean - bf_round(mean)) * rinv) * rinv2;
    const uint32_t m2 = pack_bf16(mean, mean), hi2 = pack_bf16(scale, scale), lo2 = pack_bf16(scale - bf_lo(hi2), scale - bf_lo(hi2)), sh2 = pack_bf16(shift, shift);
    const uint32_t hi1 = pack_bf16(rinv, rinv);
    asm volatile("{\n.reg .pred p;\nsetp.eq.u32 p, %5, 0;\n@p st.shared.v4.u32 [%0], {%1, %2, %3, %4};\n}" ::"r"(sb + LN_OFF + 18432 + tid), "r"(m2), "r"(hi1),
                 "r"(pack_bf16(rinv - bf_lo(hi1), rinv - bf_lo(hi1))), "r"(0u), "r"(tid & 0x10f) : "memory");
    const uint32_t g0 = 4 * (l16 >> 3) + 2 * (l16 & 1), hrow = sb + LN_OFF + ((tid >> 7) & 1) * 9216 + (tid & 0x70);
    const uint32_t hs0 = hrow + g0 * 128 + ((l16 >> 1) & 3) * 4, hs8 = ((hrow + (l16 >> 1) * 1152) ^ ((l16 >> 1) << 4)) + 1024 + (l16 & 1) * 8;
    uint32_t w[18];
#pragma unroll
    for (int i = 0; i < 18; i++) {
      const uint32_t d = hsub2((i & 1) ? xr[i >> 1].y : xr[i >> 1].x, m2);
      asm("max.u32 %0, %1, 1;" : "=r"(w[i]) : "r"(hfma2(d, hi2, hfma2(d, lo2, sh2))));
    }
#pragma unroll
    for (int i = 0; i < 16; i++) {
      const int gi = 9 * (i >> 1) + (i & 1);
      asm volatile("{\n.reg .pred p;\nsetp.ne.u32 p, %2, 0;\n@p st.shared.u32 [%0], %1;\n}" ::"r"((hs0 ^ ((g0 * 16 + (gi & 7) * 16) & 0x70)) + gi * 128), "r"(w[i]), "r"(do_ln) : "memory");
    }
    asm volatile("{\n.reg .pred p;\nsetp.ne.u32 p, %3, 0;\n@p st.shared.v2.u32 [%0], {%1, %2};\n}" ::"r"(hs8), "r"(w[16]), "r"(w[17]), "r"(do_ln) : "memory");
    if (tid == 0) PROF(13);
    fence_async_smem();
    if (warp < 8) named_arrive(wg, 160);
  } else if (warp != 8) {
    spin_until(t_start, TN(W9));
  }

  if (wg == 2) {
    asm volatile("setmaxnreg.dec.sync.aligned.u32 56;");
    if (warp == 11) {
#pragma unroll 1
      for (int w = 0; w < 2; w++) {
        named_bar(w, 160);
        if (cta < 128 && elect_one()) {
          tma3d_store(&tmH, ((lc >> 3) + 16 * w) * 72, lc & 7, sb + LN_OFF + w * 9216);
          if (w == 0) PROF(29);
          bulk_s2g(gs->stats + (lc + 128 * w) * 8, sb + LN_OFF + 18432 + w * 128, 128);
          bulk_commit();
          bulk_wait_all();
          flag_add(gs->flags, FL_H + (lc >> 3) + 16 * w, 1);
          if (w == 0) PROF(1);
        }
        __syncwarp();
      }
    } else {
      if (elect_one()) {
        if (warp == 8) {
#pragma unroll
          for (int o = 0; o < B_GO; o += 8) mbar_init(bars + o, 1);
        } else if (warp == 9) {
#pragma unroll
          for (int o = B_GO; o < B_RAW + 40; o += 8) mbar_init(bars + o, 1);
        } else {
#pragma unroll
          for (int o = B_RAW + 40; o < B_END; o += 8) mbar_init(bars + o, o < B_EMPTY ? 1 : o < B_CEMPTY ? 2 : 4);
        }
        asm volatile("fence.mbarrier_init.release.cluster;" ::: "memory");
      }
      __syncwarp();
      asm volatile("barrier.cluster.arrive.relaxed.aligned;" ::: "memory");
      if (warp == 9) { prefetch_map(&tmK); prefetch_map(&tmV); prefetch_map(&tmKV); prefetch_map(&tmW2); prefetch_map(&tmZ); }
      if (tid == 256) PROF(35);
    }
    const Role ro = get_role(roles);
    if (warp != 8) asm volatile("barrier.cluster.wait.aligned;" ::: "memory");
    if (warp == 11) {
      if (lane == 0) mbar_arrive(bars + B_KVGO);
      Ring r{0, 1};
      uint32_t ready = 0;
      const uint32_t bsz = ro.pitch - ASZ;
      const uint8_t* src = gs->h + ro.g1_nt * bsz + ST * 73728;
      named_bar(10, 64);
#pragma unroll 1
      for (int i = ST; i < 32; i++) {
        poll_bits(gs->flags, ready, i == 31 ? 0xffffffffu : 1u << i, FL_H + lane, 8u, true);
        mbar_wait(bars + B_EMPTY + r.s * 8, r.ph ^ 1);
        if (elect_one()) bulk_g2s(sb + r.s * ro.pitch + ASZ, src, bsz, bars + B_FULL + r.s * 8);
        if (i == ST && lane == 0) PROF(25);
        if (i == TN(KVGO) && lane == 0) mbar_arrive(bars + B_KVGO);
        if (i == TN(CVGO) && lane == 0) mbar_arrive(bars + B_CVGO);
        src += 73728;
        r.next();
      }
      if (ro.kind != 2) {
        uint32_t look = 0;
#pragma unroll 1
        for (int j = 0; j < 36; j++) {
          const uint8_t* su = gs->u + ((size_t)g2_block(ro.half, j) * D_ + ro.dt * 144) * 128;
          if (j == 0 || j == 12 || j == 24) wait_counter(gs->flags, FL_U + ro.half * 3 + j / 12, j == 24 ? 36u : 48u, look, 100);
          if (ro.kind ? j == 4 : j < 2) mbar_wait_u(bars + B_UDONE + (j ? 8 : 0), 0);
          mbar_wait(bars + B_EMPTY + r.s * 8, r.ph ^ 1);
          if (elect_one()) {
            bulk_g2s(sb + r.s * ro.pitch + ASZ, su + (ro.half ^ 1) * 9216, 9216, bars + B_FULL + r.s * 8);
            bulk_g2s(sb + r.s * ro.pitch + ASZ + 9216, su + ro.half * 9216, 9216, bars + B_FULL + r.s * 8);
          }
          if (j == 9 || j == 21) look = flag_ld(gs->flags, FL_U + ro.half * 3 + j / 12 + 1);
          if (j == 0 && lane == 0) PROF(8);
          r.next();
        }
#pragma unroll 1
        for (int o = lane; o < ST * 73728 / 16 / NG2; o += 32) ((uint4*)gs->h)[ro.cs * (ST * 73728 / 16 / NG2) + o] = make_uint4(0u, 0u, 0u, 0u);
      }
      polling_done(gs->flags, lane);
    } else if (warp == 8) {
      const uint64_t pol = stream_policy();
      Ring r{0, 0};
#pragma unroll 1
      for (int i = 0; i < 32; i++) {
        if (i < ST) spin_until(t_start, TN(A0) + i * TN(AD) + (ro.kind ? TN(BA) : 0) + (i >= TN(AN) ? TN(AL) : 0));
        if (i == ST) {
          asm volatile("barrier.cluster.wait.aligned;" ::: "memory");
          if (roles.by_sm) {
            uint32_t sm;
            asm volatile("mov.u32 %0, %%smid;" : "=r"(sm));
            if (elect_one()) { mbar_expect(bars + B_PEER, 8); st_async2(mapa(bars + B_END, ro.half ^ 1), sm, sm, mapa(bars + B_PEER, ro.half ^ 1)); }
            mbar_wait_u(bars + B_PEER, 0);
            if ((lds32(bars + B_END) ^ sm) != 1 || sm >= NCTA) asm volatile("trap;");
          }
        }
        if (i >= ST) mbar_wait(bars + B_EMPTY + r.s * 8, r.ph ^ 1);
        if (elect_one()) {
          mbar_expect(bars + B_FULL + r.s * 8, ro.pitch);
          tma_weights(sb + r.s * ro.pitch, &tmW1, i * 64, ro.g1_mt * 2, bars + B_FULL + r.s * 8, pol);
        }
        r.next();
      }
      if (ro.kind != 2) {
#pragma unroll 1
        for (int j = 0; j < 36; j++) {
          if (j == 4) {
#pragma unroll 1
            for (int k = 0; k < TN(NPF); k++) {
              spin_until(clock_now(), TN(PFGAP));
              const int jj = 4 + 4 * k + ro.dt;
              if (elect_one() && jj < 36) tma_weights_prefetch(&tmW2, g2_block(ro.half, jj) * 64, ro.g2_m >> 6, pol);
            }
            if (ro.kind == 0) mbar_wait_u(bars + B_CEMPTY + 24, 0);
          }
          mbar_wait(bars + B_EMPTY + r.s * 8, r.ph ^ 1);
          if (elect_one()) {
            mbar_expect(bars + B_FULL + r.s * 8, PITCH_S);
            tma_weights(sb + r.s * ro.pitch, &tmW2, g2_block(ro.half, j) * 64, ro.g2_m >> 6, bars + B_FULL + r.s * 8, pol);
          }
          r.next();
        }
        if (lane < 2) mbar_expect(bars + B_RFULL + lane * 8, 9216);
        __syncwarp();
        mbar_wait(bars + B_EMPTY + r.s * 8, r.ph ^ 1);
        if (lane == 0) mbar_arrive_cluster(mapa(bars + B_GO, ro.half ^ 1));
      }
      if (lane == 0) PROF(28);
    } else {
      const uint64_t pol = stream_policy();
      {
        const uint32_t hb = (ro.pitch - ASZ) >> 1, raw = bars + B_RAW + (warp - 9) * 40, dst = sb + ASZ + (warp - 9) * hb;
        const uint8_t* src = gs->h + (2 * ro.g1_nt + warp - 9) * hb;
        auto fetch_h = [&](int i) { if (elect_one()) { mbar_expect(raw + i * 8, hb); bulk_g2s(dst + i * ro.pitch, src + i * 73728, hb, raw + i * 8); } };
        int next = 0;
#pragma unroll 1
        for (int i = -1; i < ST; i++) {
          if (i >= 0) {
#pragma unroll 1
            for (uint32_t tries = 0;; tries++) {
              mbar_wait_u(raw + i * 8, tries & 1);
              if (tid == 288 && i < 2) PROF(38 + i);
              const uint32_t pa = dst + i * ro.pitch + lane * 32 + (lane >> 2) * 4;
              uint32_t m = 1;
#pragma unroll
              for (int j = 0; j < 12; j++) m = min(m, lds32(pa + (j < 9 || ro.kind ? j : 0) * 1024));
              if (__all_sync(0xffffffffu, m)) break;
              if (lane == 0) PROF(26);
              fetch_h(i);
            }
            if (elect_one()) asm volatile("mbarrier.complete_tx.relaxed.cta.shared::cta.b64 [%0], %1;" ::"r"(bars + B_FULL + i * 8), "r"(hb) : "memory");
          }
#pragma unroll 1
          for (const int end = min(next + 2, ST); next < end; next++) {
            if (i < 0) spin_until(t_start, TN(H0) + next * TN(HD) + (ro.kind ? TN(BH) : 0));
            fetch_h(next);
            if (next == 0 && tid == 288) PROF(3);
          }
          if (i < 0 && warp == 10) named_arrive(10, 64);
        }
      }
      if (ro.kind == 0) {
        mbar_wait_u(bars + B_KVGO, 0);
        const int cs = ro.cs, grp = (cs / 3) * 2 + warp - 9, cb0 = (cs % 3) * 3;
        const uint32_t kin_s = sb + ST * PITCH_S + (warp - 9) * KVW, kout = kin_s + 2 * KVIN + lane * 176, fb = bars + B_KFULL + (warp - 9) * 16;
        auto fetch = [&](int i) {
          if (elect_one()) {
            mbar_expect(fb + (i & 1) * 8, KVIN);
            tma2d_stream(kin_s + (i & 1) * KVIN, &tmK, (cb0 + i) * 64, grp * 32 - 4, fb + (i & 1) * 8, pol);
            tma2d_stream(kin_s + (i & 1) * KVIN + 4608, &tmV, (cb0 + i) * 64, grp * 32 - 1, fb + (i & 1) * 8, pol);
          }
        };
        if (warp == 10) spin_until(clock_now(), TN(KVSTAG));
        fetch(0);
        uint4 shk = ldg128(shiftk + (cb0 * 64 + lane * 2) * 4);
        const uint32_t dskip = ldg16(ssmD + conv_chan(cs, lane < NCONV ? lane : 0));
#pragma unroll 1
        for (int i = 0; i < 3; i++) {
          const uint32_t w0 = __byte_perm(shk.x, shk.z, 0x5410), w1 = __byte_perm(shk.x, shk.z, 0x7632);
          const uint32_t w2 = __byte_perm(shk.y, shk.w, 0x5410), w3 = __byte_perm(shk.y, shk.w, 0x7632);
          const uint32_t ka = kin_s + (i & 1) * KVIN + lane * 4;
          mbar_wait_u(fb + (i & 1) * 8, i >> 1);
          if (tid == 288 && i < 2) PROF(30 + i);
          if (i < 2) fetch(i + 1);
          shk = ldg128(i < 2 ? shiftk + ((cb0 + i + 1) * 64 + lane * 2) * 4 : ssmk + (size_t)conv_chan(cs, lane < NCONV ? lane : 0) * S_);
          uint32_t kr[20], x[17];
          auto rows = [&](uint32_t from, int j0) {
#pragma unroll
            for (int j = j0; j < j0 + 4; j++) { kr[j] = lds32(from + j * 128); if (j >= 3) x[j - 3] = lds32(from + 4608 + (j - 3) * 128); }
          };
          rows(ka, 0); rows(ka, 4); rows(ka, 8);
          x[0] = hmul2(hfma2(kr[3], w0, hfma2(kr[2], w1, hfma2(kr[1], w2, hmul2(kr[0], w3)))), x[0]);
          if (i) { if (elect_one()) bulk_wait_read(); __syncwarp(); }
#pragma unroll 1
          for (int o = 0; o < 4; o++) {
            const uint32_t from = ka + (o < 3 ? o : 2) * 1024, to = kout + o * 32;
#pragma unroll
            for (int m = 0; m < 8; m += 4) {
#pragma unroll
              for (int j = m + 1; j < m + 5; j++) x[j] = hmul2(hfma2(kr[j + 3], w0, hfma2(kr[j + 2], w1, hfma2(kr[j + 1], w2, hmul2(kr[j], w3)))), x[j]);
#pragma unroll
              for (int c = 0; c < 2; c++) {
                const uint32_t sel = c ? 0x7632 : 0x5410;
                const uint32_t a0 = __byte_perm(x[m + 1], x[m], sel), a1 = __byte_perm(x[m + 2], x[m + 1], sel);
                const uint32_t a2 = __byte_perm(x[m + 3], x[m + 2], sel), a3 = __byte_perm(x[m + 4], x[m + 3], sel);
                sts128(to + c * 5632 + m * 4, a0, a1, a2, a3);
                asm volatile("{\n.reg .pred p;\nsetp.eq.u32 p, %5, 3;\n@p st.shared.v4.u32 [%0], {%1, %2, %3, %4};\n}" ::"r"(to + c * 5632 + m * 4 + 32), "r"(a0), "r"(a1), "r"(a2), "r"(a3), "r"(o) : "memory");
              }
#pragma unroll
              for (int j = m + 12; j < m + 16; j++) { kr[j] = lds32_if(from + j * 128, o < 3); x[j - 3] = lds32_if(from + 4608 + (j - 3) * 128, o < 3); }
            }
#pragma unroll
            for (int j = 1; j < 12; j++) kr[j] = kr[j + 8];
#pragma unroll
            for (int j = 0; j < 9; j++) x[j] = x[j + 8];
          }
          fence_async_smem();
          __syncwarp();
          if (i && elect_one()) { bulk_wait_all(); flag_add(gs->flags, FL_KV + i - 1, 1); }
#pragma unroll 1
          for (int k = 0; k < 64 / KVROWS; k++) {
            if (k) spin_until(clock_now(), TN(KVGAP));
            if (elect_one()) { tma4d_store(&tmKV, (cb0 + i) * 32 + ((k * KVROWS) & 31), (k * KVROWS) >> 5, grp, kin_s + 2 * KVIN + k * KVROWS * 176); bulk_commit(); }
          }
        }
        shk.x = __byte_perm(pack_bf16(bf_lo(shk.x) + bf_lo(dskip), 0.f), shk.x, 0x7610);
        const uint32_t look = flag_ld(gs->flags, FL_KV + warp - 9);
        if (elect_one()) {
          bulk_wait_all();
          flag_add(gs->flags, FL_KV + 2, 1);
          bulk_prefetch(ssmk + (size_t)conv_chan(cs, 2 * (warp - 9)) * S_, 2 * S_ * 2, pol);
          if (warp == 9) PROFG(2);
        }
        __syncwarp();
#pragma unroll 1
        for (int i = warp == 9 ? 0 : 2; i < (warp == 9 ? 2 : NCONV); i++) {
          const int b = i & 3, d = conv_chan(cs, i);
          const uint32_t base = conv_buf(sb, b), cf = bars + B_CFULL + b * 8;
          if (!(i & 1)) wait_counter(gs->flags, FL_KV + (i >> 1), 192u, i < 4 ? look : 0u, 200);
          if (i == 0 || i == 2) mbar_wait_u(bars + B_CVGO, 0);
          if (i == 0 && lane == 0) PROF(23);
          if (i == 3) {
            mbar_wait_u(bars + B_G1DONE, 0);
            if (elect_one()) bulk_prefetch(ssmk + (size_t)conv_chan(cs, 4) * S_, 2 * S_ * 2, pol);
          }
          if (i >= 4) mbar_wait_u(bars + B_CEMPTY + b * 8, 0);
          if (lane == i) sts128(base + CH_OFF, shk.x, shk.y, shk.z, shk.w);
          if (lane >= 27) sts128(base + (lane >= 29 ? CH_OFF + (lane - 32) * 16 : CT_OFF + (lane - 27) * 16), 0u, 0u, 0u, 0u);
          fence_async_smem();
          __syncwarp();
          if (elect_one()) {
            mbar_expect(cf, 4080 + KVT - 32);
            bulk_g2s(base + CT_OFF + 32, gs->kv + (size_t)d * KVT, KVT - 32, cf);
            bulk_g2s_stream(base + CH_OFF + 16, ssmk + (size_t)d * S_ + 8, 4080, cf, pol);
          }
        }
      }
      if (warp == 9) {
        if (elect_one()) {
          const uint32_t bsz = ro.pitch - ASZ;
#pragma unroll 1
          for (int w = 0; w < 2; w++) {
            const uint32_t src = sb + (ro.kind ? (w ? (36 % ST) * PITCH_B + ASZ : ST * PITCH_B) : ((32 % ST) + w) * PITCH_S + ASZ);
            mbar_wait_u(bars + B_USTG + w * 8, 0);
            bulk_s2g(gs->u + (size_t)(2 * ro.g1_mt + w) * D_ * 128 + ro.g1_nt * bsz, src, bsz);
            bulk_commit();
            if (ro.kind && w == 0) gate_arrive(gs->flags, TN(GDELAY) - 512);
            bulk_wait_read();
            mbar_arrive(bars + B_UDONE + w * 8);
            bulk_wait_all();
            flag_add(gs->flags, FL_U + ro.half * 3 + (ro.kind ? 2 : w), 1);
            PROFG(5 + 12 * w);
          }
          if (ro.kind == 0) {
#pragma unroll 1
            for (int i = 0; i < NCONV; i++) {
              mbar_wait_u(bars + B_SFULL + (i & 1) * 8, (i >> 1) & 1);
              bulk_s2g(gs->z + (size_t)chan_pos(conv_chan(ro.cs, i)) * S_, sb + CSTG_OFF + (i & 1) * 4096, 4096);
              bulk_commit();
              if (i == NCONV - 3) gate_arrive(gs->flags, 0);
              bulk_wait_read();
              mbar_arrive(bars + B_SEMPTY + (i & 1) * 8);
            }
            bulk_wait_all();
            flag_add(gs->flags, FL_Z, 1);
            PROFG(6);
          }
        }
      } else if (ro.kind != 2) {
        mbar_wait_u(bars + B_UDONE, 0);
        uint2 gate;
#pragma unroll 1
        for (uint32_t spins = 0;; spins++) {
          asm volatile("ld.relaxed.gpu.global.v2.u32 {%0, %1}, [%2];" : "=r"(gate.x), "=r"(gate.y) : "l"(gs->flags + FL_GATE * 32) : "memory");
          if (gate.x == NCTA) break;
          __nanosleep(100);
          if (spins > SPIN_LIMIT) asm volatile("trap;");
        }
        if (lane == 0) PROF(46);
#pragma unroll 1
        for (int w = 0; w < 2; w++) {
          while (time_now() - gate.y < TN(GDELAY) + w * TN(GDELAY1)) {}
          if (lane == 0) mbar_arrive(bars + B_G2GO + w * 8);
          if (lane == 0 && w == 0) PROF(24);
        }
        wait_counter(gs->flags, FL_Z, 96u, 0, 300);
        spin_until(clock_now(), TN(ZDELAY) + TN(ZRAMP) * cta);
        if (elect_one()) {
          mbar_expect(bars + B_ZFULL, 18432);
          tma2d(sb + ST * ro.pitch, &tmZ, ro.g2_m, ro.dt * 144 + ro.half * 72, bars + B_ZFULL);
          tma2d(sb + ST * ro.pitch + 9216, &tmZ, ro.g2_m + 64, ro.dt * 144 + ro.half * 72, bars + B_ZFULL);
          PROFG(7);
        }
        polling_done(gs->flags, lane);
      }
    }
  } else {
    asm volatile("setmaxnreg.inc.sync.aligned.u32 224;");
    const int wi = warp & 3, g = lane >> 2, qd = lane & 3, wt = tid & 127;
    const bool leader = wt == 0;
    Pipe p{{0, 0}, 0, false, 0};
    asm volatile("barrier.cluster.wait.aligned;" ::: "memory");
    int kind;
    {
      const Role ro = get_role(roles);
      kind = ro.kind;
      const int f0 = ro.g1_mt * 128 + wg * 64 + wi * 16 + g;
      uint32_t bias0 = ldg16(b1 + f0), bias1 = ldg16(b1 + f0 + 8);
      spin_until(t_start, TN(G1GO));
      const uint32_t so = ((lane >> 4) * 8 + (lane & 7)) * 128 + (((2 * wi + ((lane >> 3) & 1)) ^ (lane & 7)) << 4);
      if (kind) {
        float acc[96];
        gemm_run<1, LEAD_B>(acc, 32, 0, p, sb, PITCH_B, wg, leader);
        pipe_drain(p, bars, leader);
        if (wg) mbar_wait_u(bars + B_EMPTY + (36 % ST) * 8, ((36 / ST) & 1) ^ 1);
        if (leader) PROF(4 + 10 * wg);
        uint32_t sa = sb + (wg ? (36 % ST) * PITCH_B + ASZ : ST * PITCH_B) + so;
#pragma unroll 1
        for (int c = 0; c < 4; c++, sa += 6144) {
          gelu_store<24>(acc, bias0, bias1, sa, [](int) {});
#pragma unroll
          for (int i = 0; i < 72; i++) acc[i] = acc[i + 24];
        }
        fence_async_smem();
        __syncwarp();
        if (lane == 0) mbar_arrive(bars + B_USTG + wg * 8);
        if (leader) PROF(15 + wg);
      } else {
        const int cB = (g >> 1) & 1, cA = g >> 2, b = 2 * wi + (g & 1);
        const uint32_t toff = pin(CT_OFF + (40 * (2 * cA + cB) + 8 + b - 2 * qd) * 4);
        uint32_t a[16][4];
        auto load_a = [&](uint32_t base, int t, uint32_t on) {
          const uint32_t pt = base + toff + (t >> 1) * 1280 + (t & 1) * 64;
          a[t][0] = lds32_if(pt + 32, on); a[t][1] = lds32_if(pt + 672, on); a[t][2] = lds32_if(pt, on); a[t][3] = lds32_if(pt + 640, on);
        };
        {
          float acc[72];
          gemm_run<1, LEAD_S>(acc, 32, 0, p, sb, PITCH_S, wg, leader);
          if (wg == 1) named_arrive(6, 256);
          mbar_wait_u(bars + B_EMPTY + ((32 % ST) + wg) * 8, ((32 / ST) & 1) ^ 1);
          mbar_wait_u(bars + B_CFULL + wg * 8, 0);
          pipe_drain(p, bars, leader);
          if (leader) mbar_arrive(bars + B_G1DONE);
          if (leader) PROF(4 + 10 * wg);
          if (tid == 128) PROFC(48);
          gelu_store<72>(acc, bias0, bias1, sb + ((32 % ST) + wg) * PITCH_S + ASZ + so, [&](int t) { if (t < 8) load_a(conv_buf(sb, wg), t, 1); });
          fence_async_smem();
          __syncwarp();
          if (lane == 0) mbar_arrive(bars + B_USTG + wg * 8);
          if (leader) PROF(15 + wg);
        }
        const int phi = 2 * cA + (qd >> 1) + cB, pp = cB ? (phi & 3) : ((phi + 3) & 3);
        const int srcB = pin(((pp >> 1) << 4) | ((cB ^ 1) << 3) | ((g & 1) << 2) | ((pp & 1) << 1) | (qd & 1));
        const bool pB1 = cB && phi < 4, pB2 = cB && phi == 4;
        const int word = (8 * cB + 2 * (phi & 3) + (qd & 1)) * 8 + b;
        const uint32_t sto = pin(sb + CSTG_OFF + wg * 4096 + (word ^ (((word >> 5) & 3) << 1)) * 4);
#pragma unroll 1
        for (int i = wg; i < NCONV; i += 2) {
          const uint32_t base = conv_buf(sb, i & 3), next = conv_buf(sb, (i + 2) & 3);
          const uint64_t dH = mkdesc(base + CH_OFF, 16, 128, 0);
          float y[8][16];
          named_bar(6 + wg, 256);
          wg_fence();
#pragma unroll
          for (int t = 0; t < 16; t++) {
            if (t >= 8 && t % CFENCE == 0) wg_fence();
            if (t == CTURN) named_arrive(7 - wg, 256);
#pragma unroll
            for (int cb = t >> 1; cb < 8; cb++) {
              wgmma_rs_n32(y[cb], a[t][0], a[t][1], a[t][2], a[t][3], dH + (32 * cb - 32 * (t >> 1) - 2 * (t & 1) - 1), t);
              const int n = 8 * t - (t >> 1) * ((t - 1) >> 1) - (t >> 1) + cb + 1;
              if (n % CPER == 0 && n / CPER <= 8) load_a(base, 7 + n / CPER, 1);
            }
            if (t == 7 && CEARLY) wg_commit();
          }
          wg_commit();
          const bool more = i + 2 < NCONV;
          if (more) mbar_wait_u(bars + B_CFULL + ((i + 2) & 3) * 8, (i + 2) >> 2);
          mbar_wait_u(bars + B_SEMPTY + wg * 8, ((i >> 1) & 1) ^ 1);
          if (CEARLY) wg_wait<1>();
#pragma unroll
          for (int t = 0; t < CEARLY; t++) load_a(next, t, more);
          wg_wait<0>();
          if (lane == 0) mbar_arrive(bars + B_CEMPTY + (i & 3) * 8);
          if (leader) PROF(40 + i);
          uint32_t P[16], Q[16], R[16], o[8];
#pragma unroll
          for (int j = 0; j < 32; j++) {
            if ((j & 3) == 0 && (j >> 2) >= CEARLY) load_a(next, j >> 2, more);
            float v0 = y[j >> 2][4 * (j & 3)], v1 = y[j >> 2][4 * (j & 3) + 1];
            if (j >= 2) { v0 += y[(j - 2) >> 2][4 * ((j - 2) & 3) + 2]; v1 += y[(j - 2) >> 2][4 * ((j - 2) & 3) + 3]; }
            if (j & 1) R[j >> 1] = shfl_ordered(pack_bf16(v0, v1), lane ^ 16);
            else P[j >> 1] = pack_bf16(v0, v1);
          }
#pragma unroll
          for (int m = 0; m < 16; m++) Q[m] = hadd2(P[m], cA ? R[m] : (m ? R[m - 1] : 0u));
#pragma unroll
          for (int m = 0; m < 8; m++) o[m] = shfl_ordered(pB1 ? Q[2 * m] : (pB2 ? (m ? Q[2 * m - 1] : 0u) : Q[2 * m + 1]), srcB);
#pragma unroll
          for (int m = 0; m < 8; m++) sts32(sto + m * 512, hadd2(pB1 ? Q[2 * m + 1] : Q[2 * m], o[m]));
          fence_async_smem();
          __syncwarp();
          if (lane == 0) mbar_arrive(bars + B_SFULL + wg * 8);
          if (leader && i == 5) PROF(53);
        }
        if (wg == 0) named_bar(6, 256);
      }
    }
    if (kind != 2) {
      const Role ro = get_role(roles);
      const uint32_t pitch = ro.pitch;
      const int s0 = ro.g2_m + wg * 64 + wi * 16 + g;
      const size_t go = (size_t)s0 * D_ + ro.dt * 128 + ro.half * 64 + qd * 8, go8 = (size_t)s0 * D_ + 512 + ro.dt * 16 + ro.half * 8 + qd * 2;
      uint32_t x[2][9], sg[2][9];
      float acc[72];
      mbar_wait_u(bars + B_G2GO + wg * 8, 0);
      gemm_run<0, 0>(acc, XAT + 2 * wg, 0, p, sb, pitch, wg, leader);
#pragma unroll
      for (int J = 0; J < 4; J++) {
        const uint4 v = ldg128(q + go + (J & 1) * 8 * D_ + (J >> 1) * 32);
        x[J & 1][4 * (J >> 1)] = v.x; x[J & 1][4 * (J >> 1) + 1] = v.y; x[J & 1][4 * (J >> 1) + 2] = v.z; x[J & 1][4 * (J >> 1) + 3] = v.w;
      }
      x[0][8] = ldg32(q + go8); x[1][8] = ldg32(q + go8 + 8 * D_);
      const uint4 st0 = ld_l2(gs->stats + s0), st1 = ld_l2(gs->stats + s0 + 8);
      const uint32_t braw0 = ldg16(b2 + s0), braw1 = ldg16(b2 + s0 + 8);
      gemm_run<0, 0>(acc, 20 - XAT, 1, p, sb, pitch, wg, leader);
      {
        const int zw = 8 * wi + (g ^ ((((ro.g2_m >> 6) + wg) & 3) << 1));
        const uint32_t za = sb + ST * pitch + wg * 9216 + qd * 256 + (zw & 3) * 4;
        mbar_wait_u(bars + B_ZFULL, 0);
#pragma unroll
        for (int j = 0; j < 9; j++) {
          sg[0][j] = lds32(za + j * 1024 + (((zw >> 2) ^ (2 * qd)) << 4));
          sg[1][j] = lds32(za + j * 1024 + 128 + (((zw >> 2) ^ (2 * qd + 1)) << 4));
        }
      }
      gemm_run<0, 0>(acc, 1, 1, p, sb, pitch, wg, leader);
#pragma unroll
      for (int j = 0; j < 9; j++) {
        const uint32_t z0 = __byte_perm(sg[0][j], sg[1][j], 0x5410), z1 = __byte_perm(sg[0][j], sg[1][j], 0x7632);
        sg[0][j] = hmul2(ln_apply(x[0][j], st0), z0);
        sg[1][j] = hmul2(ln_apply(x[1][j], st1), z1);
        asm volatile("" : "+r"(sg[0][j]), "+r"(sg[1][j]));
      }
      gemm_run<0, SKEW>(acc, 15 - LAG - 2 * wg, 1, p, sb, pitch, wg, leader);
      const uint32_t rbuf = sb + (68 % ST) * pitch + warp * 2304;
      const uint32_t rdst = mapa(rbuf, ro.half ^ 1), rbar = mapa(bars + B_RFULL + wg * 8, ro.half ^ 1);
      pipe_drain(p, bars, leader);
      if (leader) PROF(9 + 10 * wg);
      if (tid == 128) PROFC(50);
      float cs[36], ck[36];
      split_acc(acc, cs, ck);
      gemm2_part<0, 0, 4 * LAG>(cs, sb, pitch, wg);
      if (KPRE) gemm2_part<72, 0, KPRE>(ck, sb, pitch, wg);
      const float hb0 = fmaf(bf_lo(braw0), 0.5f, __uint_as_float(st0.w)), hb1 = fmaf(bf_lo(braw1), 0.5f, __uint_as_float(st1.w));
      mbar_wait(bars + B_GO, 0);
      wg_wait<KPRE ? 1 : 0>();
      if (leader) PROF(54 + wg);
#pragma unroll
      for (int i = 0; i < 5; i++) {
        const float* c = &cs[8 * i];
        const uint32_t v0 = pack_bf16(fmaf(c[0], 0.5f, hb0), fmaf(c[1], 0.5f, hb0)), v1 = pack_bf16(fmaf(c[2], 0.5f, hb1), fmaf(c[3], 0.5f, hb1));
        if (i < 4) st_async4(rdst + i * 512 + lane * 16, v0, v1, pack_bf16(fmaf(c[4], 0.5f, hb0), fmaf(c[5], 0.5f, hb0)), pack_bf16(fmaf(c[6], 0.5f, hb1), fmaf(c[7], 0.5f, hb1)), rbar);
        else st_async2(rdst + 2048 + lane * 8, v0, v1, rbar);
      }
      if (wg == 1) named_bar(7, 256);
      gemm2_part<72, KPRE, 4 * LAG>(ck, sb, pitch, wg);
      uint32_t rp[18];
      mbar_wait(bars + B_RFULL + wg * 8, 0);
#pragma unroll
      for (int m = 0; m < 4; m++) {
        const uint4 v = lds128(rbuf + m * 512 + lane * 16);
        rp[4 * m] = v.x; rp[4 * m + 1] = v.y; rp[4 * m + 2] = v.z; rp[4 * m + 3] = v.w;
      }
      { const uint2 v = lds64(rbuf + 2048 + lane * 8); rp[16] = v.x; rp[17] = v.y; }
      __nv_bfloat16* o = out + go;
      wg_wait<0>();
      if (leader) PROF(10 + 10 * wg);
      float h[2][4], t[2][4], half = 0.5f;
#pragma unroll
      for (int j = 0; j <= 9; j++) {
        if (j < 9) {
          const uint32_t ra = rp[2 * j], rb = rp[2 * j + 1];
          if (j >= 2) half = fmaf(t[j & 1][3], 0.f, 0.5f);
          h[j & 1][0] = fmaf(ck[4 * j], half, bf_lo(ra)); h[j & 1][1] = fmaf(ck[4 * j + 1], half, bf_hi(ra));
          h[j & 1][2] = fmaf(ck[4 * j + 2], half, bf_lo(rb)); h[j & 1][3] = fmaf(ck[4 * j + 3], half, bf_hi(rb));
#pragma unroll
          for (int u = 0; u < 4; u++) t[j & 1][u] = tanh_ordered(h[j & 1][u]);
        }
        if (j > 0) {
          const int k = j - 1;
          const float* hh = h[k & 1];
          const float* tt = t[k & 1];
          x[0][k] = hfma2(sg[0][k], pack_bf16(fmaf(hh[0], tt[0], hh[0]), fmaf(hh[1], tt[1], hh[1])), x[0][k]);
          x[1][k] = hfma2(sg[1][k], pack_bf16(fmaf(hh[2], tt[2], hh[2]), fmaf(hh[3], tt[3], hh[3])), x[1][k]);
          if ((k & 3) == 3) {
            *(uint4*)(o + (k >> 2) * 32) = make_uint4(x[0][k - 3], x[0][k - 2], x[0][k - 1], x[0][k]);
            *(uint4*)(o + 8 * D_ + (k >> 2) * 32) = make_uint4(x[1][k - 3], x[1][k - 2], x[1][k - 1], x[1][k]);
          }
        }
      }
      *(uint32_t*)(out + go8) = x[0][8];
      *(uint32_t*)(out + go8 + 8 * D_) = x[1][8];
      if (leader) PROF(11 + 7 * wg);
      if (tid == 128) PROFC(51);
    }
  }
}

typedef CUresult (*EncodeFn)(CUtensorMap*, CUtensorMapDataType, cuuint32_t, void*, const cuuint64_t*, const cuuint64_t*, const cuuint32_t*,
                             const cuuint32_t*, CUtensorMapInterleave, CUtensorMapSwizzle, CUtensorMapL2promotion, CUtensorMapFloatOOBfill);

uint32_t role_of_pair(int t) {
  int grp, i;
  if (t < 32) { const int j = t & 7; i = t >> 3; grp = j < 6 ? 1 + j : 12 + 2 * (j - 6); }
  else if (t < 60) { const int j = (t - 32) % 7; i = (t - 32) / 7; grp = j < 5 ? 7 + j : 13 + 2 * (j - 5); }
  else if (t < 62) return 2u | (uint32_t)(14 + 3 * (t - 60)) << 8 | 2u << 16;
  else { grp = 0; i = t - 62; }
  if (grp < 12) return (uint32_t)(i << 2 | grp << 4 | grp << 8 | i << 16);
  const int u = (grp & 1) * 4 + i;
  return (uint32_t)(1 | i << 2 | grp << 4 | (12 + 3 * ((grp - 12) >> 1) + u / 3) << 8 | (u % 3) << 16);
}

}

extern "C" void kernel_launch(void* const* d_in, const int* in_sizes, int n_in, void* d_out, int out_size) {
  (void)in_sizes; (void)n_in; (void)out_size;
  EncodeFn enc = nullptr;
  cudaDriverEntryPointQueryResult qr;
  cudaGetDriverEntryPoint("cuTensorMapEncodeTiled", (void**)&enc, cudaEnableDefault, &qr);
  Scratch* gs = nullptr;
  cudaGetSymbolAddress((void**)&gs, g_scratch);
  void *zp = gs->z, *hp = gs->h, *kvp = gs->kv;
  CUtensorMap tmW1, tmW2, tmZ, tmH, tmK, tmV, tmKV;
  for (int w = 0; w < 2; w++) {
    cuuint64_t gd[2] = {D_, S_};
    cuuint64_t st[1] = {D_ * 2};
    cuuint32_t bx[2] = {64, w ? 33u : 36u};
    cuuint32_t es[2] = {1, 1};
    enc(w ? &tmV : &tmK, CU_TENSOR_MAP_DATA_TYPE_BFLOAT16, 2, d_in[1 + w], gd, st, bx, es, CU_TENSOR_MAP_INTERLEAVE_NONE, CU_TENSOR_MAP_SWIZZLE_NONE,
        CU_TENSOR_MAP_L2_PROMOTION_L2_128B, CU_TENSOR_MAP_FLOAT_OOB_FILL_NONE);
  }
  {
    cuuint64_t gd[4] = {40, D_ / 2, 2, 64};
    cuuint64_t st[3] = {2 * KVT, KVT, 160};
    cuuint32_t bx[4] = {44, KVROWS, 1, 1};
    cuuint32_t es[4] = {1, 1, 1, 1};
    enc(&tmKV, CU_TENSOR_MAP_DATA_TYPE_UINT32, 4, kvp, gd, st, bx, es, CU_TENSOR_MAP_INTERLEAVE_NONE, CU_TENSOR_MAP_SWIZZLE_NONE,
        CU_TENSOR_MAP_L2_PROMOTION_NONE, CU_TENSOR_MAP_FLOAT_OOB_FILL_NONE);
  }
  {
    cuuint64_t gd[3] = {64, 32 * 72, 8};
    cuuint64_t st[2] = {1024, 128};
    cuuint32_t bx[3] = {64, 72, 1};
    cuuint32_t es[3] = {1, 1, 1};
    enc(&tmH, CU_TENSOR_MAP_DATA_TYPE_BFLOAT16, 3, hp, gd, st, bx, es, CU_TENSOR_MAP_INTERLEAVE_NONE, CU_TENSOR_MAP_SWIZZLE_128B,
        CU_TENSOR_MAP_L2_PROMOTION_NONE, CU_TENSOR_MAP_FLOAT_OOB_FILL_NONE);
  }
  for (int w = 0; w < 2; w++) {
    const cuuint64_t M = w ? S_ : F_, K = w ? F_ : S_;
    cuuint64_t gd[3] = {64, K, M / 64};
    cuuint64_t st[2] = {M * 2, 128};
    cuuint32_t bx[3] = {64, 64, 2};
    cuuint32_t es[3] = {1, 1, 1};
    enc(w ? &tmW2 : &tmW1, CU_TENSOR_MAP_DATA_TYPE_BFLOAT16, 3, d_in[w ? 9 : 7], gd, st, bx, es, CU_TENSOR_MAP_INTERLEAVE_NONE,
        CU_TENSOR_MAP_SWIZZLE_128B, CU_TENSOR_MAP_L2_PROMOTION_L2_256B, CU_TENSOR_MAP_FLOAT_OOB_FILL_NONE);
  }
  {
    cuuint64_t gd[2] = {S_, D_};
    cuuint64_t st[1] = {S_ * 2};
    cuuint32_t bx[2] = {64, 72};
    cuuint32_t es[2] = {1, 1};
    enc(&tmZ, CU_TENSOR_MAP_DATA_TYPE_BFLOAT16, 2, zp, gd, st, bx, es, CU_TENSOR_MAP_INTERLEAVE_NONE, CU_TENSOR_MAP_SWIZZLE_128B,
        CU_TENSOR_MAP_L2_PROMOTION_L2_256B, CU_TENSOR_MAP_FLOAT_OOB_FILL_NONE);
  }
  RoleMap roles;
  int dev = 0, sms = 0;
  cudaGetDevice(&dev);
  cudaDeviceGetAttribute(&sms, cudaDevAttrMultiProcessorCount, dev);
  roles.by_sm = sms == NCTA;
  for (int k = 0; k < NCTA / 2; k++) roles.role[k] = role_of_pair(k);
  cudaFuncSetAttribute(fused_kernel, cudaFuncAttributeMaxDynamicSharedMemorySize, SMEM_BYTES);
  fused_kernel<<<NCTA, 384, SMEM_BYTES>>>((const __nv_bfloat16*)d_in[0], gs, (const __nv_bfloat16*)d_in[8], (const __nv_bfloat16*)d_in[3],
                                          (const __nv_bfloat16*)d_in[4], (const __nv_bfloat16*)d_in[5], tmW1, tmW2, tmZ, tmH, tmK, tmV, tmKV,
                                          roles, (const __nv_bfloat16*)d_in[10], (__nv_bfloat16*)d_out);
}
```

```cpp
#include <cuda_runtime.h>
#include <cuda_bf16.h>
#include <cuda.h>
#include <stdint.h>

namespace {

constexpr int S_ = 2048, D_ = 576, F_ = 4608;
constexpr int NCTA = 132, NG2 = 128, NCONV = 6;
constexpr int ST = 5, ASZ = 16384, PITCH_S = ASZ + 144 * 128, PITCH_B = ASZ + 192 * 128;
constexpr int KVIN = (36 + 33) * 128, KVW = 2 * KVIN + 64 * 176;
constexpr int BAR_OFF = ST * PITCH_S + 2 * KVW;
constexpr int SMEM_BYTES = BAR_OFF + 512;
constexpr int KVROWS = 16, LNROT = 120;
constexpr int SKEW = 1;
constexpr int LEAD_S = 3, LEAD_B = 2;
constexpr int CTURN = 14, CPER = 4, CEARLY = 0, CFENCE = 8;
constexpr int TURN = 4, KPRE = 2;
constexpr int XAT = 12;
constexpr int LAG = 4;
constexpr int CBUF = 14464, CH_OFF = 128, CT_OFF = 4224, KVT = 10240;
constexpr int CSTG_OFF = ST * PITCH_S + 3 * CBUF;
constexpr uint32_t SPIN_LIMIT = 1u << 22;

constexpr int FL_H = 0, FL_U = 32, FL_KV = 38, FL_Z = 41, FL_GATE = 42, FL_DONE = 43, FL_N = 44;
struct Scratch {
  uint32_t flags[64 * 32];
  uint4 stats[S_];
  uint8_t h[32 * 72 * 1024];
  uint8_t u[72 * D_ * 128];
  uint8_t kv[D_ * KVT];
  __nv_bfloat16 z[D_ * S_];
};
__device__ __align__(1024) Scratch g_scratch;
extern __shared__ __align__(1024) uint8_t smem_raw[];
#define TUNABLES(X) X(W9, 1200) X(QLATE, 40) X(QDELAY, 400) X(QRAMP, 5) X(A0, 1200) X(AD, 300) X(AN, 2) X(AL, 1500) X(H0, 3100) X(HD, 400) X(KVGAP, 100) X(HS2, 8) X(KVGO, 6) X(CVGO, 31) X(GDELAY, 608) X(GDELAY1, 256) X(ZDELAY, 3000) X(ZRAMP, 40) X(NPF, 0) X(PFGAP, 600)
#define X(k, v) constexpr int T_##k = v;
TUNABLES(X)
#undef X
#define TN(k) T_##k
struct RoleMap { uint32_t role[NCTA / 2]; uint32_t by_sm; };
#define PROF(i) do {} while (0)
#define PROFG(i) do {} while (0)
#define PROFC(i) do {} while (0)

template<int TB> __device__ __forceinline__ void wgmma_ss(float (&d)[96], uint32_t da, uint32_t db, int sd) {
  asm volatile("{\n.reg .pred p;\n.reg .b64 a, b;\nsetp.ne.b32 p, %98, 0;\nmov.b64 a, {%96, %100};\nmov.b64 b, {%97, %101};\n"
    "wgmma.mma_async.sync.aligned.m64n192k16.f32.bf16.bf16 {%0, %1, %2, %3, %4, %5, %6, %7, %8, %9, %10, %11, %12, %13, %14, %15, %16, %17, %18, %19, %20, %21, %22, %23, %24, %25, %26, %27, %28, %29, %30, %31, %32, %33, %34, %35, %36, %37, %38, %39, %40, %41, %42, %43, %44, %45, %46, %47, %48, %49, %50, %51, %52, %53, %54, %55, %56, %57, %58, %59, %60, %61, %62, %63, %64, %65, %66, %67, %68, %69, %70, %71, %72, %73, %74, %75, %76, %77, %78, %79, %80, %81, %82, %83, %84, %85, %86, %87, %88, %89, %90, %91, %92, %93, %94, %95}, a, b, p, 1, 1, 1, %99;\n}\n"
    : "+f"(d[0]), "+f"(d[1]), "+f"(d[2]), "+f"(d[3]), "+f"(d[4]), "+f"(d[5]), "+f"(d[6]), "+f"(d[7]), "+f"(d[8]), "+f"(d[9]), "+f"(d[10]), "+f"(d[11]), "+f"(d[12]), "+f"(d[13]), "+f"(d[14]), "+f"(d[15]), "+f"(d[16]), "+f"(d[17]), "+f"(d[18]), "+f"(d[19]), "+f"(d[20]), "+f"(d[21]), "+f"(d[22]), "+f"(d[23]), "+f"(d[24]), "+f"(d[25]), "+f"(d[26]), "+f"(d[27]), "+f"(d[28]), "+f"(d[29]), "+f"(d[30]), "+f"(d[31]), "+f"(d[32]), "+f"(d[33]), "+f"(d[34]), "+f"(d[35]), "+f"(d[36]), "+f"(d[37]), "+f"(d[38]), "+f"(d[39]), "+f"(d[40]), "+f"(d[41]), "+f"(d[42]), "+f"(d[43]), "+f"(d[44]), "+f"(d[45]), "+f"(d[46]), "+f"(d[47]), "+f"(d[48]), "+f"(d[49]), "+f"(d[50]), "+f"(d[51]), "+f"(d[52]), "+f"(d[53]), "+f"(d[54]), "+f"(d[55]), "+f"(d[56]), "+f"(d[57]), "+f"(d[58]), "+f"(d[59]), "+f"(d[60]), "+f"(d[61]), "+f"(d[62]), "+f"(d[63]), "+f"(d[64]), "+f"(d[65]), "+f"(d[66]), "+f"(d[67]), "+f"(d[68]), "+f"(d[69]), "+f"(d[70]), "+f"(d[71]), "+f"(d[72]), "+f"(d[73]), "+f"(d[74]), "+f"(d[75]), "+f"(d[76]), "+f"(d[77]), "+f"(d[78]), "+f"(d[79]), "+f"(d[80]), "+f"(d[81]), "+f"(d[82]), "+f"(d[83]), "+f"(d[84]), "+f"(d[85]), "+f"(d[86]), "+f"(d[87]), "+f"(d[88]), "+f"(d[89]), "+f"(d[90]), "+f"(d[91]), "+f"(d[92]), "+f"(d[93]), "+f"(d[94]), "+f"(d[95])
    : "r"(da), "r"(db), "r"(sd), "n"(TB), "r"(0x40000040u), "r"(TB ? 0x40u : 0x40000040u));
}
template<int TB> __device__ __forceinline__ void wgmma_ss(float (&d)[72], uint32_t da, uint32_t db, int sd) {
  asm volatile("{\n.reg .pred p;\n.reg .b64 a, b;\nsetp.ne.b32 p, %74, 0;\nmov.b64 a, {%72, %76};\nmov.b64 b, {%73, %77};\n"
    "wgmma.mma_async.sync.aligned.m64n144k16.f32.bf16.bf16 {%0, %1, %2, %3, %4, %5, %6, %7, %8, %9, %10, %11, %12, %13, %14, %15, %16, %17, %18, %19, %20, %21, %22, %23, %24, %25, %26, %27, %28, %29, %30, %31, %32, %33, %34, %35, %36, %37, %38, %39, %40, %41, %42, %43, %44, %45, %46, %47, %48, %49, %50, %51, %52, %53, %54, %55, %56, %57, %58, %59, %60, %61, %62, %63, %64, %65, %66, %67, %68, %69, %70, %71}, a, b, p, 1, 1, 1, %75;\n}\n"
    : "+f"(d[0]), "+f"(d[1]), "+f"(d[2]), "+f"(d[3]), "+f"(d[4]), "+f"(d[5]), "+f"(d[6]), "+f"(d[7]), "+f"(d[8]), "+f"(d[9]), "+f"(d[10]), "+f"(d[11]), "+f"(d[12]), "+f"(d[13]), "+f"(d[14]), "+f"(d[15]), "+f"(d[16]), "+f"(d[17]), "+f"(d[18]), "+f"(d[19]), "+f"(d[20]), "+f"(d[21]), "+f"(d[22]), "+f"(d[23]), "+f"(d[24]), "+f"(d[25]), "+f"(d[26]), "+f"(d[27]), "+f"(d[28]), "+f"(d[29]), "+f"(d[30]), "+f"(d[31]), "+f"(d[32]), "+f"(d[33]), "+f"(d[34]), "+f"(d[35]), "+f"(d[36]), "+f"(d[37]), "+f"(d[38]), "+f"(d[39]), "+f"(d[40]), "+f"(d[41]), "+f"(d[42]), "+f"(d[43]), "+f"(d[44]), "+f"(d[45]), "+f"(d[46]), "+f"(d[47]), "+f"(d[48]), "+f"(d[49]), "+f"(d[50]), "+f"(d[51]), "+f"(d[52]), "+f"(d[53]), "+f"(d[54]), "+f"(d[55]), "+f"(d[56]), "+f"(d[57]), "+f"(d[58]), "+f"(d[59]), "+f"(d[60]), "+f"(d[61]), "+f"(d[62]), "+f"(d[63]), "+f"(d[64]), "+f"(d[65]), "+f"(d[66]), "+f"(d[67]), "+f"(d[68]), "+f"(d[69]), "+f"(d[70]), "+f"(d[71])
    : "r"(da), "r"(db), "r"(sd), "n"(TB), "r"(0x40000040u), "r"(TB ? 0x40u : 0x40000040u));
}
template<int TB> __device__ __forceinline__ void wgmma_ss(float (&d)[36], uint32_t da, uint32_t db, int sd) {
  asm volatile("{\n.reg .pred p;\n.reg .b64 a, b;\nsetp.ne.b32 p, %38, 0;\nmov.b64 a, {%36, %40};\nmov.b64 b, {%37, %41};\n"
    "wgmma.mma_async.sync.aligned.m64n72k16.f32.bf16.bf16 {%0, %1, %2, %3, %4, %5, %6, %7, %8, %9, %10, %11, %12, %13, %14, %15, %16, %17, %18, %19, %20, %21, %22, %23, %24, %25, %26, %27, %28, %29, %30, %31, %32, %33, %34, %35}, a, b, p, 1, 1, 1, %39;\n}\n"
    : "+f"(d[0]), "+f"(d[1]), "+f"(d[2]), "+f"(d[3]), "+f"(d[4]), "+f"(d[5]), "+f"(d[6]), "+f"(d[7]), "+f"(d[8]), "+f"(d[9]), "+f"(d[10]), "+f"(d[11]), "+f"(d[12]), "+f"(d[13]), "+f"(d[14]), "+f"(d[15]), "+f"(d[16]), "+f"(d[17]), "+f"(d[18]), "+f"(d[19]), "+f"(d[20]), "+f"(d[21]), "+f"(d[22]), "+f"(d[23]), "+f"(d[24]), "+f"(d[25]), "+f"(d[26]), "+f"(d[27]), "+f"(d[28]), "+f"(d[29]), "+f"(d[30]), "+f"(d[31]), "+f"(d[32]), "+f"(d[33]), "+f"(d[34]), "+f"(d[35])
    : "r"(da), "r"(db), "r"(sd), "n"(TB), "r"(0x40000040u), "r"(TB ? 0x40u : 0x40000040u));
}
__device__ __forceinline__ void wgmma_rs_n32(float (&d)[16], uint32_t a0, uint32_t a1, uint32_t a2, uint32_t a3, uint64_t db, int sd) {
  asm volatile("{\n.reg .pred p;\nsetp.ne.b32 p, %21, 0;\n"
    "wgmma.mma_async.sync.aligned.m64n32k16.f32.bf16.bf16 {%0, %1, %2, %3, %4, %5, %6, %7, %8, %9, %10, %11, %12, %13, %14, %15}, {%16, %17, %18, %19}, %20, p, 1, 1, 0;\n}\n"
    : "+f"(d[0]), "+f"(d[1]), "+f"(d[2]), "+f"(d[3]), "+f"(d[4]), "+f"(d[5]), "+f"(d[6]), "+f"(d[7]), "+f"(d[8]), "+f"(d[9]), "+f"(d[10]), "+f"(d[11]), "+f"(d[12]), "+f"(d[13]), "+f"(d[14]), "+f"(d[15])
    : "r"(a0), "r"(a1), "r"(a2), "r"(a3), "l"(db), "r"(sd));
}

__device__ __forceinline__ void wg_fence() { asm volatile("wgmma.fence.sync.aligned;" ::: "memory"); }
__device__ __forceinline__ void wg_commit() { asm volatile("wgmma.commit_group.sync.aligned;" ::: "memory"); }
template <int n> __device__ __forceinline__ void wg_wait() { asm volatile("wgmma.wait_group.sync.aligned %0;" ::"n"(n) : "memory"); }
__device__ __forceinline__ uint64_t mkdesc(uint32_t addr, uint32_t lbo, uint32_t sbo, uint32_t sw) {
  return (uint64_t)((addr & 0x3FFFF) >> 4) | ((uint64_t)(lbo >> 4) << 16) | ((uint64_t)(sbo >> 4) << 32) | ((uint64_t)sw << 62);
}
__device__ __forceinline__ void mbar_init(uint32_t a, int c) { asm volatile("mbarrier.init.shared::cta.b64 [%0], %1;" ::"r"(a), "r"(c)); }
__device__ __forceinline__ void mbar_expect(uint32_t a, uint32_t b) { asm volatile("mbarrier.arrive.expect_tx.shared::cta.b64 _, [%0], %1;" ::"r"(a), "r"(b) : "memory"); }
__device__ __forceinline__ void mbar_arrive(uint32_t a) { asm volatile("mbarrier.arrive.shared::cta.b64 _, [%0];" ::"r"(a) : "memory"); }
__device__ __forceinline__ void mbar_arrive_cluster(uint32_t raddr) { asm volatile("mbarrier.arrive.shared::cluster.b64 _, [%0];" ::"r"(raddr) : "memory"); }
__device__ __forceinline__ uint32_t mapa(uint32_t a, uint32_t cta) { uint32_t r; asm("mapa.shared::cluster.u32 %0, %1, %2;" : "=r"(r) : "r"(a), "r"(cta)); return r; }
__device__ __forceinline__ void mbar_wait(uint32_t a, uint32_t ph) {
  asm volatile(
      "{\n.reg .pred p;\n.reg .u32 c;\nmov.u32 c, 0;\n"
      "WAIT_LOOP:\nmbarrier.try_wait.parity.shared::cta.b64 p, [%0], %1;\n@p bra WAIT_DONE;\n"
      "add.u32 c, c, 1;\nsetp.lt.u32 p, c, %2;\n@p bra WAIT_LOOP;\ntrap;\nWAIT_DONE:\n}" ::"r"(a), "r"(ph), "n"(SPIN_LIMIT) : "memory");
}
__device__ __forceinline__ void mbar_wait_u(uint32_t a, uint32_t ph) {
  asm volatile("{\n.reg .pred p;\nWAIT_LOOP:\nmbarrier.try_wait.parity.shared::cta.b64 p, [%0], %1;\n@!p bra WAIT_LOOP;\n}" ::"r"(a), "r"(ph) : "memory");
}
__device__ __forceinline__ uint32_t desc_lo(uint32_t addr, uint32_t lbo) { return ((addr & 0x3FFFF) >> 4) | ((lbo >> 4) << 16); }
__device__ __forceinline__ void tma2d(uint32_t dst, const CUtensorMap* m, int c0, int c1, uint32_t bar) {
  asm volatile("cp.async.bulk.tensor.2d.shared::cluster.global.mbarrier::complete_tx::bytes [%0], [%1, {%3, %4}], [%2];" ::"r"(dst), "l"(m), "r"(bar), "r"(c0), "r"(c1) : "memory");
}
__device__ __forceinline__ void bulk_g2s(uint32_t dst, const void* src, uint32_t sz, uint32_t bar) {
  asm volatile("cp.async.bulk.shared::cluster.global.mbarrier::complete_tx::bytes [%0], [%1], %2, [%3];" ::"r"(dst), "l"(src), "r"(sz), "r"(bar) : "memory");
}
__device__ __forceinline__ void bulk_s2g(void* dst, uint32_t src, uint32_t sz) {
  asm volatile("cp.async.bulk.global.shared::cta.bulk_group [%0], [%1], %2;" ::"l"(dst), "r"(src), "r"(sz) : "memory");
}
__device__ __forceinline__ uint64_t stream_policy() {
  uint64_t p;
  asm volatile("createpolicy.fractional.L2::evict_first.b64 %0, 1.0;" : "=l"(p));
  return p;
}
__device__ __forceinline__ void tma_weights(uint32_t dst, const CUtensorMap* m, int k0, int mchunk, uint32_t bar, uint64_t pol) {
  asm volatile("cp.async.bulk.tensor.3d.shared::cluster.global.mbarrier::complete_tx::bytes.L2::cache_hint [%0], [%1, {%6, %3, %4}], [%2], %5;"
               ::"r"(dst), "l"(m), "r"(bar), "r"(k0), "r"(mchunk), "l"(pol), "r"(0) : "memory");
}
__device__ __forceinline__ void tma_weights_prefetch(const CUtensorMap* m, int k0, int mchunk, uint64_t pol) {
  asm volatile("cp.async.bulk.prefetch.tensor.3d.L2.global.L2::cache_hint [%0, {%4, %1, %2}], %3;" ::"l"(m), "r"(k0), "r"(mchunk), "l"(pol), "r"(0) : "memory");
}
__device__ __forceinline__ bool elect_one() {
  uint32_t p;
  asm volatile("{\n.reg .pred P;\nelect.sync _|P, 0xffffffff;\nselp.u32 %0, 1, 0, P;\n}" : "=r"(p));
  return p;
}
__device__ __forceinline__ void bulk_g2s_stream(uint32_t dst, const void* src, uint32_t sz, uint32_t bar, uint64_t pol) {
  asm volatile("cp.async.bulk.shared::cluster.global.mbarrier::complete_tx::bytes.L2::cache_hint [%0], [%1], %2, [%3], %4;"
               ::"r"(dst), "l"(src), "r"(sz), "r"(bar), "l"(pol) : "memory");
}
__device__ __forceinline__ void tma3d_store(const CUtensorMap* m, int c1, int c2, uint32_t src) {
  asm volatile("cp.async.bulk.tensor.3d.global.shared::cta.bulk_group [%0, {%4, %2, %3}], [%1];" ::"l"(m), "r"(src), "r"(c1), "r"(c2), "r"(0) : "memory");
}
__device__ __forceinline__ void tma2d_stream(uint32_t dst, const CUtensorMap* m, int c0, int c1, uint32_t bar, uint64_t pol) {
  asm volatile("cp.async.bulk.tensor.2d.shared::cluster.global.mbarrier::complete_tx::bytes.L2::cache_hint [%0], [%1, {%3, %4}], [%2], %5;"
               ::"r"(dst), "l"(m), "r"(bar), "r"(c0), "r"(c1), "l"(pol) : "memory");
}
__device__ __forceinline__ void tma4d_store(const CUtensorMap* m, int c1, int c2, int c3, uint32_t src) {
  asm volatile("cp.async.bulk.tensor.4d.global.shared::cta.bulk_group [%0, {%5, %2, %3, %4}], [%1];" ::"l"(m), "r"(src), "r"(c1), "r"(c2), "r"(c3), "r"(0) : "memory");
}
__device__ __forceinline__ void bulk_commit() { asm volatile("cp.async.bulk.commit_group;" ::: "memory"); }
__device__ __forceinline__ void bulk_wait_all() { asm volatile("cp.async.bulk.wait_group 0;" ::: "memory"); }
__device__ __forceinline__ void fence_async_smem() { asm volatile("fence.proxy.async.shared::cta;" ::: "memory"); }
__device__ __forceinline__ void fence_async_global() { asm volatile("fence.proxy.async.global;" ::: "memory"); }
__device__ __forceinline__ void named_bar(int id, int n) { asm volatile("bar.sync %0, %1;" ::"r"(id), "r"(n) : "memory"); }
__device__ __forceinline__ void named_arrive(int id, int n) { asm volatile("bar.arrive %0, %1;" ::"r"(id), "r"(n) : "memory"); }
__device__ __forceinline__ void flag_add(uint32_t* f, int i, uint32_t v) { asm volatile("red.relaxed.gpu.global.add.u32 [%0], %1;" ::"l"(f + i * 32), "r"(v) : "memory"); }
__device__ __forceinline__ uint32_t flag_ld(uint32_t* f, int i) { uint32_t v; asm volatile("ld.relaxed.gpu.global.u32 %0, [%1];" : "=r"(v) : "l"(f + i * 32) : "memory"); return v; }
__device__ __forceinline__ void prefetch_map(const CUtensorMap* m) { asm volatile("prefetch.tensormap [%0];" ::"l"(m) : "memory"); }
__device__ __forceinline__ void stsm4_t(uint32_t a, uint32_t r0, uint32_t r1, uint32_t r2, uint32_t r3) {
  asm volatile("stmatrix.sync.aligned.m8n8.x4.trans.shared.b16 [%0], {%1, %2, %3, %4};" ::"r"(a), "r"(r0), "r"(r1), "r"(r2), "r"(r3) : "memory");
}
__device__ __forceinline__ uint32_t lds32(uint32_t a) { uint32_t v; asm volatile("ld.shared.u32 %0, [%1];" : "=r"(v) : "r"(a) : "memory"); return v; }
__device__ __forceinline__ void sts32(uint32_t a, uint32_t v) { asm volatile("st.shared.u32 [%0], %1;" ::"r"(a), "r"(v) : "memory"); }
__device__ __forceinline__ uint4 ld_l2(const uint4* p) { uint4 v; asm volatile("ld.relaxed.gpu.global.v4.u32 {%0, %1, %2, %3}, [%4];" : "=r"(v.x), "=r"(v.y), "=r"(v.z), "=r"(v.w) : "l"(p) : "memory"); return v; }
__device__ __forceinline__ void sts128(uint32_t a, uint32_t x, uint32_t y, uint32_t z, uint32_t w) { asm volatile("st.shared.v4.u32 [%0], {%1, %2, %3, %4};" ::"r"(a), "r"(x), "r"(y), "r"(z), "r"(w) : "memory"); }
__device__ __forceinline__ uint4 lds128(uint32_t a) { uint4 v; asm volatile("ld.shared.v4.u32 {%0, %1, %2, %3}, [%4];" : "=r"(v.x), "=r"(v.y), "=r"(v.z), "=r"(v.w) : "r"(a) : "memory"); return v; }
__device__ __forceinline__ void st_async4(uint32_t raddr, uint32_t a, uint32_t b, uint32_t c, uint32_t d, uint32_t rbar) {
  asm volatile("st.async.weak.shared::cluster.mbarrier::complete_tx::bytes.v4.b32 [%0], {%1, %2, %3, %4}, [%5];" ::"r"(raddr), "r"(a), "r"(b), "r"(c), "r"(d), "r"(rbar) : "memory");
}
__device__ __forceinline__ uint32_t pack_bf16(float lo, float hi) { uint32_t r; asm("cvt.rn.bf16x2.f32 %0, %1, %2;" : "=r"(r) : "f"(hi), "f"(lo)); return r; }
__device__ __forceinline__ float bf_lo(uint32_t v) { return __uint_as_float(v << 16); }
__device__ __forceinline__ float bf_hi(uint32_t v) { return __uint_as_float(v & 0xffff0000u); }
__device__ __forceinline__ float bf_round(float x) { return bf_lo(pack_bf16(x, 0.f)); }
__device__ __forceinline__ uint32_t hmul2(uint32_t a, uint32_t b) { uint32_t r; asm("mul.rn.bf16x2 %0, %1, %2;" : "=r"(r) : "r"(a), "r"(b)); return r; }
__device__ __forceinline__ uint32_t hsub2(uint32_t a, uint32_t b) { uint32_t r; asm("sub.rn.bf16x2 %0, %1, %2;" : "=r"(r) : "r"(a), "r"(b)); return r; }
__device__ __forceinline__ uint32_t hfma2(uint32_t a, uint32_t b, uint32_t c) { uint32_t r; asm("fma.rn.bf16x2 %0, %1, %2, %3;" : "=r"(r) : "r"(a), "r"(b), "r"(c)); return r; }
__device__ __forceinline__ uint4 ldg128(const void* p) { uint4 v; asm volatile("ld.global.nc.v4.u32 {%0, %1, %2, %3}, [%4];" : "=r"(v.x), "=r"(v.y), "=r"(v.z), "=r"(v.w) : "l"(p)); return v; }
__device__ __forceinline__ uint32_t ldg16(const void* p) { uint32_t v; asm volatile("ld.global.nc.u16 %0, [%1];" : "=r"(v) : "l"(p)); return v; }
__device__ __forceinline__ float tanh_ordered(float x) { float y; asm volatile("tanh.approx.f32 %0, %1;" : "=f"(y) : "f"(x)); return y; }
__device__ __forceinline__ void mma16816(float (&d)[4], uint32_t a0, uint32_t a1, uint32_t a2, uint32_t a3, uint32_t b0, uint32_t b1) {
  asm("mma.sync.aligned.m16n8k16.row.col.f32.bf16.bf16.f32 {%0, %1, %2, %3}, {%4, %5, %6, %7}, {%8, %9}, {%0, %1, %2, %3};"
      : "+f"(d[0]), "+f"(d[1]), "+f"(d[2]), "+f"(d[3]) : "r"(a0), "r"(a1), "r"(a2), "r"(a3), "r"(b0), "r"(b1));
}
__device__ __forceinline__ uint32_t hadd2(uint32_t a, uint32_t b) { uint32_t r; asm("add.rn.bf16x2 %0, %1, %2;" : "=r"(r) : "r"(a), "r"(b)); return r; }
__device__ __forceinline__ uint32_t ldg32(const void* p) { uint32_t v; asm volatile("ld.global.nc.L1::no_allocate.u32 %0, [%1];" : "=r"(v) : "l"(p)); return v; }
__device__ __forceinline__ uint2 lds64(uint32_t a) { uint2 v; asm volatile("ld.shared.v2.u32 {%0, %1}, [%2];" : "=r"(v.x), "=r"(v.y) : "r"(a) : "memory"); return v; }
__device__ __forceinline__ uint32_t lds32_if(uint32_t a, uint32_t on) {
  uint32_t v;
  asm volatile("{\n.reg .pred p;\nsetp.ne.u32 p, %2, 0;\n@p ld.shared.u32 %0, [%1];\n}" : "=r"(v) : "r"(a), "r"(on) : "memory");
  return v;
}
__device__ __forceinline__ uint32_t clock_now() { uint32_t t; asm volatile("mov.u32 %0, %%clock;" : "=r"(t)); return t; }
__device__ __forceinline__ uint32_t time_now() { uint32_t t; asm volatile("mov.u32 %0, %%globaltimer_lo;" : "=r"(t)); return t; }
__device__ __forceinline__ void spin_until(uint32_t t0, uint32_t n) { while (clock_now() - t0 < n) {} }
__device__ __forceinline__ uint2 ldg64_if(const void* p, uint32_t on) {
  uint2 v;
  asm volatile("{\n.reg .pred p;\nsetp.ne.u32 p, %3, 0;\n@p ld.global.nc.v2.u32 {%0, %1}, [%2];\n}" : "=r"(v.x), "=r"(v.y) : "l"(p), "r"(on));
  return v;
}
template <class T> __device__ __forceinline__ T pin(T v) { asm volatile("" : "+r"(v)); return v; }
__device__ __forceinline__ void st_async2(uint32_t raddr, uint32_t a, uint32_t b, uint32_t rbar) {
  asm volatile("st.async.weak.shared::cluster.mbarrier::complete_tx::bytes.v2.b32 [%0], {%1, %2}, [%3];" ::"r"(raddr), "r"(a), "r"(b), "r"(rbar) : "memory");
}
__device__ __forceinline__ void bulk_prefetch(const void* src, uint32_t sz, uint64_t pol) {
  asm volatile("cp.async.bulk.prefetch.L2.global.L2::cache_hint [%0], %1, %2;" ::"l"(src), "r"(sz), "l"(pol) : "memory");
}
__device__ __forceinline__ void bulk_wait_read() { asm volatile("cp.async.bulk.wait_group.read 0;" ::: "memory"); }
__device__ __forceinline__ uint32_t shfl_ordered(uint32_t v, int src) { uint32_t r; asm volatile("shfl.sync.idx.b32 %0, %1, %2, 0x1f, 0xffffffff;" : "=r"(r) : "r"(v), "r"(src)); return r; }
__device__ __forceinline__ int chan_pos(int d) {
  return d < 512 ? 72 * (d >> 6) + ((d & 33) | ((d & 6) << 2) | ((d >> 2) & 6)) : 72 * ((d - 512) >> 3) + 64 + (d & 7);
}

struct Ring {
  uint32_t s, ph;
  __device__ __forceinline__ void next() { if (++s == ST) { s = 0; ph ^= 1; } }
};
constexpr int B_FULL = 0, B_GO = 40, B_CFULL = 48, B_SEMPTY = 80, B_ZFULL = 96, B_RFULL = 104, B_UDONE = 120, B_KFULL = 136, B_RAW = 168, B_CVGO = 248, B_PEER = 256, B_G2GO = 264, B_KVGO = 280,
              B_EMPTY = 296, B_G1DONE = 336,
              B_CEMPTY = 344, B_SFULL = 376, B_USTG = 392, B_END = 408;

__device__ __forceinline__ void poll_once(uint32_t* f, uint32_t& ready, int idx, uint32_t want, bool active) {
  bool ok = false;
  if (active) ok = flag_ld(f, idx) == want;
  const uint32_t seen = __ballot_sync(0xffffffffu, ok);
  if (seen & ~ready) fence_async_global();
  ready |= seen;
}
__device__ __forceinline__ void poll_bits(uint32_t* f, uint32_t& ready, uint32_t bits, int idx, uint32_t want, bool active) {
  for (uint32_t spins = 0; (ready & bits) != bits; spins++) {
    poll_once(f, ready, idx, want, active);
    if (spins > SPIN_LIMIT) asm volatile("trap;");
  }
}
__device__ __forceinline__ void wait_counter(uint32_t* f, int idx, uint32_t want, uint32_t first, uint32_t nap) {
#pragma unroll 1
  for (uint32_t spins = 0; first != want; spins++) {
    if (spins) __nanosleep(nap);
    first = flag_ld(f, idx);
    if (spins > SPIN_LIMIT) asm volatile("trap;");
  }
  fence_async_global();
}

__device__ __forceinline__ void gate_arrive(uint32_t* f, uint32_t back) {
  asm volatile("red.relaxed.gpu.global.max.u32 [%0], %1;" ::"l"(f + FL_GATE * 32 + 1), "r"(time_now() - back) : "memory");
  flag_add(f, FL_GATE, 1);
}

__device__ __forceinline__ float ln_rinv(float var) {
  float rt, rinv;
  asm("sqrt.approx.ftz.f32 %0, %1;" : "=f"(rt) : "f"(bf_round(bf_round(var) + 1e-5f)));
  asm("rcp.approx.ftz.f32 %0, %1;" : "=f"(rinv) : "f"(bf_round(rt)));
  return rinv;
}
__device__ __forceinline__ uint32_t ln_apply(uint32_t x, const uint4& st) {
  const uint32_t d = hsub2(x, st.x);
  return hfma2(d, st.y, hmul2(d, st.z));
}

__device__ __forceinline__ void polling_done(uint32_t* f, int lane) {
  unsigned old = 0;
  if (lane == 0) asm volatile("atom.relaxed.gpu.global.add.u32 %0, [%1], 1;" : "=r"(old) : "l"(f + FL_DONE * 32) : "memory");
  old = __shfl_sync(0xffffffffu, old, 0);
  if (old == NCTA + NG2 - 1) {
#pragma unroll 1
    for (int i = lane; i < FL_N; i += 32) *(uint2*)(f + i * 32) = make_uint2(0u, 0u);
  }
}

struct Pipe { Ring r; uint32_t prev; bool pending; int cnt; };
__device__ __forceinline__ void pipe_drain(Pipe& p, uint32_t bars, bool leader) {
  wg_wait<0>();
  if (leader) mbar_arrive(bars + B_EMPTY + p.prev * 8);
  p.pending = false;
}
template <int TB, int LEAD, int R>
__device__ __forceinline__ void gemm_run(float (&acc)[R], int n, int accumulate, Pipe& p, uint32_t sb, uint32_t pitch, int wg, bool leader) {
  const uint32_t bars = sb + BAR_OFF;
  const uint32_t dA0 = desc_lo(sb + wg * 8192, 8192), dB0 = desc_lo(sb + ASZ, TB ? 128 : 16);
  constexpr int KB_STEP = TB ? 16 : 2;
#pragma unroll 1
  for (int kb = 0; kb < n; kb++) {
    if (LEAD && kb == n - LEAD && wg == 1) { if (TB) pipe_drain(p, bars, leader); named_bar(8, 256); }
    mbar_wait(bars + B_FULL + p.r.s * 8, p.r.ph);
    if (kb == 0 && !accumulate && threadIdx.x == 0) { PROF(21 + TB); PROFC(49 - 2 * TB); }
    const uint32_t dA = dA0 + p.r.s * (pitch >> 4), dB = dB0 + p.r.s * (pitch >> 4);
    wg_fence();
    wgmma_ss<TB>(acc, dA, dB, accumulate | kb);
#pragma unroll
    for (int k = 1; k < 4; k++) wgmma_ss<TB>(acc, dA + k * 128, dB + k * KB_STEP, 1);
    wg_commit();
    wg_wait<1>();
    if (p.pending && leader) mbar_arrive(bars + B_EMPTY + p.prev * 8);
    p.pending = true;
    p.prev = p.r.s;
    p.r.next();
  }
  if (LEAD && wg == 0) named_arrive(8, 256);
}

template <int BROW0, int I0, int I1>
__device__ __forceinline__ void gemm2_part(float (&c)[36], uint32_t sb, uint32_t pitch, int wg) {
  const uint32_t dA0 = desc_lo(sb + wg * 8192, 8192), dB0 = desc_lo(sb + ASZ + BROW0 * 128, 16);
  wg_fence();
#pragma unroll
  for (int i = I0; i < I1; i++) {
    const int step = 68 - LAG + (i >> 2);
    if ((i & 3) == 0 && BROW0 == 0) mbar_wait_u(sb + BAR_OFF + B_FULL + (step % ST) * 8, (step / ST) & 1);
    if (i == 4 * LAG - TURN && BROW0 && wg == 0) named_arrive(7, 256);
    wgmma_ss<0>(c, dA0 + (step % ST) * (pitch >> 4) + (i & 3) * 128, dB0 + (step % ST) * (pitch >> 4) + (i & 3) * 2, 1);
  }
  wg_commit();
}
__device__ __forceinline__ void split_acc(const float (&acc)[72], float (&a)[36], float (&b)[36]) {
#pragma unroll
  for (int i = 0; i < 36; i++) { asm volatile("mov.b32 %0, %1;" : "=f"(a[i]) : "f"(acc[i])); asm volatile("mov.b32 %0, %1;" : "=f"(b[i]) : "f"(acc[36 + i])); }
}
template <int NV, int R, class Slice>
__device__ __forceinline__ void gelu_store(const float (&acc)[R], uint32_t bias0, uint32_t bias1, uint32_t sa, Slice slice) {
  const float hbias0 = 0.5f * bf_lo(pin(bias0)), hbias1 = 0.5f * bf_lo(pin(bias1));
  float hx[2][4], t[2][4], half = 0.5f;
  uint32_t pk[4];
#pragma unroll
  for (int j = 0; j <= NV / 4; j++) {
    if (j < NV / 4) {
      if (j >= 2) half = fmaf(t[j & 1][1], 0.f, 0.5f);
#pragma unroll
      for (int u = 0; u < 4; u++) {
        hx[j & 1][u] = fmaf(acc[4 * j + u], half, (u & 2) ? hbias1 : hbias0);
        t[j & 1][u] = tanh_ordered(hx[j & 1][u] * fmaf(hx[j & 1][u] * hx[j & 1][u], 0.2854192651f, 1.5957691216f));
      }
    }
    if (j > 0) {
      const float *hh = hx[(j - 1) & 1], *tt = t[(j - 1) & 1];
      pk[2 * ((j - 1) & 1)] = pack_bf16(fmaf(hh[0], tt[0], hh[0]), fmaf(hh[1], tt[1], hh[1]));
      pk[2 * ((j - 1) & 1) + 1] = pack_bf16(fmaf(hh[2], tt[2], hh[2]), fmaf(hh[3], tt[3], hh[3]));
      if (!(j & 1)) { stsm4_t(sa + (j - 2) * 1024, pk[0], pk[1], pk[2], pk[3]); slice(j / 2 - 1); }
    }
  }
}
struct Role { int half, kind, g2_m, dt, g1_mt, g1_nt, cs; uint32_t pitch; };
__device__ __forceinline__ Role get_role(const RoleMap& roles) {
  uint32_t b, sm;
  asm volatile("mov.u32 %0, %%ctaid.x;" : "=r"(b));
  asm volatile("mov.u32 %0, %%smid;" : "=r"(sm));
  const uint32_t w = roles.role[(roles.by_sm ? sm : b) >> 1];
  const int half = b & 1, kind = w & 3, m = (w >> 4) & 15, dt = (w >> 2) & 3;
  return Role{half, kind, m * 128, dt, half * 18 + (int)((w >> 8) & 31), (int)(w >> 16), (m * 4 + dt) * 2 + half, kind ? (uint32_t)PITCH_B : (uint32_t)PITCH_S};
}
__device__ __forceinline__ int g2_block(int half, int j) { return half * 36 + (j < 12 ? 2 * j : j < 24 ? 2 * j - 23 : j); }
__device__ __forceinline__ int conv_chan(int cs, int i) { return (3 * (cs >> 5) + (i >> 1)) * 64 + ((2 * cs) & 63) + (i & 1); }
__device__ __forceinline__ uint32_t conv_buf(uint32_t sb, int b) { return sb + (b == 3 ? (36 % ST) * PITCH_S : ST * PITCH_S + b * CBUF); }

__global__ void __cluster_dims__(2, 1, 1) __launch_bounds__(384, 1)
fused_kernel(const __nv_bfloat16* __restrict__ q, Scratch* __restrict__ gs, const __nv_bfloat16* __restrict__ b1,
             const __nv_bfloat16* __restrict__ shiftk, const __nv_bfloat16* __restrict__ ssmk, const __nv_bfloat16* __restrict__ ssmD,
             const __grid_constant__ CUtensorMap tmW1, const __grid_constant__ CUtensorMap tmW2, const __grid_constant__ CUtensorMap tmZ,
             const __grid_constant__ CUtensorMap tmH, const __grid_constant__ CUtensorMap tmK, const __grid_constant__ CUtensorMap tmV,
             const __grid_constant__ CUtensorMap tmKV, const __grid_constant__ RoleMap roles, const __nv_bfloat16* __restrict__ b2,
             __nv_bfloat16* __restrict__ out) {
  const int cta = blockIdx.x;
  const int tid = threadIdx.x;
  if (tid == 288) PROFG(0);

  const uint32_t t_start = clock_now();
  if (tid == 256) { prefetch_map(&tmW1); prefetch_map(&tmH); }
  const int lc = (cta + LNROT) & 127;
  const uint32_t do_ln = cta < 128 && tid < 256;
  const int oct = lc + (tid & 128), ln_row = oct * 8 + ((tid >> 4) & 7), l16 = tid & 15;
  uint2 xr[9];
  if (do_ln && oct >= TN(QLATE)) spin_until(t_start, TN(QDELAY) + TN(QRAMP) * oct / 2);
#pragma unroll
  for (int i = 0; i < 9; i++) xr[i] = ldg64_if(q + (size_t)ln_row * D_ + i * 64 + l16 * 4, do_ln);
  if (tid == 0) PROF(32);
  const int warp = __shfl_sync(0xffffffffu, tid >> 5, 0);
  const uint32_t sb = __shfl_sync(0xffffffffu, (uint32_t)__cvta_generic_to_shared(smem_raw), 0);
  const uint32_t bars = sb + BAR_OFF;
  const int lane = tid & 31;
  const int wg = warp >> 2;
  constexpr int LN_OFF = ST * PITCH_B;

  if (warp < 8 || warp == 11) {
    asm volatile("barrier.cluster.arrive.relaxed.aligned;" ::: "memory");
    const int hq = (lane & 16) >> 3, hb = (lane & 16) + hq;
    float da[3][4] = {};
#pragma unroll
    for (int i = 0; i < 9; i++) mma16816(da[i % 3], xr[i].x, 0x3f803f80u, xr[i].y, 0x3f803f80u, xr[i].x, xr[i].y);
    const float r1 = ((da[0][2] + da[0][3]) + (da[1][2] + da[1][3])) + (da[2][2] + da[2][3]);
    const float r2 = (lane & 4) ? (da[0][1] + da[1][1]) + da[2][1] : (da[0][0] + da[1][0]) + da[2][0];
    const float s1 = __shfl_sync(0xffffffffu, r1, hq) + __shfl_sync(0xffffffffu, r1, hq + 1);
    const float s2 = (__shfl_sync(0xffffffffu, r2, hb) + __shfl_sync(0xffffffffu, r2, hb + 4)) + (__shfl_sync(0xffffffffu, r2, hb + 9) + __shfl_sync(0xffffffffu, r2, hb + 13));
    if (tid == 0) { asm volatile("" ::"f"(s2) : "memory"); PROF(27); }
    const float mean = s1 * (1.f / D_), var = fmaxf(fmaf(-mean, mean, s2 * (1.f / D_)), 0.f);
    const float rinv = ln_rinv(var), rinv2 = ln_rinv(var * rinv * rinv), scale = rinv * rinv2, shift = -bf_round((mean - bf_round(mean)) * rinv) * rinv2;
    const uint32_t m2 = pack_bf16(mean, mean), hi2 = pack_bf16(scale, scale), lo2 = pack_bf16(scale - bf_lo(hi2), scale - bf_lo(hi2)), sh2 = pack_bf16(shift, shift);
    const uint32_t hi1 = pack_bf16(rinv, rinv);
    asm volatile("{\n.reg .pred p;\nsetp.eq.u32 p, %5, 0;\n@p st.shared.v4.u32 [%0], {%1, %2, %3, %4};\n}" ::"r"(sb + LN_OFF + 18432 + tid), "r"(m2), "r"(hi1),
                 "r"(pack_bf16(rinv - bf_lo(hi1), rinv - bf_lo(hi1))), "r"(0u), "r"(tid & 0x10f) : "memory");
    const uint32_t g0 = 4 * (l16 >> 3) + 2 * (l16 & 1), hrow = sb + LN_OFF + ((tid >> 7) & 1) * 9216 + (tid & 0x70);
    const uint32_t hs0 = hrow + g0 * 128 + ((l16 >> 1) & 3) * 4, hs8 = ((hrow + (l16 >> 1) * 1152) ^ ((l16 >> 1) << 4)) + 1024 + (l16 & 1) * 8;
    uint32_t w[18];
#pragma unroll
    for (int i = 0; i < 18; i++) {
      const uint32_t d = hsub2((i & 1) ? xr[i >> 1].y : xr[i >> 1].x, m2);
      asm("max.u32 %0, %1, 1;" : "=r"(w[i]) : "r"(hfma2(d, hi2, hfma2(d, lo2, sh2))));
    }
#pragma unroll
    for (int i = 0; i < 16; i++) {
      const int gi = 9 * (i >> 1) + (i & 1);
      asm volatile("{\n.reg .pred p;\nsetp.ne.u32 p, %2, 0;\n@p st.shared.u32 [%0], %1;\n}" ::"r"((hs0 ^ ((g0 * 16 + (gi & 7) * 16) & 0x70)) + gi * 128), "r"(w[i]), "r"(do_ln) : "memory");
    }
    asm volatile("{\n.reg .pred p;\nsetp.ne.u32 p, %3, 0;\n@p st.shared.v2.u32 [%0], {%1, %2};\n}" ::"r"(hs8), "r"(w[16]), "r"(w[17]), "r"(do_ln) : "memory");
    if (tid == 224) PROF(13);
    fence_async_smem();
    if (warp < 8) named_arrive(wg, 160);
  } else if (warp != 8) {
    spin_until(t_start, TN(W9));
  }

  if (wg == 2) {
    asm volatile("setmaxnreg.dec.sync.aligned.u32 56;");
    auto store_h = [&](int w) {
      named_bar(w, 160);
      if (cta < 128 && elect_one()) {
        tma3d_store(&tmH, ((lc >> 3) + 16 * w) * 72, lc & 7, sb + LN_OFF + w * 9216);
        bulk_s2g(gs->stats + (lc + 128 * w) * 8, sb + LN_OFF + 18432 + w * 128, 128);
        bulk_commit();
      }
    };
    auto publish_h = [&](int w) {
      if (cta < 128 && elect_one()) { bulk_wait_all(); flag_add(gs->flags, FL_H + (lc >> 3) + 16 * w, 1); }
      __syncwarp();
    };
    if (warp == 11) {
      store_h(0);
      if (lane == 0) PROF(29);
      publish_h(0);
      if (lane == 0) PROF(1);
    } else {
      if (elect_one()) {
        if (warp == 8) {
#pragma unroll
          for (int o = 0; o < B_GO; o += 8) mbar_init(bars + o, 1);
        } else if (warp == 9) {
#pragma unroll
          for (int o = B_GO; o < B_RAW + 40; o += 8) mbar_init(bars + o, 1);
        } else {
#pragma unroll
          for (int o = B_RAW + 40; o < B_END; o += 8) mbar_init(bars + o, o < B_EMPTY ? 1 : o < B_CEMPTY ? 2 : 4);
        }
        asm volatile("fence.mbarrier_init.release.cluster;" ::: "memory");
      }
      __syncwarp();
      asm volatile("barrier.cluster.arrive.relaxed.aligned;" ::: "memory");
      if (warp == 9) { prefetch_map(&tmK); prefetch_map(&tmV); prefetch_map(&tmKV); prefetch_map(&tmW2); prefetch_map(&tmZ); }
      if (tid == 256) PROF(35);
    }
    const Role ro = get_role(roles);
    if (warp != 8) asm volatile("barrier.cluster.wait.aligned;" ::: "memory");
    if (warp == 11) {
      Ring r{0, 1};
      uint32_t ready = 0;
      const uint32_t bsz = ro.pitch - ASZ;
      const uint8_t* src = gs->h + ro.g1_nt * bsz + ST * 73728;
      named_bar(10, 64);
#pragma unroll 1
      for (int i = ST; i < 32; i++) {
        poll_bits(gs->flags, ready, i == 31 ? 0xffffffffu : 1u << i, FL_H + lane, 8u, true);
        mbar_wait(bars + B_EMPTY + r.s * 8, r.ph ^ 1);
        if (elect_one()) bulk_g2s(sb + r.s * ro.pitch + ASZ, src, bsz, bars + B_FULL + r.s * 8);
        if (i == ST && lane == 0) PROF(25);
        if (i == TN(HS2)) store_h(1);
        if (i == TN(HS2) + 2) { publish_h(1); if (lane == 0) mbar_arrive(bars + B_KVGO + 8); }
        if (i == TN(KVGO) && lane == 0) mbar_arrive(bars + B_KVGO);
        if (i == TN(CVGO) && lane == 0) mbar_arrive(bars + B_CVGO);
        src += 73728;
        r.next();
      }
      if (ro.kind != 2) {
        uint32_t look = 0;
#pragma unroll 1
        for (int j = 0; j < 36; j++) {
          const uint8_t* su = gs->u + ((size_t)g2_block(ro.half, j) * D_ + ro.dt * 144) * 128;
          if (j == 0 || j == 12 || j == 24) wait_counter(gs->flags, FL_U + ro.half * 3 + j / 12, j == 24 ? 36u : 48u, look, 100);
          if (ro.kind ? j == 4 : j < 2) mbar_wait_u(bars + B_UDONE + (j ? 8 : 0), 0);
          mbar_wait(bars + B_EMPTY + r.s * 8, r.ph ^ 1);
          if (elect_one()) {
            bulk_g2s(sb + r.s * ro.pitch + ASZ, su + (ro.half ^ 1) * 9216, 9216, bars + B_FULL + r.s * 8);
            bulk_g2s(sb + r.s * ro.pitch + ASZ + 9216, su + ro.half * 9216, 9216, bars + B_FULL + r.s * 8);
          }
          if (j == 9 || j == 21) look = flag_ld(gs->flags, FL_U + ro.half * 3 + j / 12 + 1);
          if (j == 0 && lane == 0) PROF(8);
          r.next();
        }
#pragma unroll 1
        for (int o = lane; o < ST * 73728 / 16 / NG2; o += 32) ((uint4*)gs->h)[ro.cs * (ST * 73728 / 16 / NG2) + o] = make_uint4(0u, 0u, 0u, 0u);
      }
      polling_done(gs->flags, lane);
    } else if (warp == 8) {
      const uint64_t pol = stream_policy();
      Ring r{0, 0};
#pragma unroll 1
      for (int i = 0; i < 32; i++) {
        if (i < ST) spin_until(t_start, TN(A0) + i * TN(AD) + (i >= TN(AN) ? TN(AL) : 0));
        if (i == ST) {
          asm volatile("barrier.cluster.wait.aligned;" ::: "memory");
          if (roles.by_sm) {
            uint32_t sm;
            asm volatile("mov.u32 %0, %%smid;" : "=r"(sm));
            if (elect_one()) { mbar_expect(bars + B_PEER, 8); st_async2(mapa(bars + B_END, ro.half ^ 1), sm, sm, mapa(bars + B_PEER, ro.half ^ 1)); }
            mbar_wait_u(bars + B_PEER, 0);
            if ((lds32(bars + B_END) ^ sm) != 1 || sm >= NCTA) asm volatile("trap;");
          }
        }
        if (i >= ST) mbar_wait(bars + B_EMPTY + r.s * 8, r.ph ^ 1);
        if (elect_one()) {
          mbar_expect(bars + B_FULL + r.s * 8, ro.pitch);
          tma_weights(sb + r.s * ro.pitch, &tmW1, i * 64, ro.g1_mt * 2, bars + B_FULL + r.s * 8, pol);
        }
        r.next();
      }
      if (ro.kind != 2) {
#pragma unroll 1
        for (int j = 0; j < 36; j++) {
          if (j == 4) {
#pragma unroll 1
            for (int k = 0; k < TN(NPF); k++) {
              spin_until(clock_now(), TN(PFGAP));
              const int jj = 4 + 4 * k + ro.dt;
              if (elect_one() && jj < 36) tma_weights_prefetch(&tmW2, g2_block(ro.half, jj) * 64, ro.g2_m >> 6, pol);
            }
            if (ro.kind == 0) mbar_wait_u(bars + B_CEMPTY + 24, 0);
          }
          mbar_wait(bars + B_EMPTY + r.s * 8, r.ph ^ 1);
          if (elect_one()) {
            mbar_expect(bars + B_FULL + r.s * 8, PITCH_S);
            tma_weights(sb + r.s * ro.pitch, &tmW2, g2_block(ro.half, j) * 64, ro.g2_m >> 6, bars + B_FULL + r.s * 8, pol);
          }
          r.next();
        }
        if (lane < 2) mbar_expect(bars + B_RFULL + lane * 8, 9216);
        __syncwarp();
        mbar_wait(bars + B_EMPTY + r.s * 8, r.ph ^ 1);
        if (lane == 0) mbar_arrive_cluster(mapa(bars + B_GO, ro.half ^ 1));
      }
      if (lane == 0) PROF(28);
    } else {
      const uint64_t pol = stream_policy();
      {
        const uint32_t hb = (ro.pitch - ASZ) >> 1, raw = bars + B_RAW + (warp - 9) * 40, dst = sb + ASZ + (warp - 9) * hb;
        const uint8_t* src = gs->h + (2 * ro.g1_nt + warp - 9) * hb;
        auto fetch_h = [&](int i) { if (elect_one()) { mbar_expect(raw + i * 8, hb); bulk_g2s(dst + i * ro.pitch, src + i * 73728, hb, raw + i * 8); } };
        int next = 0;
#pragma unroll 1
        for (int i = -1; i < ST; i++) {
          if (i >= 0) {
#pragma unroll 1
            for (uint32_t tries = 0;; tries++) {
              mbar_wait_u(raw + i * 8, tries & 1);
              if (lane == 0 && i == 0) PROF(29 + warp);
              const uint32_t pa = dst + i * ro.pitch + lane * 32 + (lane >> 2) * 4;
              uint32_t m = 1;
#pragma unroll
              for (int j = 0; j < 12; j++) m = min(m, lds32(pa + (j < 9 || ro.kind ? j : 0) * 1024));
              if (__all_sync(0xffffffffu, m)) break;
              if (lane == 0) PROF(26);
              fetch_h(i);
            }
            if (elect_one()) asm volatile("mbarrier.complete_tx.relaxed.cta.shared::cta.b64 [%0], %1;" ::"r"(bars + B_FULL + i * 8), "r"(hb) : "memory");
          }
#pragma unroll 1
          for (const int end = min(next + 2, ST); next < end; next++) {
            if (i < 0) spin_until(t_start, TN(H0) + next * TN(HD));
            fetch_h(next);
            if (next == 0 && tid == 288) PROF(3);
          }
          if (i < 0 && warp == 10) named_arrive(10, 64);
        }
      }
      if (ro.kind == 0) {
        mbar_wait_u(bars + B_KVGO + (warp - 9) * 8, 0);
        const int cs = ro.cs, grp = (cs / 3) * 2 + warp - 9, cb0 = (cs % 3) * 3;
        const uint32_t kin_s = sb + ST * PITCH_S + (warp - 9) * KVW, kout = kin_s + 2 * KVIN + lane * 176, fb = bars + B_KFULL + (warp - 9) * 16;
        auto fetch = [&](int i) {
          if (elect_one()) {
            mbar_expect(fb + (i & 1) * 8, KVIN);
            tma2d_stream(kin_s + (i & 1) * KVIN, &tmK, (cb0 + i) * 64, grp * 32 - 4, fb + (i & 1) * 8, pol);
            tma2d_stream(kin_s + (i & 1) * KVIN + 4608, &tmV, (cb0 + i) * 64, grp * 32 - 1, fb + (i & 1) * 8, pol);
          }
        };
        fetch(0);
        uint4 shk = ldg128(shiftk + (cb0 * 64 + lane * 2) * 4);
        const uint32_t dskip = ldg16(ssmD + conv_chan(cs, lane < NCONV ? lane : 0));
#pragma unroll 1
        for (int i = 0; i < 3; i++) {
          const uint32_t w0 = __byte_perm(shk.x, shk.z, 0x5410), w1 = __byte_perm(shk.x, shk.z, 0x7632);
          const uint32_t w2 = __byte_perm(shk.y, shk.w, 0x5410), w3 = __byte_perm(shk.y, shk.w, 0x7632);
          const uint32_t ka = kin_s + (i & 1) * KVIN + lane * 4;
          mbar_wait_u(fb + (i & 1) * 8, i >> 1);
          if (tid == 288 && i < 2) PROF(30 + i);
          if (i < 2) fetch(i + 1);
          shk = ldg128(i < 2 ? shiftk + ((cb0 + i + 1) * 64 + lane * 2) * 4 : ssmk + (size_t)conv_chan(cs, lane < NCONV ? lane : 0) * S_);
          uint32_t kr[20], x[17];
          auto rows = [&](uint32_t from, int j0) {
#pragma unroll
            for (int j = j0; j < j0 + 4; j++) { kr[j] = lds32(from + j * 128); if (j >= 3) x[j - 3] = lds32(from + 4608 + (j - 3) * 128); }
          };
          rows(ka, 0); rows(ka, 4); rows(ka, 8);
          x[0] = hmul2(hfma2(kr[3], w0, hfma2(kr[2], w1, hfma2(kr[1], w2, hmul2(kr[0], w3)))), x[0]);
          if (i) { if (elect_one()) bulk_wait_read(); __syncwarp(); }
#pragma unroll 1
          for (int o = 0; o < 4; o++) {
            const uint32_t from = ka + (o < 3 ? o : 2) * 1024, to = kout + o * 32;
#pragma unroll
            for (int m = 0; m < 8; m += 4) {
#pragma unroll
              for (int j = m + 1; j < m + 5; j++) x[j] = hmul2(hfma2(kr[j + 3], w0, hfma2(kr[j + 2], w1, hfma2(kr[j + 1], w2, hmul2(kr[j], w3)))), x[j]);
#pragma unroll
              for (int c = 0; c < 2; c++) {
                const uint32_t sel = c ? 0x7632 : 0x5410;
                const uint32_t a0 = __byte_perm(x[m + 1], x[m], sel), a1 = __byte_perm(x[m + 2], x[m + 1], sel);
                const uint32_t a2 = __byte_perm(x[m + 3], x[m + 2], sel), a3 = __byte_perm(x[m + 4], x[m + 3], sel);
                sts128(to + c * 5632 + m * 4, a0, a1, a2, a3);
                asm volatile("{\n.reg .pred p;\nsetp.eq.u32 p, %5, 3;\n@p st.shared.v4.u32 [%0], {%1, %2, %3, %4};\n}" ::"r"(to + c * 5632 + m * 4 + 32), "r"(a0), "r"(a1), "r"(a2), "r"(a3), "r"(o) : "memory");
              }
#pragma unroll
              for (int j = m + 12; j < m + 16; j++) { kr[j] = lds32_if(from + j * 128, o < 3); x[j - 3] = lds32_if(from + 4608 + (j - 3) * 128, o < 3); }
            }
#pragma unroll
            for (int j = 1; j < 12; j++) kr[j] = kr[j + 8];
#pragma unroll
            for (int j = 0; j < 9; j++) x[j] = x[j + 8];
          }
          fence_async_smem();
          __syncwarp();
          if (i && elect_one()) { bulk_wait_all(); flag_add(gs->flags, FL_KV + i - 1, 1); }
#pragma unroll 1
          for (int k = 0; k < 64 / KVROWS; k++) {
            if (k) spin_until(clock_now(), TN(KVGAP));
            if (elect_one()) { tma4d_store(&tmKV, (cb0 + i) * 32 + ((k * KVROWS) & 31), (k * KVROWS) >> 5, grp, kin_s + 2 * KVIN + k * KVROWS * 176); bulk_commit(); }
          }
        }
        shk.x = __byte_perm(pack_bf16(bf_lo(shk.x) + bf_lo(dskip), 0.f), shk.x, 0x7610);
        const uint32_t look = flag_ld(gs->flags, FL_KV + warp - 9);
        if (elect_one()) {
          bulk_wait_all();
          flag_add(gs->flags, FL_KV + 2, 1);
          bulk_prefetch(ssmk + (size_t)conv_chan(cs, 2 * (warp - 9)) * S_, 2 * S_ * 2, pol);
          if (warp == 9) PROFG(2);
        }
        __syncwarp();
#pragma unroll 1
        for (int i = warp == 9 ? 0 : 2; i < (warp == 9 ? 2 : NCONV); i++) {
          const int b = i & 3, d = conv_chan(cs, i);
          const uint32_t base = conv_buf(sb, b), cf = bars + B_CFULL + b * 8;
          if (!(i & 1)) wait_counter(gs->flags, FL_KV + (i >> 1), 192u, i < 4 ? look : 0u, 200);
          if (i == 0 || i == 2) mbar_wait_u(bars + B_CVGO, 0);
          if (i == 0 && lane == 0) PROF(23);
          if (i == 3) {
            mbar_wait_u(bars + B_G1DONE, 0);
            if (elect_one()) bulk_prefetch(ssmk + (size_t)conv_chan(cs, 4) * S_, 2 * S_ * 2, pol);
          }
          if (i >= 4) mbar_wait_u(bars + B_CEMPTY + b * 8, 0);
          if (lane == i) sts128(base + CH_OFF, shk.x, shk.y, shk.z, shk.w);
          if (lane >= 27) sts128(base + (lane >= 29 ? CH_OFF + (lane - 32) * 16 : CT_OFF + (lane - 27) * 16), 0u, 0u, 0u, 0u);
          fence_async_smem();
          __syncwarp();
          if (elect_one()) {
            mbar_expect(cf, 4080 + KVT - 32);
            bulk_g2s(base + CT_OFF + 32, gs->kv + (size_t)d * KVT, KVT - 32, cf);
            bulk_g2s_stream(base + CH_OFF + 16, ssmk + (size_t)d * S_ + 8, 4080, cf, pol);
          }
        }
      }
      if (warp == 9) {
        if (elect_one()) {
          const uint32_t bsz = ro.pitch - ASZ;
#pragma unroll 1
          for (int w = 0; w < 2; w++) {
            const uint32_t src = sb + (ro.kind ? (w ? (36 % ST) * PITCH_B + ASZ : ST * PITCH_B) : ((32 % ST) + w) * PITCH_S + ASZ);
            mbar_wait_u(bars + B_USTG + w * 8, 0);
            bulk_s2g(gs->u + (size_t)(2 * ro.g1_mt + w) * D_ * 128 + ro.g1_nt * bsz, src, bsz);
            bulk_commit();
            if (ro.kind && w == 0) gate_arrive(gs->flags, TN(GDELAY) - 512);
            bulk_wait_read();
            mbar_arrive(bars + B_UDONE + w * 8);
            bulk_wait_all();
            flag_add(gs->flags, FL_U + ro.half * 3 + (ro.kind ? 2 : w), 1);
            PROFG(5 + 12 * w);
          }
          if (ro.kind == 0) {
#pragma unroll 1
            for (int i = 0; i < NCONV; i++) {
              mbar_wait_u(bars + B_SFULL + (i & 1) * 8, (i >> 1) & 1);
              bulk_s2g(gs->z + (size_t)chan_pos(conv_chan(ro.cs, i)) * S_, sb + CSTG_OFF + (i & 1) * 4096, 4096);
              bulk_commit();
              if (i == NCONV - 3) gate_arrive(gs->flags, 0);
              bulk_wait_read();
              mbar_arrive(bars + B_SEMPTY + (i & 1) * 8);
            }
            bulk_wait_all();
            flag_add(gs->flags, FL_Z, 1);
            PROFG(6);
          }
        }
      } else if (ro.kind != 2) {
        mbar_wait_u(bars + B_UDONE, 0);
        uint2 gate;
#pragma unroll 1
        for (uint32_t spins = 0;; spins++) {
          asm volatile("ld.relaxed.gpu.global.v2.u32 {%0, %1}, [%2];" : "=r"(gate.x), "=r"(gate.y) : "l"(gs->flags + FL_GATE * 32) : "memory");
          if (gate.x == NCTA) break;
          __nanosleep(100);
          if (spins > SPIN_LIMIT) asm volatile("trap;");
        }
        if (lane == 0) PROF(46);
#pragma unroll 1
        for (int w = 0; w < 2; w++) {
          while (time_now() - gate.y < TN(GDELAY) + w * TN(GDELAY1)) {}
          if (lane == 0) mbar_arrive(bars + B_G2GO + w * 8);
          if (lane == 0 && w == 0) PROF(24);
        }
        wait_counter(gs->flags, FL_Z, 96u, 0, 300);
        spin_until(clock_now(), TN(ZDELAY) + TN(ZRAMP) * cta);
        if (elect_one()) {
          mbar_expect(bars + B_ZFULL, 18432);
          tma2d(sb + ST * ro.pitch, &tmZ, ro.g2_m, ro.dt * 144 + ro.half * 72, bars + B_ZFULL);
          tma2d(sb + ST * ro.pitch + 9216, &tmZ, ro.g2_m + 64, ro.dt * 144 + ro.half * 72, bars + B_ZFULL);
          PROFG(7);
        }
        polling_done(gs->flags, lane);
      }
    }
  } else {
    asm volatile("setmaxnreg.inc.sync.aligned.u32 224;");
    const int wi = warp & 3, g = lane >> 2, qd = lane & 3, wt = tid & 127;
    const bool leader = wt == 0;
    Pipe p{{0, 0}, 0, false, 0};
    asm volatile("barrier.cluster.wait.aligned;" ::: "memory");
    int kind;
    {
      const Role ro = get_role(roles);
      kind = ro.kind;
      const int f0 = ro.g1_mt * 128 + wg * 64 + wi * 16 + g;
      uint32_t bias0 = ldg16(b1 + f0), bias1 = ldg16(b1 + f0 + 8);
      const uint32_t so = ((lane >> 4) * 8 + (lane & 7)) * 128 + (((2 * wi + ((lane >> 3) & 1)) ^ (lane & 7)) << 4);
      if (kind) {
        float acc[96];
        gemm_run<1, LEAD_B>(acc, 32, 0, p, sb, PITCH_B, wg, leader);
        pipe_drain(p, bars, leader);
        if (wg) mbar_wait_u(bars + B_EMPTY + (36 % ST) * 8, ((36 / ST) & 1) ^ 1);
        if (leader) PROF(4 + 10 * wg);
        uint32_t sa = sb + (wg ? (36 % ST) * PITCH_B + ASZ : ST * PITCH_B) + so;
#pragma unroll 1
        for (int c = 0; c < 4; c++, sa += 6144) {
          gelu_store<24>(acc, bias0, bias1, sa, [](int) {});
#pragma unroll
          for (int i = 0; i < 72; i++) acc[i] = acc[i + 24];
        }
        fence_async_smem();
        __syncwarp();
        if (lane == 0) mbar_arrive(bars + B_USTG + wg * 8);
        if (leader) PROF(15 + wg);
      } else {
        const int cB = (g >> 1) & 1, cA = g >> 2, b = 2 * wi + (g & 1);
        const uint32_t toff = pin(CT_OFF + (40 * (2 * cA + cB) + 8 + b - 2 * qd) * 4);
        uint32_t a[16][4];
        auto load_a = [&](uint32_t base, int t, uint32_t on) {
          const uint32_t pt = base + toff + (t >> 1) * 1280 + (t & 1) * 64;
          a[t][0] = lds32_if(pt + 32, on); a[t][1] = lds32_if(pt + 672, on); a[t][2] = lds32_if(pt, on); a[t][3] = lds32_if(pt + 640, on);
        };
        {
          float acc[72];
          gemm_run<1, LEAD_S>(acc, 32, 0, p, sb, PITCH_S, wg, leader);
          if (wg == 1) named_arrive(6, 256);
          mbar_wait_u(bars + B_EMPTY + ((32 % ST) + wg) * 8, ((32 / ST) & 1) ^ 1);
          mbar_wait_u(bars + B_CFULL + wg * 8, 0);
          pipe_drain(p, bars, leader);
          if (leader) mbar_arrive(bars + B_G1DONE);
          if (leader) PROF(4 + 10 * wg);
          if (tid == 128) PROFC(48);
          gelu_store<72>(acc, bias0, bias1, sb + ((32 % ST) + wg) * PITCH_S + ASZ + so, [&](int t) { if (t < 8) load_a(conv_buf(sb, wg), t, 1); });
          fence_async_smem();
          __syncwarp();
          if (lane == 0) mbar_arrive(bars + B_USTG + wg * 8);
          if (leader) PROF(15 + wg);
        }
        const int phi = 2 * cA + (qd >> 1) + cB, pp = cB ? (phi & 3) : ((phi + 3) & 3);
        const int srcB = pin(((pp >> 1) << 4) | ((cB ^ 1) << 3) | ((g & 1) << 2) | ((pp & 1) << 1) | (qd & 1));
        const bool pB1 = cB && phi < 4, pB2 = cB && phi == 4;
        const int word = (8 * cB + 2 * (phi & 3) + (qd & 1)) * 8 + b;
        const uint32_t sto = pin(sb + CSTG_OFF + wg * 4096 + (word ^ (((word >> 5) & 3) << 1)) * 4);
#pragma unroll 1
        for (int i = wg; i < NCONV; i += 2) {
          const uint32_t base = conv_buf(sb, i & 3), next = conv_buf(sb, (i + 2) & 3);
          const uint64_t dH = mkdesc(base + CH_OFF, 16, 128, 0);
          float y[8][16];
          named_bar(6 + wg, 256);
          wg_fence();
#pragma unroll
          for (int t = 0; t < 16; t++) {
            if (t >= 8 && t % CFENCE == 0) wg_fence();
            if (t == CTURN) named_arrive(7 - wg, 256);
#pragma unroll
            for (int cb = t >> 1; cb < 8; cb++) {
              wgmma_rs_n32(y[cb], a[t][0], a[t][1], a[t][2], a[t][3], dH + (32 * cb - 32 * (t >> 1) - 2 * (t & 1) - 1), t);
              const int n = 8 * t - (t >> 1) * ((t - 1) >> 1) - (t >> 1) + cb + 1;
              if (n % CPER == 0 && n / CPER <= 8) load_a(base, 7 + n / CPER, 1);
            }
            if (t == 7 && CEARLY) wg_commit();
          }
          wg_commit();
          const bool more = i + 2 < NCONV;
          if (more) mbar_wait_u(bars + B_CFULL + ((i + 2) & 3) * 8, (i + 2) >> 2);
          mbar_wait_u(bars + B_SEMPTY + wg * 8, ((i >> 1) & 1) ^ 1);
          if (CEARLY) wg_wait<1>();
#pragma unroll
          for (int t = 0; t < CEARLY; t++) load_a(next, t, more);
          wg_wait<0>();
          if (lane == 0) mbar_arrive(bars + B_CEMPTY + (i & 3) * 8);
          if (leader) PROF(40 + i);
          uint32_t P[16], Q[16], R[16], o[8];
#pragma unroll
          for (int j = 0; j < 32; j++) {
            if ((j & 3) == 0 && (j >> 2) >= CEARLY) load_a(next, j >> 2, more);
            float v0 = y[j >> 2][4 * (j & 3)], v1 = y[j >> 2][4 * (j & 3) + 1];
            if (j >= 2) { v0 += y[(j - 2) >> 2][4 * ((j - 2) & 3) + 2]; v1 += y[(j - 2) >> 2][4 * ((j - 2) & 3) + 3]; }
            if (j & 1) R[j >> 1] = shfl_ordered(pack_bf16(v0, v1), lane ^ 16);
            else P[j >> 1] = pack_bf16(v0, v1);
          }
#pragma unroll
          for (int m = 0; m < 16; m++) Q[m] = hadd2(P[m], cA ? R[m] : (m ? R[m - 1] : 0u));
#pragma unroll
          for (int m = 0; m < 8; m++) o[m] = shfl_ordered(pB1 ? Q[2 * m] : (pB2 ? (m ? Q[2 * m - 1] : 0u) : Q[2 * m + 1]), srcB);
#pragma unroll
          for (int m = 0; m < 8; m++) sts32(sto + m * 512, hadd2(pB1 ? Q[2 * m + 1] : Q[2 * m], o[m]));
          fence_async_smem();
          __syncwarp();
          if (lane == 0) mbar_arrive(bars + B_SFULL + wg * 8);
          if (leader && i == 5) PROF(53);
        }
        if (wg == 0) named_bar(6, 256);
      }
    }
    if (kind != 2) {
      const Role ro = get_role(roles);
      const uint32_t pitch = ro.pitch;
      const int s0 = ro.g2_m + wg * 64 + wi * 16 + g;
      const size_t go = (size_t)s0 * D_ + ro.dt * 128 + ro.half * 64 + qd * 8, go8 = (size_t)s0 * D_ + 512 + ro.dt * 16 + ro.half * 8 + qd * 2;
      uint32_t x[2][9], sg[2][9];
      float acc[72];
      mbar_wait_u(bars + B_G2GO + wg * 8, 0);
      gemm_run<0, 0>(acc, XAT + 2 * wg, 0, p, sb, pitch, wg, leader);
#pragma unroll
      for (int J = 0; J < 4; J++) {
        const uint4 v = ldg128(q + go + (J & 1) * 8 * D_ + (J >> 1) * 32);
        x[J & 1][4 * (J >> 1)] = v.x; x[J & 1][4 * (J >> 1) + 1] = v.y; x[J & 1][4 * (J >> 1) + 2] = v.z; x[J & 1][4 * (J >> 1) + 3] = v.w;
      }
      x[0][8] = ldg32(q + go8); x[1][8] = ldg32(q + go8 + 8 * D_);
      const uint4 st0 = ld_l2(gs->stats + s0), st1 = ld_l2(gs->stats + s0 + 8);
      const uint32_t braw0 = ldg16(b2 + s0), braw1 = ldg16(b2 + s0 + 8);
      gemm_run<0, 0>(acc, 20 - XAT, 1, p, sb, pitch, wg, leader);
      {
        const int zw = 8 * wi + (g ^ ((((ro.g2_m >> 6) + wg) & 3) << 1));
        const uint32_t za = sb + ST * pitch + wg * 9216 + qd * 256 + (zw & 3) * 4;
        mbar_wait_u(bars + B_ZFULL, 0);
#pragma unroll
        for (int j = 0; j < 9; j++) {
          sg[0][j] = lds32(za + j * 1024 + (((zw >> 2) ^ (2 * qd)) << 4));
          sg[1][j] = lds32(za + j * 1024 + 128 + (((zw >> 2) ^ (2 * qd + 1)) << 4));
        }
      }
      gemm_run<0, 0>(acc, 1, 1, p, sb, pitch, wg, leader);
#pragma unroll
      for (int j = 0; j < 9; j++) {
        const uint32_t z0 = __byte_perm(sg[0][j], sg[1][j], 0x5410), z1 = __byte_perm(sg[0][j], sg[1][j], 0x7632);
        sg[0][j] = hmul2(ln_apply(x[0][j], st0), z0);
        sg[1][j] = hmul2(ln_apply(x[1][j], st1), z1);
        asm volatile("" : "+r"(sg[0][j]), "+r"(sg[1][j]));
      }
      gemm_run<0, SKEW>(acc, 15 - LAG - 2 * wg, 1, p, sb, pitch, wg, leader);
      const uint32_t rbuf = sb + (68 % ST) * pitch + warp * 2304;
      const uint32_t rdst = mapa(rbuf, ro.half ^ 1), rbar = mapa(bars + B_RFULL + wg * 8, ro.half ^ 1);
      pipe_drain(p, bars, leader);
      if (leader) PROF(9 + 10 * wg);
      if (tid == 128) PROFC(50);
      float cs[36], ck[36];
      split_acc(acc, cs, ck);
      gemm2_part<0, 0, 4 * LAG>(cs, sb, pitch, wg);
      if (KPRE) gemm2_part<72, 0, KPRE>(ck, sb, pitch, wg);
      const float hb0 = fmaf(bf_lo(braw0), 0.5f, __uint_as_float(st0.w)), hb1 = fmaf(bf_lo(braw1), 0.5f, __uint_as_float(st1.w));
      mbar_wait(bars + B_GO, 0);
      wg_wait<KPRE ? 1 : 0>();
      if (leader) PROF(54 + wg);
#pragma unroll
      for (int i = 0; i < 5; i++) {
        const float* c = &cs[8 * i];
        const uint32_t v0 = pack_bf16(fmaf(c[0], 0.5f, hb0), fmaf(c[1], 0.5f, hb0)), v1 = pack_bf16(fmaf(c[2], 0.5f, hb1), fmaf(c[3], 0.5f, hb1));
        if (i < 4) st_async4(rdst + i * 512 + lane * 16, v0, v1, pack_bf16(fmaf(c[4], 0.5f, hb0), fmaf(c[5], 0.5f, hb0)), pack_bf16(fmaf(c[6], 0.5f, hb1), fmaf(c[7], 0.5f, hb1)), rbar);
        else st_async2(rdst + 2048 + lane * 8, v0, v1, rbar);
      }
      if (wg == 1) named_bar(7, 256);
      gemm2_part<72, KPRE, 4 * LAG>(ck, sb, pitch, wg);
      uint32_t rp[18];
      mbar_wait(bars + B_RFULL + wg * 8, 0);
#pragma unroll
      for (int m = 0; m < 4; m++) {
        const uint4 v = lds128(rbuf + m * 512 + lane * 16);
        rp[4 * m] = v.x; rp[4 * m + 1] = v.y; rp[4 * m + 2] = v.z; rp[4 * m + 3] = v.w;
      }
      { const uint2 v = lds64(rbuf + 2048 + lane * 8); rp[16] = v.x; rp[17] = v.y; }
      __nv_bfloat16* o = out + go;
      wg_wait<0>();
      if (leader) PROF(10 + 10 * wg);
      float h[2][4], t[2][4], half = 0.5f;
#pragma unroll
      for (int j = 0; j <= 9; j++) {
        if (j < 9) {
          const uint32_t ra = rp[2 * j], rb = rp[2 * j + 1];
          if (j >= 2) half = fmaf(t[j & 1][3], 0.f, 0.5f);
          h[j & 1][0] = fmaf(ck[4 * j], half, bf_lo(ra)); h[j & 1][1] = fmaf(ck[4 * j + 1], half, bf_hi(ra));
          h[j & 1][2] = fmaf(ck[4 * j + 2], half, bf_lo(rb)); h[j & 1][3] = fmaf(ck[4 * j + 3], half, bf_hi(rb));
#pragma unroll
          for (int u = 0; u < 4; u++) t[j & 1][u] = tanh_ordered(h[j & 1][u]);
        }
        if (j > 0) {
          const int k = j - 1;
          const float* hh = h[k & 1];
          const float* tt = t[k & 1];
          x[0][k] = hfma2(sg[0][k], pack_bf16(fmaf(hh[0], tt[0], hh[0]), fmaf(hh[1], tt[1], hh[1])), x[0][k]);
          x[1][k] = hfma2(sg[1][k], pack_bf16(fmaf(hh[2], tt[2], hh[2]), fmaf(hh[3], tt[3], hh[3])), x[1][k]);
          if ((k & 3) == 3) {
            *(uint4*)(o + (k >> 2) * 32) = make_uint4(x[0][k - 3], x[0][k - 2], x[0][k - 1], x[0][k]);
            *(uint4*)(o + 8 * D_ + (k >> 2) * 32) = make_uint4(x[1][k - 3], x[1][k - 2], x[1][k - 1], x[1][k]);
          }
        }
      }
      *(uint32_t*)(out + go8) = x[0][8];
      *(uint32_t*)(out + go8 + 8 * D_) = x[1][8];
      if (leader) PROF(11 + 7 * wg);
      if (tid == 128) PROFC(51);
    }
  }
}

typedef CUresult (*EncodeFn)(CUtensorMap*, CUtensorMapDataType, cuuint32_t, void*, const cuuint64_t*, const cuuint64_t*, const cuuint32_t*,
                             const cuuint32_t*, CUtensorMapInterleave, CUtensorMapSwizzle, CUtensorMapL2promotion, CUtensorMapFloatOOBfill);

uint32_t role_of_pair(int t) {
  int grp, i;
  if (t < 32) { const int j = t & 7; i = t >> 3; grp = j < 6 ? 1 + j : 12 + 2 * (j - 6); }
  else if (t < 60) { const int j = (t - 32) % 7; i = (t - 32) / 7; grp = j < 5 ? 7 + j : 13 + 2 * (j - 5); }
  else if (t < 62) return 2u | (uint32_t)(14 + 3 * (t - 60)) << 8 | 2u << 16;
  else { grp = 0; i = t - 62; }
  if (grp < 12) return (uint32_t)(i << 2 | grp << 4 | grp << 8 | i << 16);
  const int u = (grp & 1) * 4 + i;
  return (uint32_t)(1 | i << 2 | grp << 4 | (12 + 3 * ((grp - 12) >> 1) + u / 3) << 8 | (u % 3) << 16);
}

}

extern "C" void kernel_launch(void* const* d_in, const int* in_sizes, int n_in, void* d_out, int out_size) {
  (void)in_sizes; (void)n_in; (void)out_size;
  EncodeFn enc = nullptr;
  cudaDriverEntryPointQueryResult qr;
  cudaGetDriverEntryPoint("cuTensorMapEncodeTiled", (void**)&enc, cudaEnableDefault, &qr);
  Scratch* gs = nullptr;
  cudaGetSymbolAddress((void**)&gs, g_scratch);
  void *zp = gs->z, *hp = gs->h, *kvp = gs->kv;
  CUtensorMap tmW1, tmW2, tmZ, tmH, tmK, tmV, tmKV;
  for (int w = 0; w < 2; w++) {
    cuuint64_t gd[2] = {D_, S_};
    cuuint64_t st[1] = {D_ * 2};
    cuuint32_t bx[2] = {64, w ? 33u : 36u};
    cuuint32_t es[2] = {1, 1};
    enc(w ? &tmV : &tmK, CU_TENSOR_MAP_DATA_TYPE_BFLOAT16, 2, d_in[1 + w], gd, st, bx, es, CU_TENSOR_MAP_INTERLEAVE_NONE, CU_TENSOR_MAP_SWIZZLE_NONE,
        CU_TENSOR_MAP_L2_PROMOTION_L2_128B, CU_TENSOR_MAP_FLOAT_OOB_FILL_NONE);
  }
  {
    cuuint64_t gd[4] = {40, D_ / 2, 2, 64};
    cuuint64_t st[3] = {2 * KVT, KVT, 160};
    cuuint32_t bx[4] = {44, KVROWS, 1, 1};
    cuuint32_t es[4] = {1, 1, 1, 1};
    enc(&tmKV, CU_TENSOR_MAP_DATA_TYPE_UINT32, 4, kvp, gd, st, bx, es, CU_TENSOR_MAP_INTERLEAVE_NONE, CU_TENSOR_MAP_SWIZZLE_NONE,
        CU_TENSOR_MAP_L2_PROMOTION_NONE, CU_TENSOR_MAP_FLOAT_OOB_FILL_NONE);
  }
  {
    cuuint64_t gd[3] = {64, 32 * 72, 8};
    cuuint64_t st[2] = {1024, 128};
    cuuint32_t bx[3] = {64, 72, 1};
    cuuint32_t es[3] = {1, 1, 1};
    enc(&tmH, CU_TENSOR_MAP_DATA_TYPE_BFLOAT16, 3, hp, gd, st, bx, es, CU_TENSOR_MAP_INTERLEAVE_NONE, CU_TENSOR_MAP_SWIZZLE_128B,
        CU_TENSOR_MAP_L2_PROMOTION_NONE, CU_TENSOR_MAP_FLOAT_OOB_FILL_NONE);
  }
  for (int w = 0; w < 2; w++) {
    const cuuint64_t M = w ? S_ : F_, K = w ? F_ : S_;
    cuuint64_t gd[3] = {64, K, M / 64};
    cuuint64_t st[2] = {M * 2, 128};
    cuuint32_t bx[3] = {64, 64, 2};
    cuuint32_t es[3] = {1, 1, 1};
    enc(w ? &tmW2 : &tmW1, CU_TENSOR_MAP_DATA_TYPE_BFLOAT16, 3, d_in[w ? 9 : 7], gd, st, bx, es, CU_TENSOR_MAP_INTERLEAVE_NONE,
        CU_TENSOR_MAP_SWIZZLE_128B, CU_TENSOR_MAP_L2_PROMOTION_L2_256B, CU_TENSOR_MAP_FLOAT_OOB_FILL_NONE);
  }
  {
    cuuint64_t gd[2] = {S_, D_};
    cuuint64_t st[1] = {S_ * 2};
    cuuint32_t bx[2] = {64, 72};
    cuuint32_t es[2] = {1, 1};
    enc(&tmZ, CU_TENSOR_MAP_DATA_TYPE_BFLOAT16, 2, zp, gd, st, bx, es, CU_TENSOR_MAP_INTERLEAVE_NONE, CU_TENSOR_MAP_SWIZZLE_128B,
        CU_TENSOR_MAP_L2_PROMOTION_L2_256B, CU_TENSOR_MAP_FLOAT_OOB_FILL_NONE);
  }
  RoleMap roles;
  int dev = 0, sms = 0;
  cudaGetDevice(&dev);
  cudaDeviceGetAttribute(&sms, cudaDevAttrMultiProcessorCount, dev);
  roles.by_sm = sms == NCTA;
  for (int k = 0; k < NCTA / 2; k++) roles.role[k] = role_of_pair(k);
  cudaFuncSetAttribute(fused_kernel, cudaFuncAttributeMaxDynamicSharedMemorySize, SMEM_BYTES);
  fused_kernel<<<NCTA, 384, SMEM_BYTES>>>((const __nv_bfloat16*)d_in[0], gs, (const __nv_bfloat16*)d_in[8], (const __nv_bfloat16*)d_in[3],
                                          (const __nv_bfloat16*)d_in[4], (const __nv_bfloat16*)d_in[5], tmW1, tmW2, tmZ, tmH, tmK, tmV, tmKV,
                                          roles, (const __nv_bfloat16*)d_in[10], (__nv_bfloat16*)d_out);
}
```

```cpp
#include <cuda_runtime.h>
#include <cuda_bf16.h>
#include <cuda.h>
#include <stdint.h>

namespace {

constexpr int S_ = 2048, D_ = 576, F_ = 4608;
constexpr int NCTA = 132, NG2 = 128, NCONV = 6;
constexpr int ST = 5, ASZ = 16384, PITCH_S = ASZ + 144 * 128, PITCH_B = ASZ + 192 * 128;
constexpr int KVIN = (36 + 33) * 128, KVW = 2 * KVIN + 64 * 176;
constexpr int BAR_OFF = ST * PITCH_S + 2 * KVW;
constexpr int SMEM_BYTES = BAR_OFF + 512;
constexpr int KVROWS = 16, LNROT = 120;
constexpr int SKEW = 1;
constexpr int LEAD_S = 3, LEAD_B = 2;
constexpr int CTURN = 14, CPER = 4, CEARLY = 0, CFENCE = 8;
constexpr int TURN = 4, KPRE = 2;
constexpr int XAT = 12;
constexpr int LAG = 4;
constexpr int CBUF = 14464, CH_OFF = 128, CT_OFF = 4224, KVT = 10240;
constexpr int CSTG_OFF = ST * PITCH_S + 3 * CBUF;
constexpr uint32_t SPIN_LIMIT = 1u << 22;

constexpr int FL_H = 0, FL_U = 3, FL_KV = 9, FL_Z = 12, FL_GATE = 13, FL_DONE = 14, FL_N = 15;
struct Scratch {
  uint32_t flags[64 * 32];
  uint4 stats[S_];
  uint8_t h[32 * 72 * 1024];
  uint8_t u[72 * D_ * 128];
  uint8_t kv[D_ * KVT];
  __nv_bfloat16 z[D_ * S_];
};
__device__ __align__(1024) Scratch g_scratch;
extern __shared__ __align__(1024) uint8_t smem_raw[];
#define TUNABLES(X) X(W9, 1200) X(QLATE, 40) X(QDELAY, 400) X(QRAMP, 5) X(A0, 1200) X(AD, 300) X(AN, 2) X(AL, 1500) X(H0, 3100) X(HD, 400) X(KVGAP, 100) X(HS2, 8) X(HW, 4200) X(LK1, 7) X(LK2, 14) X(KVGO, 6) X(CVGO, 31) X(GDELAY, 608) X(GDELAY1, 256) X(ZDELAY, 3000) X(ZRAMP, 40) X(NPF, 0) X(PFGAP, 600)
#define X(k, v) constexpr int T_##k = v;
TUNABLES(X)
#undef X
#define TN(k) T_##k
struct RoleMap { uint32_t role[NCTA / 2]; uint32_t by_sm; };
#define PROF(i) do {} while (0)
#define PROFG(i) do {} while (0)
#define PROFC(i) do {} while (0)

template<int TB> __device__ __forceinline__ void wgmma_ss(float (&d)[96], uint32_t da, uint32_t db, int sd) {
  asm volatile("{\n.reg .pred p;\n.reg .b64 a, b;\nsetp.ne.b32 p, %98, 0;\nmov.b64 a, {%96, %100};\nmov.b64 b, {%97, %101};\n"
    "wgmma.mma_async.sync.aligned.m64n192k16.f32.bf16.bf16 {%0, %1, %2, %3, %4, %5, %6, %7, %8, %9, %10, %11, %12, %13, %14, %15, %16, %17, %18, %19, %20, %21, %22, %23, %24, %25, %26, %27, %28, %29, %30, %31, %32, %33, %34, %35, %36, %37, %38, %39, %40, %41, %42, %43, %44, %45, %46, %47, %48, %49, %50, %51, %52, %53, %54, %55, %56, %57, %58, %59, %60, %61, %62, %63, %64, %65, %66, %67, %68, %69, %70, %71, %72, %73, %74, %75, %76, %77, %78, %79, %80, %81, %82, %83, %84, %85, %86, %87, %88, %89, %90, %91, %92, %93, %94, %95}, a, b, p, 1, 1, 1, %99;\n}\n"
    : "+f"(d[0]), "+f"(d[1]), "+f"(d[2]), "+f"(d[3]), "+f"(d[4]), "+f"(d[5]), "+f"(d[6]), "+f"(d[7]), "+f"(d[8]), "+f"(d[9]), "+f"(d[10]), "+f"(d[11]), "+f"(d[12]), "+f"(d[13]), "+f"(d[14]), "+f"(d[15]), "+f"(d[16]), "+f"(d[17]), "+f"(d[18]), "+f"(d[19]), "+f"(d[20]), "+f"(d[21]), "+f"(d[22]), "+f"(d[23]), "+f"(d[24]), "+f"(d[25]), "+f"(d[26]), "+f"(d[27]), "+f"(d[28]), "+f"(d[29]), "+f"(d[30]), "+f"(d[31]), "+f"(d[32]), "+f"(d[33]), "+f"(d[34]), "+f"(d[35]), "+f"(d[36]), "+f"(d[37]), "+f"(d[38]), "+f"(d[39]), "+f"(d[40]), "+f"(d[41]), "+f"(d[42]), "+f"(d[43]), "+f"(d[44]), "+f"(d[45]), "+f"(d[46]), "+f"(d[47]), "+f"(d[48]), "+f"(d[49]), "+f"(d[50]), "+f"(d[51]), "+f"(d[52]), "+f"(d[53]), "+f"(d[54]), "+f"(d[55]), "+f"(d[56]), "+f"(d[57]), "+f"(d[58]), "+f"(d[59]), "+f"(d[60]), "+f"(d[61]), "+f"(d[62]), "+f"(d[63]), "+f"(d[64]), "+f"(d[65]), "+f"(d[66]), "+f"(d[67]), "+f"(d[68]), "+f"(d[69]), "+f"(d[70]), "+f"(d[71]), "+f"(d[72]), "+f"(d[73]), "+f"(d[74]), "+f"(d[75]), "+f"(d[76]), "+f"(d[77]), "+f"(d[78]), "+f"(d[79]), "+f"(d[80]), "+f"(d[81]), "+f"(d[82]), "+f"(d[83]), "+f"(d[84]), "+f"(d[85]), "+f"(d[86]), "+f"(d[87]), "+f"(d[88]), "+f"(d[89]), "+f"(d[90]), "+f"(d[91]), "+f"(d[92]), "+f"(d[93]), "+f"(d[94]), "+f"(d[95])
    : "r"(da), "r"(db), "r"(sd), "n"(TB), "r"(0x40000040u), "r"(TB ? 0x40u : 0x40000040u));
}
template<int TB> __device__ __forceinline__ void wgmma_ss(float (&d)[72], uint32_t da, uint32_t db, int sd) {
  asm volatile("{\n.reg .pred p;\n.reg .b64 a, b;\nsetp.ne.b32 p, %74, 0;\nmov.b64 a, {%72, %76};\nmov.b64 b, {%73, %77};\n"
    "wgmma.mma_async.sync.aligned.m64n144k16.f32.bf16.bf16 {%0, %1, %2, %3, %4, %5, %6, %7, %8, %9, %10, %11, %12, %13, %14, %15, %16, %17, %18, %19, %20, %21, %22, %23, %24, %25, %26, %27, %28, %29, %30, %31, %32, %33, %34, %35, %36, %37, %38, %39, %40, %41, %42, %43, %44, %45, %46, %47, %48, %49, %50, %51, %52, %53, %54, %55, %56, %57, %58, %59, %60, %61, %62, %63, %64, %65, %66, %67, %68, %69, %70, %71}, a, b, p, 1, 1, 1, %75;\n}\n"
    : "+f"(d[0]), "+f"(d[1]), "+f"(d[2]), "+f"(d[3]), "+f"(d[4]), "+f"(d[5]), "+f"(d[6]), "+f"(d[7]), "+f"(d[8]), "+f"(d[9]), "+f"(d[10]), "+f"(d[11]), "+f"(d[12]), "+f"(d[13]), "+f"(d[14]), "+f"(d[15]), "+f"(d[16]), "+f"(d[17]), "+f"(d[18]), "+f"(d[19]), "+f"(d[20]), "+f"(d[21]), "+f"(d[22]), "+f"(d[23]), "+f"(d[24]), "+f"(d[25]), "+f"(d[26]), "+f"(d[27]), "+f"(d[28]), "+f"(d[29]), "+f"(d[30]), "+f"(d[31]), "+f"(d[32]), "+f"(d[33]), "+f"(d[34]), "+f"(d[35]), "+f"(d[36]), "+f"(d[37]), "+f"(d[38]), "+f"(d[39]), "+f"(d[40]), "+f"(d[41]), "+f"(d[42]), "+f"(d[43]), "+f"(d[44]), "+f"(d[45]), "+f"(d[46]), "+f"(d[47]), "+f"(d[48]), "+f"(d[49]), "+f"(d[50]), "+f"(d[51]), "+f"(d[52]), "+f"(d[53]), "+f"(d[54]), "+f"(d[55]), "+f"(d[56]), "+f"(d[57]), "+f"(d[58]), "+f"(d[59]), "+f"(d[60]), "+f"(d[61]), "+f"(d[62]), "+f"(d[63]), "+f"(d[64]), "+f"(d[65]), "+f"(d[66]), "+f"(d[67]), "+f"(d[68]), "+f"(d[69]), "+f"(d[70]), "+f"(d[71])
    : "r"(da), "r"(db), "r"(sd), "n"(TB), "r"(0x40000040u), "r"(TB ? 0x40u : 0x40000040u));
}
template<int TB> __device__ __forceinline__ void wgmma_ss(float (&d)[36], uint32_t da, uint32_t db, int sd) {
  asm volatile("{\n.reg .pred p;\n.reg .b64 a, b;\nsetp.ne.b32 p, %38, 0;\nmov.b64 a, {%36, %40};\nmov.b64 b, {%37, %41};\n"
    "wgmma.mma_async.sync.aligned.m64n72k16.f32.bf16.bf16 {%0, %1, %2, %3, %4, %5, %6, %7, %8, %9, %10, %11, %12, %13, %14, %15, %16, %17, %18, %19, %20, %21, %22, %23, %24, %25, %26, %27, %28, %29, %30, %31, %32, %33, %34, %35}, a, b, p, 1, 1, 1, %39;\n}\n"
    : "+f"(d[0]), "+f"(d[1]), "+f"(d[2]), "+f"(d[3]), "+f"(d[4]), "+f"(d[5]), "+f"(d[6]), "+f"(d[7]), "+f"(d[8]), "+f"(d[9]), "+f"(d[10]), "+f"(d[11]), "+f"(d[12]), "+f"(d[13]), "+f"(d[14]), "+f"(d[15]), "+f"(d[16]), "+f"(d[17]), "+f"(d[18]), "+f"(d[19]), "+f"(d[20]), "+f"(d[21]), "+f"(d[22]), "+f"(d[23]), "+f"(d[24]), "+f"(d[25]), "+f"(d[26]), "+f"(d[27]), "+f"(d[28]), "+f"(d[29]), "+f"(d[30]), "+f"(d[31]), "+f"(d[32]), "+f"(d[33]), "+f"(d[34]), "+f"(d[35])
    : "r"(da), "r"(db), "r"(sd), "n"(TB), "r"(0x40000040u), "r"(TB ? 0x40u : 0x40000040u));
}
__device__ __forceinline__ void wgmma_rs_n32(float (&d)[16], uint32_t a0, uint32_t a1, uint32_t a2, uint32_t a3, uint64_t db, int sd) {
  asm volatile("{\n.reg .pred p;\nsetp.ne.b32 p, %21, 0;\n"
    "wgmma.mma_async.sync.aligned.m64n32k16.f32.bf16.bf16 {%0, %1, %2, %3, %4, %5, %6, %7, %8, %9, %10, %11, %12, %13, %14, %15}, {%16, %17, %18, %19}, %20, p, 1, 1, 0;\n}\n"
    : "+f"(d[0]), "+f"(d[1]), "+f"(d[2]), "+f"(d[3]), "+f"(d[4]), "+f"(d[5]), "+f"(d[6]), "+f"(d[7]), "+f"(d[8]), "+f"(d[9]), "+f"(d[10]), "+f"(d[11]), "+f"(d[12]), "+f"(d[13]), "+f"(d[14]), "+f"(d[15])
    : "r"(a0), "r"(a1), "r"(a2), "r"(a3), "l"(db), "r"(sd));
}

__device__ __forceinline__ void wg_fence() { asm volatile("wgmma.fence.sync.aligned;" ::: "memory"); }
__device__ __forceinline__ void wg_commit() { asm volatile("wgmma.commit_group.sync.aligned;" ::: "memory"); }
template <int n> __device__ __forceinline__ void wg_wait() { asm volatile("wgmma.wait_group.sync.aligned %0;" ::"n"(n) : "memory"); }
__device__ __forceinline__ uint64_t mkdesc(uint32_t addr, uint32_t lbo, uint32_t sbo, uint32_t sw) {
  return (uint64_t)((addr & 0x3FFFF) >> 4) | ((uint64_t)(lbo >> 4) << 16) | ((uint64_t)(sbo >> 4) << 32) | ((uint64_t)sw << 62);
}
__device__ __forceinline__ void mbar_init(uint32_t a, int c) { asm volatile("mbarrier.init.shared::cta.b64 [%0], %1;" ::"r"(a), "r"(c)); }
__device__ __forceinline__ void mbar_expect(uint32_t a, uint32_t b) { asm volatile("mbarrier.arrive.expect_tx.shared::cta.b64 _, [%0], %1;" ::"r"(a), "r"(b) : "memory"); }
__device__ __forceinline__ void mbar_arrive(uint32_t a) { asm volatile("mbarrier.arrive.shared::cta.b64 _, [%0];" ::"r"(a) : "memory"); }
__device__ __forceinline__ void mbar_arrive_cluster(uint32_t raddr) { asm volatile("mbarrier.arrive.shared::cluster.b64 _, [%0];" ::"r"(raddr) : "memory"); }
__device__ __forceinline__ uint32_t mapa(uint32_t a, uint32_t cta) { uint32_t r; asm("mapa.shared::cluster.u32 %0, %1, %2;" : "=r"(r) : "r"(a), "r"(cta)); return r; }
__device__ __forceinline__ void mbar_wait(uint32_t a, uint32_t ph) {
  asm volatile(
      "{\n.reg .pred p;\n.reg .u32 c;\nmov.u32 c, 0;\n"
      "WAIT_LOOP:\nmbarrier.try_wait.parity.shared::cta.b64 p, [%0], %1;\n@p bra WAIT_DONE;\n"
      "add.u32 c, c, 1;\nsetp.lt.u32 p, c, %2;\n@p bra WAIT_LOOP;\ntrap;\nWAIT_DONE:\n}" ::"r"(a), "r"(ph), "n"(SPIN_LIMIT) : "memory");
}
__device__ __forceinline__ void mbar_wait_u(uint32_t a, uint32_t ph) {
  asm volatile("{\n.reg .pred p;\nWAIT_LOOP:\nmbarrier.try_wait.parity.shared::cta.b64 p, [%0], %1;\n@!p bra WAIT_LOOP;\n}" ::"r"(a), "r"(ph) : "memory");
}
__device__ __forceinline__ uint32_t desc_lo(uint32_t addr, uint32_t lbo) { return ((addr & 0x3FFFF) >> 4) | ((lbo >> 4) << 16); }
__device__ __forceinline__ void tma2d(uint32_t dst, const CUtensorMap* m, int c0, int c1, uint32_t bar) {
  asm volatile("cp.async.bulk.tensor.2d.shared::cluster.global.mbarrier::complete_tx::bytes [%0], [%1, {%3, %4}], [%2];" ::"r"(dst), "l"(m), "r"(bar), "r"(c0), "r"(c1) : "memory");
}
__device__ __forceinline__ void bulk_g2s(uint32_t dst, const void* src, uint32_t sz, uint32_t bar) {
  asm volatile("cp.async.bulk.shared::cluster.global.mbarrier::complete_tx::bytes [%0], [%1], %2, [%3];" ::"r"(dst), "l"(src), "r"(sz), "r"(bar) : "memory");
}
__device__ __forceinline__ void bulk_s2g(void* dst, uint32_t src, uint32_t sz) {
  asm volatile("cp.async.bulk.global.shared::cta.bulk_group [%0], [%1], %2;" ::"l"(dst), "r"(src), "r"(sz) : "memory");
}
__device__ __forceinline__ uint64_t stream_policy() {
  uint64_t p;
  asm volatile("createpolicy.fractional.L2::evict_first.b64 %0, 1.0;" : "=l"(p));
  return p;
}
__device__ __forceinline__ void tma_weights(uint32_t dst, const CUtensorMap* m, int k0, int mchunk, uint32_t bar, uint64_t pol) {
  asm volatile("cp.async.bulk.tensor.3d.shared::cluster.global.mbarrier::complete_tx::bytes.L2::cache_hint [%0], [%1, {%6, %3, %4}], [%2], %5;"
               ::"r"(dst), "l"(m), "r"(bar), "r"(k0), "r"(mchunk), "l"(pol), "r"(0) : "memory");
}
__device__ __forceinline__ void tma_weights_prefetch(const CUtensorMap* m, int k0, int mchunk, uint64_t pol) {
  asm volatile("cp.async.bulk.prefetch.tensor.3d.L2.global.L2::cache_hint [%0, {%4, %1, %2}], %3;" ::"l"(m), "r"(k0), "r"(mchunk), "l"(pol), "r"(0) : "memory");
}
__device__ __forceinline__ bool elect_one() {
  uint32_t p;
  asm volatile("{\n.reg .pred P;\nelect.sync _|P, 0xffffffff;\nselp.u32 %0, 1, 0, P;\n}" : "=r"(p));
  return p;
}
__device__ __forceinline__ void bulk_g2s_stream(uint32_t dst, const void* src, uint32_t sz, uint32_t bar, uint64_t pol) {
  asm volatile("cp.async.bulk.shared::cluster.global.mbarrier::complete_tx::bytes.L2::cache_hint [%0], [%1], %2, [%3], %4;"
               ::"r"(dst), "l"(src), "r"(sz), "r"(bar), "l"(pol) : "memory");
}
__device__ __forceinline__ void tma3d_store(const CUtensorMap* m, int c1, int c2, uint32_t src) {
  asm volatile("cp.async.bulk.tensor.3d.global.shared::cta.bulk_group [%0, {%4, %2, %3}], [%1];" ::"l"(m), "r"(src), "r"(c1), "r"(c2), "r"(0) : "memory");
}
__device__ __forceinline__ void tma2d_stream(uint32_t dst, const CUtensorMap* m, int c0, int c1, uint32_t bar, uint64_t pol) {
  asm volatile("cp.async.bulk.tensor.2d.shared::cluster.global.mbarrier::complete_tx::bytes.L2::cache_hint [%0], [%1, {%3, %4}], [%2], %5;"
               ::"r"(dst), "l"(m), "r"(bar), "r"(c0), "r"(c1), "l"(pol) : "memory");
}
__device__ __forceinline__ void tma4d_store(const CUtensorMap* m, int c1, int c2, int c3, uint32_t src) {
  asm volatile("cp.async.bulk.tensor.4d.global.shared::cta.bulk_group [%0, {%5, %2, %3, %4}], [%1];" ::"l"(m), "r"(src), "r"(c1), "r"(c2), "r"(c3), "r"(0) : "memory");
}
__device__ __forceinline__ void bulk_commit() { asm volatile("cp.async.bulk.commit_group;" ::: "memory"); }
__device__ __forceinline__ void bulk_wait_all() { asm volatile("cp.async.bulk.wait_group 0;" ::: "memory"); }
__device__ __forceinline__ void fence_async_smem() { asm volatile("fence.proxy.async.shared::cta;" ::: "memory"); }
__device__ __forceinline__ void fence_async_global() { asm volatile("fence.proxy.async.global;" ::: "memory"); }
__device__ __forceinline__ void named_bar(int id, int n) { asm volatile("bar.sync %0, %1;" ::"r"(id), "r"(n) : "memory"); }
__device__ __forceinline__ void named_arrive(int id, int n) { asm volatile("bar.arrive %0, %1;" ::"r"(id), "r"(n) : "memory"); }
__device__ __forceinline__ void flag_add(uint32_t* f, int i, uint32_t v) { asm volatile("red.relaxed.gpu.global.add.u32 [%0], %1;" ::"l"(f + i * 32), "r"(v) : "memory"); }
__device__ __forceinline__ uint32_t flag_ld(uint32_t* f, int i) { uint32_t v; asm volatile("ld.relaxed.gpu.global.u32 %0, [%1];" : "=r"(v) : "l"(f + i * 32) : "memory"); return v; }
__device__ __forceinline__ void prefetch_map(const CUtensorMap* m) { asm volatile("prefetch.tensormap [%0];" ::"l"(m) : "memory"); }
__device__ __forceinline__ void stsm4_t(uint32_t a, uint32_t r0, uint32_t r1, uint32_t r2, uint32_t r3) {
  asm volatile("stmatrix.sync.aligned.m8n8.x4.trans.shared.b16 [%0], {%1, %2, %3, %4};" ::"r"(a), "r"(r0), "r"(r1), "r"(r2), "r"(r3) : "memory");
}
__device__ __forceinline__ uint32_t lds32(uint32_t a) { uint32_t v; asm volatile("ld.shared.u32 %0, [%1];" : "=r"(v) : "r"(a) : "memory"); return v; }
__device__ __forceinline__ void sts32(uint32_t a, uint32_t v) { asm volatile("st.shared.u32 [%0], %1;" ::"r"(a), "r"(v) : "memory"); }
__device__ __forceinline__ uint4 ld_l2(const uint4* p) { uint4 v; asm volatile("ld.relaxed.gpu.global.v4.u32 {%0, %1, %2, %3}, [%4];" : "=r"(v.x), "=r"(v.y), "=r"(v.z), "=r"(v.w) : "l"(p) : "memory"); return v; }
__device__ __forceinline__ void sts128(uint32_t a, uint32_t x, uint32_t y, uint32_t z, uint32_t w) { asm volatile("st.shared.v4.u32 [%0], {%1, %2, %3, %4};" ::"r"(a), "r"(x), "r"(y), "r"(z), "r"(w) : "memory"); }
__device__ __forceinline__ uint4 lds128(uint32_t a) { uint4 v; asm volatile("ld.shared.v4.u32 {%0, %1, %2, %3}, [%4];" : "=r"(v.x), "=r"(v.y), "=r"(v.z), "=r"(v.w) : "r"(a) : "memory"); return v; }
__device__ __forceinline__ void st_async4(uint32_t raddr, uint32_t a, uint32_t b, uint32_t c, uint32_t d, uint32_t rbar) {
  asm volatile("st.async.weak.shared::cluster.mbarrier::complete_tx::bytes.v4.b32 [%0], {%1, %2, %3, %4}, [%5];" ::"r"(raddr), "r"(a), "r"(b), "r"(c), "r"(d), "r"(rbar) : "memory");
}
__device__ __forceinline__ uint32_t pack_bf16(float lo, float hi) { uint32_t r; asm("cvt.rn.bf16x2.f32 %0, %1, %2;" : "=r"(r) : "f"(hi), "f"(lo)); return r; }
__device__ __forceinline__ float bf_lo(uint32_t v) { return __uint_as_float(v << 16); }
__device__ __forceinline__ float bf_hi(uint32_t v) { return __uint_as_float(v & 0xffff0000u); }
__device__ __forceinline__ float bf_round(float x) { return bf_lo(pack_bf16(x, 0.f)); }
__device__ __forceinline__ uint32_t hmul2(uint32_t a, uint32_t b) { uint32_t r; asm("mul.rn.bf16x2 %0, %1, %2;" : "=r"(r) : "r"(a), "r"(b)); return r; }
__device__ __forceinline__ uint32_t hsub2(uint32_t a, uint32_t b) { uint32_t r; asm("sub.rn.bf16x2 %0, %1, %2;" : "=r"(r) : "r"(a), "r"(b)); return r; }
__device__ __forceinline__ uint32_t hfma2(uint32_t a, uint32_t b, uint32_t c) { uint32_t r; asm("fma.rn.bf16x2 %0, %1, %2, %3;" : "=r"(r) : "r"(a), "r"(b), "r"(c)); return r; }
__device__ __forceinline__ uint4 ldg128(const void* p) { uint4 v; asm volatile("ld.global.nc.v4.u32 {%0, %1, %2, %3}, [%4];" : "=r"(v.x), "=r"(v.y), "=r"(v.z), "=r"(v.w) : "l"(p)); return v; }
__device__ __forceinline__ uint32_t ldg16(const void* p) { uint32_t v; asm volatile("ld.global.nc.u16 %0, [%1];" : "=r"(v) : "l"(p)); return v; }
__device__ __forceinline__ float tanh_ordered(float x) { float y; asm volatile("tanh.approx.f32 %0, %1;" : "=f"(y) : "f"(x)); return y; }
__device__ __forceinline__ void mma16816(float (&d)[4], uint32_t a0, uint32_t a1, uint32_t a2, uint32_t a3, uint32_t b0, uint32_t b1) {
  asm("mma.sync.aligned.m16n8k16.row.col.f32.bf16.bf16.f32 {%0, %1, %2, %3}, {%4, %5, %6, %7}, {%8, %9}, {%0, %1, %2, %3};"
      : "+f"(d[0]), "+f"(d[1]), "+f"(d[2]), "+f"(d[3]) : "r"(a0), "r"(a1), "r"(a2), "r"(a3), "r"(b0), "r"(b1));
}
__device__ __forceinline__ uint32_t hadd2(uint32_t a, uint32_t b) { uint32_t r; asm("add.rn.bf16x2 %0, %1, %2;" : "=r"(r) : "r"(a), "r"(b)); return r; }
__device__ __forceinline__ uint32_t ldg32(const void* p) { uint32_t v; asm volatile("ld.global.nc.L1::no_allocate.u32 %0, [%1];" : "=r"(v) : "l"(p)); return v; }
__device__ __forceinline__ uint2 lds64(uint32_t a) { uint2 v; asm volatile("ld.shared.v2.u32 {%0, %1}, [%2];" : "=r"(v.x), "=r"(v.y) : "r"(a) : "memory"); return v; }
__device__ __forceinline__ uint32_t lds32_if(uint32_t a, uint32_t on) {
  uint32_t v;
  asm volatile("{\n.reg .pred p;\nsetp.ne.u32 p, %2, 0;\n@p ld.shared.u32 %0, [%1];\n}" : "=r"(v) : "r"(a), "r"(on) : "memory");
  return v;
}
__device__ __forceinline__ uint32_t clock_now() { uint32_t t; asm volatile("mov.u32 %0, %%clock;" : "=r"(t)); return t; }
__device__ __forceinline__ uint32_t time_now() { uint32_t t; asm volatile("mov.u32 %0, %%globaltimer_lo;" : "=r"(t)); return t; }
__device__ __forceinline__ void spin_until(uint32_t t0, uint32_t n) { while (clock_now() - t0 < n) {} }
__device__ __forceinline__ uint2 ldg64_if(const void* p, uint32_t on) {
  uint2 v;
  asm volatile("{\n.reg .pred p;\nsetp.ne.u32 p, %3, 0;\n@p ld.global.nc.v2.u32 {%0, %1}, [%2];\n}" : "=r"(v.x), "=r"(v.y) : "l"(p), "r"(on));
  return v;
}
template <class T> __device__ __forceinline__ T pin(T v) { asm volatile("" : "+r"(v)); return v; }
__device__ __forceinline__ void st_async2(uint32_t raddr, uint32_t a, uint32_t b, uint32_t rbar) {
  asm volatile("st.async.weak.shared::cluster.mbarrier::complete_tx::bytes.v2.b32 [%0], {%1, %2}, [%3];" ::"r"(raddr), "r"(a), "r"(b), "r"(rbar) : "memory");
}
__device__ __forceinline__ void bulk_prefetch(const void* src, uint32_t sz, uint64_t pol) {
  asm volatile("cp.async.bulk.prefetch.L2.global.L2::cache_hint [%0], %1, %2;" ::"l"(src), "r"(sz), "l"(pol) : "memory");
}
__device__ __forceinline__ void bulk_wait_read() { asm volatile("cp.async.bulk.wait_group.read 0;" ::: "memory"); }
__device__ __forceinline__ uint32_t shfl_ordered(uint32_t v, int src) { uint32_t r; asm volatile("shfl.sync.idx.b32 %0, %1, %2, 0x1f, 0xffffffff;" : "=r"(r) : "r"(v), "r"(src)); return r; }
__device__ __forceinline__ int chan_pos(int d) {
  return d < 512 ? 72 * (d >> 6) + ((d & 33) | ((d & 6) << 2) | ((d >> 2) & 6)) : 72 * ((d - 512) >> 3) + 64 + (d & 7);
}

struct Ring {
  uint32_t s, ph;
  __device__ __forceinline__ void next() { if (++s == ST) { s = 0; ph ^= 1; } }
};
constexpr int B_FULL = 0, B_GO = 40, B_CFULL = 48, B_SEMPTY = 80, B_ZFULL = 96, B_RFULL = 104, B_UDONE = 120, B_KFULL = 136, B_RAW = 168, B_CVGO = 248, B_PEER = 256, B_G2GO = 264, B_KVGO = 280,
              B_EMPTY = 296, B_G1DONE = 336,
              B_CEMPTY = 344, B_SFULL = 376, B_USTG = 392, B_END = 408;

__device__ __forceinline__ void wait_counter(uint32_t* f, int idx, uint32_t want, uint32_t first, uint32_t nap) {
#pragma unroll 1
  for (uint32_t spins = 0; first != want; spins++) {
    if (nap && spins) __nanosleep(nap);
    first = flag_ld(f, idx);
    if (spins > SPIN_LIMIT) asm volatile("trap;");
  }
  fence_async_global();
}

__device__ __forceinline__ void gate_arrive(uint32_t* f, uint32_t back) {
  asm volatile("red.relaxed.gpu.global.max.u32 [%0], %1;" ::"l"(f + FL_GATE * 32 + 1), "r"(time_now() - back) : "memory");
  flag_add(f, FL_GATE, 1);
}

__device__ __forceinline__ float ln_rinv(float var) {
  float rt, rinv;
  asm("sqrt.approx.ftz.f32 %0, %1;" : "=f"(rt) : "f"(bf_round(bf_round(var) + 1e-5f)));
  asm("rcp.approx.ftz.f32 %0, %1;" : "=f"(rinv) : "f"(bf_round(rt)));
  return rinv;
}
__device__ __forceinline__ uint32_t ln_apply(uint32_t x, const uint4& st) {
  const uint32_t d = hsub2(x, st.x);
  return hfma2(d, st.y, hmul2(d, st.z));
}

__device__ __forceinline__ void polling_done(uint32_t* f, int lane) {
  unsigned old = 0;
  if (lane == 0) asm volatile("atom.relaxed.gpu.global.add.u32 %0, [%1], 1;" : "=r"(old) : "l"(f + FL_DONE * 32) : "memory");
  old = __shfl_sync(0xffffffffu, old, 0);
  if (old == NCTA + NG2 - 1) {
    if (lane < FL_N) *(uint2*)(f + lane * 32) = make_uint2(0u, 0u);
  }
}

struct Pipe { Ring r; uint32_t prev; bool pending; int cnt; };
__device__ __forceinline__ void pipe_drain(Pipe& p, uint32_t bars, bool leader) {
  wg_wait<0>();
  if (leader) mbar_arrive(bars + B_EMPTY + p.prev * 8);
  p.pending = false;
}
template <int TB, int LEAD, int R>
__device__ __forceinline__ void gemm_run(float (&acc)[R], int n, int accumulate, Pipe& p, uint32_t sb, uint32_t pitch, int wg, bool leader) {
  const uint32_t bars = sb + BAR_OFF;
  const uint32_t dA0 = desc_lo(sb + wg * 8192, 8192), dB0 = desc_lo(sb + ASZ, TB ? 128 : 16);
  constexpr int KB_STEP = TB ? 16 : 2;
#pragma unroll 1
  for (int kb = 0; kb < n; kb++) {
    if (LEAD && kb == n - LEAD && wg == 1) { if (TB) pipe_drain(p, bars, leader); named_bar(8, 256); }
    mbar_wait(bars + B_FULL + p.r.s * 8, p.r.ph);
    if (kb == 0 && !accumulate && threadIdx.x == 0) { PROF(21 + TB); PROFC(49 - 2 * TB); }
    const uint32_t dA = dA0 + p.r.s * (pitch >> 4), dB = dB0 + p.r.s * (pitch >> 4);
    wg_fence();
    wgmma_ss<TB>(acc, dA, dB, accumulate | kb);
#pragma unroll
    for (int k = 1; k < 4; k++) wgmma_ss<TB>(acc, dA + k * 128, dB + k * KB_STEP, 1);
    wg_commit();
    wg_wait<1>();
    if (p.pending && leader) mbar_arrive(bars + B_EMPTY + p.prev * 8);
    p.pending = true;
    p.prev = p.r.s;
    p.r.next();
  }
  if (LEAD && wg == 0) named_arrive(8, 256);
}

template <int BROW0, int I0, int I1>
__device__ __forceinline__ void gemm2_part(float (&c)[36], uint32_t sb, uint32_t pitch, int wg) {
  const uint32_t dA0 = desc_lo(sb + wg * 8192, 8192), dB0 = desc_lo(sb + ASZ + BROW0 * 128, 16);
  wg_fence();
#pragma unroll
  for (int i = I0; i < I1; i++) {
    const int step = 68 - LAG + (i >> 2);
    if ((i & 3) == 0 && BROW0 == 0) mbar_wait_u(sb + BAR_OFF + B_FULL + (step % ST) * 8, (step / ST) & 1);
    if (i == 4 * LAG - TURN && BROW0 && wg == 0) named_arrive(7, 256);
    wgmma_ss<0>(c, dA0 + (step % ST) * (pitch >> 4) + (i & 3) * 128, dB0 + (step % ST) * (pitch >> 4) + (i & 3) * 2, 1);
  }
  wg_commit();
}
__device__ __forceinline__ void split_acc(const float (&acc)[72], float (&a)[36], float (&b)[36]) {
#pragma unroll
  for (int i = 0; i < 36; i++) { asm volatile("mov.b32 %0, %1;" : "=f"(a[i]) : "f"(acc[i])); asm volatile("mov.b32 %0, %1;" : "=f"(b[i]) : "f"(acc[36 + i])); }
}
template <int NV, int R, class Slice>
__device__ __forceinline__ void gelu_store(const float (&acc)[R], uint32_t bias0, uint32_t bias1, uint32_t sa, Slice slice) {
  const float hbias0 = 0.5f * bf_lo(pin(bias0)), hbias1 = 0.5f * bf_lo(pin(bias1));
  float hx[2][4], t[2][4], half = 0.5f;
  uint32_t pk[4];
#pragma unroll
  for (int j = 0; j <= NV / 4; j++) {
    if (j < NV / 4) {
      if (j >= 2) half = fmaf(t[j & 1][1], 0.f, 0.5f);
#pragma unroll
      for (int u = 0; u < 4; u++) {
        hx[j & 1][u] = fmaf(acc[4 * j + u], half, (u & 2) ? hbias1 : hbias0);
        t[j & 1][u] = tanh_ordered(hx[j & 1][u] * fmaf(hx[j & 1][u] * hx[j & 1][u], 0.2854192651f, 1.5957691216f));
      }
    }
    if (j > 0) {
      const float *hh = hx[(j - 1) & 1], *tt = t[(j - 1) & 1];
      pk[2 * ((j - 1) & 1)] = pack_bf16(fmaf(hh[0], tt[0], hh[0]), fmaf(hh[1], tt[1], hh[1]));
      pk[2 * ((j - 1) & 1) + 1] = pack_bf16(fmaf(hh[2], tt[2], hh[2]), fmaf(hh[3], tt[3], hh[3]));
      if (!(j & 1)) { stsm4_t(sa + (j - 2) * 1024, pk[0], pk[1], pk[2], pk[3]); slice(j / 2 - 1); }
    }
  }
}
struct Role { int half, kind, g2_m, dt, g1_mt, g1_nt, cs; uint32_t pitch; };
__device__ __forceinline__ Role get_role(const RoleMap& roles) {
  uint32_t b, sm;
  asm volatile("mov.u32 %0, %%ctaid.x;" : "=r"(b));
  asm volatile("mov.u32 %0, %%smid;" : "=r"(sm));
  const uint32_t w = roles.role[(roles.by_sm ? sm : b) >> 1];
  const int half = b & 1, kind = w & 3, m = (w >> 4) & 15, dt = (w >> 2) & 3;
  return Role{half, kind, m * 128, dt, half * 18 + (int)((w >> 8) & 31), (int)(w >> 16), (m * 4 + dt) * 2 + half, kind ? (uint32_t)PITCH_B : (uint32_t)PITCH_S};
}
__device__ __forceinline__ int g2_block(int half, int j) { return half * 36 + (j < 12 ? 2 * j : j < 24 ? 2 * j - 23 : j); }
__device__ __forceinline__ int conv_chan(int cs, int i) { return (3 * (cs >> 5) + (i >> 1)) * 64 + ((2 * cs) & 63) + (i & 1); }
__device__ __forceinline__ uint32_t conv_buf(uint32_t sb, int b) { return sb + (b == 3 ? (36 % ST) * PITCH_S : ST * PITCH_S + b * CBUF); }

__global__ void __cluster_dims__(2, 1, 1) __launch_bounds__(384, 1)
fused_kernel(const __nv_bfloat16* __restrict__ q, Scratch* __restrict__ gs, const __nv_bfloat16* __restrict__ b1,
             const __nv_bfloat16* __restrict__ shiftk, const __nv_bfloat16* __restrict__ ssmk, const __nv_bfloat16* __restrict__ ssmD,
             const __grid_constant__ CUtensorMap tmW1, const __grid_constant__ CUtensorMap tmW2, const __grid_constant__ CUtensorMap tmZ,
             const __grid_constant__ CUtensorMap tmH, const __grid_constant__ CUtensorMap tmK, const __grid_constant__ CUtensorMap tmV,
             const __grid_constant__ CUtensorMap tmKV, const __grid_constant__ RoleMap roles, const __nv_bfloat16* __restrict__ b2,
             __nv_bfloat16* __restrict__ out) {
  const int cta = blockIdx.x;
  const int tid = threadIdx.x;
  if (tid == 288) PROFG(0);

  const uint32_t t_start = clock_now();
  if (tid == 256) { prefetch_map(&tmW1); prefetch_map(&tmH); }
  const int lc = (cta + LNROT) & 127;
  const uint32_t do_ln = cta < 128 && tid < 256;
  const int oct = lc + (tid & 128), ln_row = oct * 8 + ((tid >> 4) & 7), l16 = tid & 15;
  uint2 xr[9];
  if (do_ln && oct >= TN(QLATE)) spin_until(t_start, TN(QDELAY) + TN(QRAMP) * oct / 2);
#pragma unroll
  for (int i = 0; i < 9; i++) xr[i] = ldg64_if(q + (size_t)ln_row * D_ + i * 64 + l16 * 4, do_ln);
  if (tid == 0) PROF(32);
  const int warp = __shfl_sync(0xffffffffu, tid >> 5, 0);
  const uint32_t sb = __shfl_sync(0xffffffffu, (uint32_t)__cvta_generic_to_shared(smem_raw), 0);
  const uint32_t bars = sb + BAR_OFF;
  const int lane = tid & 31;
  const int wg = warp >> 2;
  constexpr int LN_OFF = ST * PITCH_B;

  if (warp < 8 || warp == 11) {
    asm volatile("barrier.cluster.arrive.relaxed.aligned;" ::: "memory");
    const int hq = (lane & 16) >> 3, hb = (lane & 16) + hq;
    float da[3][4] = {};
#pragma unroll
    for (int i = 0; i < 9; i++) mma16816(da[i % 3], xr[i].x, 0x3f803f80u, xr[i].y, 0x3f803f80u, xr[i].x, xr[i].y);
    const float r1 = ((da[0][2] + da[0][3]) + (da[1][2] + da[1][3])) + (da[2][2] + da[2][3]);
    const float r2 = (lane & 4) ? (da[0][1] + da[1][1]) + da[2][1] : (da[0][0] + da[1][0]) + da[2][0];
    const float s1 = __shfl_sync(0xffffffffu, r1, hq) + __shfl_sync(0xffffffffu, r1, hq + 1);
    const float s2 = (__shfl_sync(0xffffffffu, r2, hb) + __shfl_sync(0xffffffffu, r2, hb + 4)) + (__shfl_sync(0xffffffffu, r2, hb + 9) + __shfl_sync(0xffffffffu, r2, hb + 13));
    if (tid == 0) { asm volatile("" ::"f"(s2) : "memory"); PROF(27); }
    const float mean = s1 * (1.f / D_), var = fmaxf(fmaf(-mean, mean, s2 * (1.f / D_)), 0.f);
    const float rinv = ln_rinv(var), rinv2 = ln_rinv(var * rinv * rinv), scale = rinv * rinv2, shift = -bf_round((mean - bf_round(mean)) * rinv) * rinv2;
    const uint32_t m2 = pack_bf16(mean, mean), hi2 = pack_bf16(scale, scale), lo2 = pack_bf16(scale - bf_lo(hi2), scale - bf_lo(hi2)), sh2 = pack_bf16(shift, shift);
    const uint32_t hi1 = pack_bf16(rinv, rinv);
    asm volatile("{\n.reg .pred p;\nsetp.eq.u32 p, %5, 0;\n@p st.shared.v4.u32 [%0], {%1, %2, %3, %4};\n}" ::"r"(sb + LN_OFF + 18432 + tid), "r"(m2), "r"(hi1),
                 "r"(pack_bf16(rinv - bf_lo(hi1), rinv - bf_lo(hi1))), "r"(0u), "r"(tid & 0x10f) : "memory");
    const uint32_t g0 = 4 * (l16 >> 3) + 2 * (l16 & 1), hrow = sb + LN_OFF + ((tid >> 7) & 1) * 9216 + (tid & 0x70);
    const uint32_t hs0 = hrow + g0 * 128 + ((l16 >> 1) & 3) * 4, hs8 = ((hrow + (l16 >> 1) * 1152) ^ ((l16 >> 1) << 4)) + 1024 + (l16 & 1) * 8;
    uint32_t w[18];
#pragma unroll
    for (int i = 0; i < 18; i++) {
      const uint32_t d = hsub2((i & 1) ? xr[i >> 1].y : xr[i >> 1].x, m2);
      asm("max.u32 %0, %1, 1;" : "=r"(w[i]) : "r"(hfma2(d, hi2, hfma2(d, lo2, sh2))));
    }
#pragma unroll
    for (int i = 0; i < 16; i++) {
      const int gi = 9 * (i >> 1) + (i & 1);
      asm volatile("{\n.reg .pred p;\nsetp.ne.u32 p, %2, 0;\n@p st.shared.u32 [%0], %1;\n}" ::"r"((hs0 ^ ((g0 * 16 + (gi & 7) * 16) & 0x70)) + gi * 128), "r"(w[i]), "r"(do_ln) : "memory");
    }
    asm volatile("{\n.reg .pred p;\nsetp.ne.u32 p, %3, 0;\n@p st.shared.v2.u32 [%0], {%1, %2};\n}" ::"r"(hs8), "r"(w[16]), "r"(w[17]), "r"(do_ln) : "memory");
    if (tid == 224) PROF(13);
    fence_async_smem();
    if (warp < 8) named_arrive(wg, 160);
  } else if (warp != 8) {
    spin_until(t_start, TN(W9));
  }

  if (wg == 2) {
    asm volatile("setmaxnreg.dec.sync.aligned.u32 56;");
    auto store_h = [&](int w) {
      named_bar(w, 160);
      if (cta < 128 && elect_one()) {
        tma3d_store(&tmH, ((lc >> 3) + 16 * w) * 72, lc & 7, sb + LN_OFF + w * 9216);
        bulk_s2g(gs->stats + (lc + 128 * w) * 8, sb + LN_OFF + 18432 + w * 128, 128);
        bulk_commit();
      }
    };
    auto publish_h = [&](int w) {
      if (cta < 128 && elect_one()) { bulk_wait_all(); flag_add(gs->flags, FL_H + (w ? 2 : lc >> 6), 1); }
      __syncwarp();
    };
    if (warp == 11) {
      if (lc >= 64) spin_until(t_start, TN(HW));
      store_h(0);
      publish_h(0);
      if (lane == 0) PROF(1);
    } else {
      if (elect_one()) {
        if (warp == 8) {
#pragma unroll
          for (int o = 0; o < B_GO; o += 8) mbar_init(bars + o, 1);
        } else if (warp == 9) {
#pragma unroll
          for (int o = B_GO; o < B_RAW + 40; o += 8) mbar_init(bars + o, 1);
        } else {
#pragma unroll
          for (int o = B_RAW + 40; o < B_END; o += 8) mbar_init(bars + o, o < B_EMPTY ? 1 : o < B_CEMPTY ? 2 : 4);
        }
        asm volatile("fence.mbarrier_init.release.cluster;" ::: "memory");
      }
      __syncwarp();
      asm volatile("barrier.cluster.arrive.relaxed.aligned;" ::: "memory");
      if (warp == 9) { prefetch_map(&tmK); prefetch_map(&tmV); prefetch_map(&tmKV); prefetch_map(&tmW2); prefetch_map(&tmZ); }
      if (tid == 256) PROF(35);
    }
    const Role ro = get_role(roles);
    if (warp != 8) asm volatile("barrier.cluster.wait.aligned;" ::: "memory");
    if (warp == 11) {
      Ring r{0, 1};
      uint32_t look = 0;
      const uint32_t bsz = ro.pitch - ASZ;
      const uint8_t* src = gs->h + ro.g1_nt * bsz + ST * 73728;
      named_bar(10, 64);
#pragma unroll 1
      for (int i = ST; i < 32; i++) {
        if (i == ST || i == 8 || i == 16) wait_counter(gs->flags, FL_H + (i >> 3), i == 16 ? 128u : 64u, look, 0);
        if (i == TN(LK1) || i == TN(LK2)) look = flag_ld(gs->flags, FL_H + (i >> 3) + 1);
        mbar_wait(bars + B_EMPTY + r.s * 8, r.ph ^ 1);
        if (elect_one()) bulk_g2s(sb + r.s * ro.pitch + ASZ, src, bsz, bars + B_FULL + r.s * 8);
        if (i == ST && lane == 0) PROF(25);
        if (i == TN(HS2)) store_h(1);
        if (i == TN(HS2) + 2) { publish_h(1); if (lane == 0) mbar_arrive(bars + B_KVGO + 8); }
        if (i == TN(KVGO) && lane == 0) mbar_arrive(bars + B_KVGO);
        if (i == TN(CVGO) && lane == 0) mbar_arrive(bars + B_CVGO);
        src += 73728;
        r.next();
      }
      if (ro.kind != 2) {
        look = 0;
#pragma unroll 1
        for (int j = 0; j < 36; j++) {
          const uint8_t* su = gs->u + ((size_t)g2_block(ro.half, j) * D_ + ro.dt * 144) * 128;
          if (j == 0 || j == 12 || j == 24) wait_counter(gs->flags, FL_U + ro.half * 3 + j / 12, j == 24 ? 36u : 48u, look, 100);
          if (ro.kind ? j == 4 : j < 2) mbar_wait_u(bars + B_UDONE + (j ? 8 : 0), 0);
          mbar_wait(bars + B_EMPTY + r.s * 8, r.ph ^ 1);
          if (elect_one()) {
            bulk_g2s(sb + r.s * ro.pitch + ASZ, su + (ro.half ^ 1) * 9216, 9216, bars + B_FULL + r.s * 8);
            bulk_g2s(sb + r.s * ro.pitch + ASZ + 9216, su + ro.half * 9216, 9216, bars + B_FULL + r.s * 8);
          }
          if (j == 9 || j == 21) look = flag_ld(gs->flags, FL_U + ro.half * 3 + j / 12 + 1);
          if (j == 0 && lane == 0) PROF(8);
          r.next();
        }
#pragma unroll 1
        for (int o = lane; o < ST * 73728 / 16 / NG2; o += 32) ((uint4*)gs->h)[ro.cs * (ST * 73728 / 16 / NG2) + o] = make_uint4(0u, 0u, 0u, 0u);
      }
      polling_done(gs->flags, lane);
    } else if (warp == 8) {
      const uint64_t pol = stream_policy();
      Ring r{0, 0};
#pragma unroll 1
      for (int i = 0; i < 32; i++) {
        if (i < ST) spin_until(t_start, TN(A0) + i * TN(AD) + (i >= TN(AN) ? TN(AL) : 0));
        if (i == ST) {
          asm volatile("barrier.cluster.wait.aligned;" ::: "memory");
          if (roles.by_sm) {
            uint32_t sm;
            asm volatile("mov.u32 %0, %%smid;" : "=r"(sm));
            if (elect_one()) { mbar_expect(bars + B_PEER, 8); st_async2(mapa(bars + B_END, ro.half ^ 1), sm, sm, mapa(bars + B_PEER, ro.half ^ 1)); }
            mbar_wait_u(bars + B_PEER, 0);
            if ((lds32(bars + B_END) ^ sm) != 1 || sm >= NCTA) asm volatile("trap;");
          }
        }
        if (i >= ST) mbar_wait(bars + B_EMPTY + r.s * 8, r.ph ^ 1);
        if (elect_one()) {
          mbar_expect(bars + B_FULL + r.s * 8, ro.pitch);
          tma_weights(sb + r.s * ro.pitch, &tmW1, i * 64, ro.g1_mt * 2, bars + B_FULL + r.s * 8, pol);
        }
        r.next();
      }
      if (ro.kind != 2) {
#pragma unroll 1
        for (int j = 0; j < 36; j++) {
          if (j == 4) {
#pragma unroll 1
            for (int k = 0; k < TN(NPF); k++) {
              spin_until(clock_now(), TN(PFGAP));
              const int jj = 4 + 4 * k + ro.dt;
              if (elect_one() && jj < 36) tma_weights_prefetch(&tmW2, g2_block(ro.half, jj) * 64, ro.g2_m >> 6, pol);
            }
            if (ro.kind == 0) mbar_wait_u(bars + B_CEMPTY + 24, 0);
          }
          mbar_wait(bars + B_EMPTY + r.s * 8, r.ph ^ 1);
          if (elect_one()) {
            mbar_expect(bars + B_FULL + r.s * 8, PITCH_S);
            tma_weights(sb + r.s * ro.pitch, &tmW2, g2_block(ro.half, j) * 64, ro.g2_m >> 6, bars + B_FULL + r.s * 8, pol);
          }
          r.next();
        }
        if (lane < 2) mbar_expect(bars + B_RFULL + lane * 8, 9216);
        __syncwarp();
        mbar_wait(bars + B_EMPTY + r.s * 8, r.ph ^ 1);
        if (lane == 0) mbar_arrive_cluster(mapa(bars + B_GO, ro.half ^ 1));
      }
      if (lane == 0) PROF(28);
    } else {
      const uint64_t pol = stream_policy();
      {
        const uint32_t hb = (ro.pitch - ASZ) >> 1, raw = bars + B_RAW + (warp - 9) * 40, dst = sb + ASZ + (warp - 9) * hb;
        const uint8_t* src = gs->h + (2 * ro.g1_nt + warp - 9) * hb;
        auto fetch_h = [&](int i) { if (elect_one()) { mbar_expect(raw + i * 8, hb); bulk_g2s(dst + i * ro.pitch, src + i * 73728, hb, raw + i * 8); } };
        int next = 0;
#pragma unroll 1
        for (int i = -1; i < ST; i++) {
          if (i >= 0) {
#pragma unroll 1
            for (uint32_t tries = 0;; tries++) {
              mbar_wait_u(raw + i * 8, tries & 1);
              if (lane == 0 && i == 0) PROF(29 + warp);
              const uint32_t pa = dst + i * ro.pitch + lane * 32 + (lane >> 2) * 4;
              uint32_t m = 1;
#pragma unroll
              for (int j = 0; j < 12; j++) m = min(m, lds32(pa + (j < 9 || ro.kind ? j : 0) * 1024));
              if (__all_sync(0xffffffffu, m)) break;
              if (lane == 0) PROF(26);
              fetch_h(i);
            }
            if (elect_one()) asm volatile("mbarrier.complete_tx.relaxed.cta.shared::cta.b64 [%0], %1;" ::"r"(bars + B_FULL + i * 8), "r"(hb) : "memory");
          }
#pragma unroll 1
          for (const int end = min(next + 2, ST); next < end; next++) {
            if (i < 0) spin_until(t_start, TN(H0) + next * TN(HD));
            fetch_h(next);
            if (next == 0 && tid == 288) PROF(3);
          }
          if (i < 0 && warp == 10) named_arrive(10, 64);
        }
      }
      if (ro.kind == 0) {
        mbar_wait_u(bars + B_KVGO + (warp - 9) * 8, 0);
        const int cs = ro.cs, grp = (cs / 3) * 2 + warp - 9, cb0 = (cs % 3) * 3;
        const uint32_t kin_s = sb + ST * PITCH_S + (warp - 9) * KVW, kout = kin_s + 2 * KVIN + lane * 176, fb = bars + B_KFULL + (warp - 9) * 16;
        auto fetch = [&](int i) {
          if (elect_one()) {
            mbar_expect(fb + (i & 1) * 8, KVIN);
            tma2d_stream(kin_s + (i & 1) * KVIN, &tmK, (cb0 + i) * 64, grp * 32 - 4, fb + (i & 1) * 8, pol);
            tma2d_stream(kin_s + (i & 1) * KVIN + 4608, &tmV, (cb0 + i) * 64, grp * 32 - 1, fb + (i & 1) * 8, pol);
          }
        };
        fetch(0);
        uint4 shk = ldg128(shiftk + (cb0 * 64 + lane * 2) * 4);
        const uint32_t dskip = ldg16(ssmD + conv_chan(cs, lane < NCONV ? lane : 0));
#pragma unroll 1
        for (int i = 0; i < 3; i++) {
          const uint32_t w0 = __byte_perm(shk.x, shk.z, 0x5410), w1 = __byte_perm(shk.x, shk.z, 0x7632);
          const uint32_t w2 = __byte_perm(shk.y, shk.w, 0x5410), w3 = __byte_perm(shk.y, shk.w, 0x7632);
          const uint32_t ka = kin_s + (i & 1) * KVIN + lane * 4;
          mbar_wait_u(fb + (i & 1) * 8, i >> 1);
          if (tid == 288 && i < 2) PROF(30 + i);
          if (i < 2) fetch(i + 1);
          shk = ldg128(i < 2 ? shiftk + ((cb0 + i + 1) * 64 + lane * 2) * 4 : ssmk + (size_t)conv_chan(cs, lane < NCONV ? lane : 0) * S_);
          uint32_t kr[20], x[17];
          auto rows = [&](uint32_t from, int j0) {
#pragma unroll
            for (int j = j0; j < j0 + 4; j++) { kr[j] = lds32(from + j * 128); if (j >= 3) x[j - 3] = lds32(from + 4608 + (j - 3) * 128); }
          };
          rows(ka, 0); rows(ka, 4); rows(ka, 8);
          x[0] = hmul2(hfma2(kr[3], w0, hfma2(kr[2], w1, hfma2(kr[1], w2, hmul2(kr[0], w3)))), x[0]);
          if (i) { if (elect_one()) bulk_wait_read(); __syncwarp(); }
#pragma unroll 1
          for (int o = 0; o < 4; o++) {
            const uint32_t from = ka + (o < 3 ? o : 2) * 1024, to = kout + o * 32;
#pragma unroll
            for (int m = 0; m < 8; m += 4) {
#pragma unroll
              for (int j = m + 1; j < m + 5; j++) x[j] = hmul2(hfma2(kr[j + 3], w0, hfma2(kr[j + 2], w1, hfma2(kr[j + 1], w2, hmul2(kr[j], w3)))), x[j]);
#pragma unroll
              for (int c = 0; c < 2; c++) {
                const uint32_t sel = c ? 0x7632 : 0x5410;
                const uint32_t a0 = __byte_perm(x[m + 1], x[m], sel), a1 = __byte_perm(x[m + 2], x[m + 1], sel);
                const uint32_t a2 = __byte_perm(x[m + 3], x[m + 2], sel), a3 = __byte_perm(x[m + 4], x[m + 3], sel);
                sts128(to + c * 5632 + m * 4, a0, a1, a2, a3);
                asm volatile("{\n.reg .pred p;\nsetp.eq.u32 p, %5, 3;\n@p st.shared.v4.u32 [%0], {%1, %2, %3, %4};\n}" ::"r"(to + c * 5632 + m * 4 + 32), "r"(a0), "r"(a1), "r"(a2), "r"(a3), "r"(o) : "memory");
              }
#pragma unroll
              for (int j = m + 12; j < m + 16; j++) { kr[j] = lds32_if(from + j * 128, o < 3); x[j - 3] = lds32_if(from + 4608 + (j - 3) * 128, o < 3); }
            }
#pragma unroll
            for (int j = 1; j < 12; j++) kr[j] = kr[j + 8];
#pragma unroll
            for (int j = 0; j < 9; j++) x[j] = x[j + 8];
          }
          fence_async_smem();
          __syncwarp();
          if (i && elect_one()) { bulk_wait_all(); flag_add(gs->flags, FL_KV + i - 1, 1); }
#pragma unroll 1
          for (int k = 0; k < 64 / KVROWS; k++) {
            if (k) spin_until(clock_now(), TN(KVGAP));
            if (elect_one()) { tma4d_store(&tmKV, (cb0 + i) * 32 + ((k * KVROWS) & 31), (k * KVROWS) >> 5, grp, kin_s + 2 * KVIN + k * KVROWS * 176); bulk_commit(); }
          }
        }
        shk.x = __byte_perm(pack_bf16(bf_lo(shk.x) + bf_lo(dskip), 0.f), shk.x, 0x7610);
        const uint32_t look = flag_ld(gs->flags, FL_KV + warp - 9);
        if (elect_one()) {
          bulk_wait_all();
          flag_add(gs->flags, FL_KV + 2, 1);
          bulk_prefetch(ssmk + (size_t)conv_chan(cs, 2 * (warp - 9)) * S_, 2 * S_ * 2, pol);
          if (warp == 9) PROFG(2);
        }
        __syncwarp();
#pragma unroll 1
        for (int i = warp == 9 ? 0 : 2; i < (warp == 9 ? 2 : NCONV); i++) {
          const int b = i & 3, d = conv_chan(cs, i);
          const uint32_t base = conv_buf(sb, b), cf = bars + B_CFULL + b * 8;
          if (!(i & 1)) wait_counter(gs->flags, FL_KV + (i >> 1), 192u, i < 4 ? look : 0u, 200);
          if (i == 0 || i == 2) mbar_wait_u(bars + B_CVGO, 0);
          if (i == 0 && lane == 0) PROF(23);
          if (i == 3) {
            mbar_wait_u(bars + B_G1DONE, 0);
            if (elect_one()) bulk_prefetch(ssmk + (size_t)conv_chan(cs, 4) * S_, 2 * S_ * 2, pol);
          }
          if (i >= 4) mbar_wait_u(bars + B_CEMPTY + b * 8, 0);
          if (lane == i) sts128(base + CH_OFF, shk.x, shk.y, shk.z, shk.w);
          if (lane >= 27) sts128(base + (lane >= 29 ? CH_OFF + (lane - 32) * 16 : CT_OFF + (lane - 27) * 16), 0u, 0u, 0u, 0u);
          fence_async_smem();
          __syncwarp();
          if (elect_one()) {
            mbar_expect(cf, 4080 + KVT - 32);
            bulk_g2s(base + CT_OFF + 32, gs->kv + (size_t)d * KVT, KVT - 32, cf);
            bulk_g2s_stream(base + CH_OFF + 16, ssmk + (size_t)d * S_ + 8, 4080, cf, pol);
          }
        }
      }
      if (warp == 9) {
        if (elect_one()) {
          const uint32_t bsz = ro.pitch - ASZ;
#pragma unroll 1
          for (int w = 0; w < 2; w++) {
            const uint32_t src = sb + (ro.kind ? (w ? (36 % ST) * PITCH_B + ASZ : ST * PITCH_B) : ((32 % ST) + w) * PITCH_S + ASZ);
            mbar_wait_u(bars + B_USTG + w * 8, 0);
            bulk_s2g(gs->u + (size_t)(2 * ro.g1_mt + w) * D_ * 128 + ro.g1_nt * bsz, src, bsz);
            bulk_commit();
            if (ro.kind && w == 0) gate_arrive(gs->flags, TN(GDELAY) - 512);
            bulk_wait_read();
            mbar_arrive(bars + B_UDONE + w * 8);
            bulk_wait_all();
            flag_add(gs->flags, FL_U + ro.half * 3 + (ro.kind ? 2 : w), 1);
            PROFG(5 + 12 * w);
          }
          if (ro.kind == 0) {
#pragma unroll 1
            for (int i = 0; i < NCONV; i++) {
              mbar_wait_u(bars + B_SFULL + (i & 1) * 8, (i >> 1) & 1);
              bulk_s2g(gs->z + (size_t)chan_pos(conv_chan(ro.cs, i)) * S_, sb + CSTG_OFF + (i & 1) * 4096, 4096);
              bulk_commit();
              if (i == NCONV - 3) gate_arrive(gs->flags, 0);
              bulk_wait_read();
              mbar_arrive(bars + B_SEMPTY + (i & 1) * 8);
            }
            bulk_wait_all();
            flag_add(gs->flags, FL_Z, 1);
            PROFG(6);
          }
        }
      } else if (ro.kind != 2) {
        mbar_wait_u(bars + B_UDONE, 0);
        uint2 gate;
#pragma unroll 1
        for (uint32_t spins = 0;; spins++) {
          asm volatile("ld.relaxed.gpu.global.v2.u32 {%0, %1}, [%2];" : "=r"(gate.x), "=r"(gate.y) : "l"(gs->flags + FL_GATE * 32) : "memory");
          if (gate.x == NCTA) break;
          __nanosleep(100);
          if (spins > SPIN_LIMIT) asm volatile("trap;");
        }
        if (lane == 0) PROF(46);
#pragma unroll 1
        for (int w = 0; w < 2; w++) {
          while (time_now() - gate.y < TN(GDELAY) + w * TN(GDELAY1)) {}
          if (lane == 0) mbar_arrive(bars + B_G2GO + w * 8);
          if (lane == 0 && w == 0) PROF(24);
        }
        wait_counter(gs->flags, FL_Z, 96u, 0, 300);
        spin_until(clock_now(), TN(ZDELAY) + TN(ZRAMP) * cta);
        if (elect_one()) {
          mbar_expect(bars + B_ZFULL, 18432);
          tma2d(sb + ST * ro.pitch, &tmZ, ro.g2_m, ro.dt * 144 + ro.half * 72, bars + B_ZFULL);
          tma2d(sb + ST * ro.pitch + 9216, &tmZ, ro.g2_m + 64, ro.dt * 144 + ro.half * 72, bars + B_ZFULL);
          PROFG(7);
        }
        polling_done(gs->flags, lane);
      }
    }
  } else {
    asm volatile("setmaxnreg.inc.sync.aligned.u32 224;");
    const int wi = warp & 3, g = lane >> 2, qd = lane & 3, wt = tid & 127;
    const bool leader = wt == 0;
    Pipe p{{0, 0}, 0, false, 0};
    asm volatile("barrier.cluster.wait.aligned;" ::: "memory");
    int kind;
    {
      const Role ro = get_role(roles);
      kind = ro.kind;
      const int f0 = ro.g1_mt * 128 + wg * 64 + wi * 16 + g;
      uint32_t bias0 = ldg16(b1 + f0), bias1 = ldg16(b1 + f0 + 8);
      const uint32_t so = ((lane >> 4) * 8 + (lane & 7)) * 128 + (((2 * wi + ((lane >> 3) & 1)) ^ (lane & 7)) << 4);
      if (kind) {
        float acc[96];
        gemm_run<1, LEAD_B>(acc, 32, 0, p, sb, PITCH_B, wg, leader);
        pipe_drain(p, bars, leader);
        if (wg) mbar_wait_u(bars + B_EMPTY + (36 % ST) * 8, ((36 / ST) & 1) ^ 1);
        if (leader) PROF(4 + 10 * wg);
        uint32_t sa = sb + (wg ? (36 % ST) * PITCH_B + ASZ : ST * PITCH_B) + so;
#pragma unroll 1
        for (int c = 0; c < 4; c++, sa += 6144) {
          gelu_store<24>(acc, bias0, bias1, sa, [](int) {});
#pragma unroll
          for (int i = 0; i < 72; i++) acc[i] = acc[i + 24];
        }
        fence_async_smem();
        __syncwarp();
        if (lane == 0) mbar_arrive(bars + B_USTG + wg * 8);
        if (leader) PROF(15 + wg);
      } else {
        const int cB = (g >> 1) & 1, cA = g >> 2, b = 2 * wi + (g & 1);
        const uint32_t toff = pin(CT_OFF + (40 * (2 * cA + cB) + 8 + b - 2 * qd) * 4);
        uint32_t a[16][4];
        auto load_a = [&](uint32_t base, int t, uint32_t on) {
          const uint32_t pt = base + toff + (t >> 1) * 1280 + (t & 1) * 64;
          a[t][0] = lds32_if(pt + 32, on); a[t][1] = lds32_if(pt + 672, on); a[t][2] = lds32_if(pt, on); a[t][3] = lds32_if(pt + 640, on);
        };
        {
          float acc[72];
          gemm_run<1, LEAD_S>(acc, 32, 0, p, sb, PITCH_S, wg, leader);
          if (wg == 1) named_arrive(6, 256);
          mbar_wait_u(bars + B_EMPTY + ((32 % ST) + wg) * 8, ((32 / ST) & 1) ^ 1);
          mbar_wait_u(bars + B_CFULL + wg * 8, 0);
          pipe_drain(p, bars, leader);
          if (leader) mbar_arrive(bars + B_G1DONE);
          if (leader) PROF(4 + 10 * wg);
          if (tid == 128) PROFC(48);
          gelu_store<72>(acc, bias0, bias1, sb + ((32 % ST) + wg) * PITCH_S + ASZ + so, [&](int t) { if (t < 8) load_a(conv_buf(sb, wg), t, 1); });
          fence_async_smem();
          __syncwarp();
          if (lane == 0) mbar_arrive(bars + B_USTG + wg * 8);
          if (leader) PROF(15 + wg);
        }
        const int phi = 2 * cA + (qd >> 1) + cB, pp = cB ? (phi & 3) : ((phi + 3) & 3);
        const int srcB = pin(((pp >> 1) << 4) | ((cB ^ 1) << 3) | ((g & 1) << 2) | ((pp & 1) << 1) | (qd & 1));
        const bool pB1 = cB && phi < 4, pB2 = cB && phi == 4;
        const int word = (8 * cB + 2 * (phi & 3) + (qd & 1)) * 8 + b;
        const uint32_t sto = pin(sb + CSTG_OFF + wg * 4096 + (word ^ (((word >> 5) & 3) << 1)) * 4);
#pragma unroll 1
        for (int i = wg; i < NCONV; i += 2) {
          const uint32_t base = conv_buf(sb, i & 3), next = conv_buf(sb, (i + 2) & 3);
          const uint64_t dH = mkdesc(base + CH_OFF, 16, 128, 0);
          float y[8][16];
          named_bar(6 + wg, 256);
          wg_fence();
#pragma unroll
          for (int t = 0; t < 16; t++) {
            if (t >= 8 && t % CFENCE == 0) wg_fence();
            if (t == CTURN) named_arrive(7 - wg, 256);
#pragma unroll
            for (int cb = t >> 1; cb < 8; cb++) {
              wgmma_rs_n32(y[cb], a[t][0], a[t][1], a[t][2], a[t][3], dH + (32 * cb - 32 * (t >> 1) - 2 * (t & 1) - 1), t);
              const int n = 8 * t - (t >> 1) * ((t - 1) >> 1) - (t >> 1) + cb + 1;
              if (n % CPER == 0 && n / CPER <= 8) load_a(base, 7 + n / CPER, 1);
            }
            if (t == 7 && CEARLY) wg_commit();
          }
          wg_commit();
          const bool more = i + 2 < NCONV;
          if (more) mbar_wait_u(bars + B_CFULL + ((i + 2) & 3) * 8, (i + 2) >> 2);
          mbar_wait_u(bars + B_SEMPTY + wg * 8, ((i >> 1) & 1) ^ 1);
          if (CEARLY) wg_wait<1>();
#pragma unroll
          for (int t = 0; t < CEARLY; t++) load_a(next, t, more);
          wg_wait<0>();
          if (lane == 0) mbar_arrive(bars + B_CEMPTY + (i & 3) * 8);
          if (leader) PROF(40 + i);
          uint32_t P[16], Q[16], R[16], o[8];
#pragma unroll
          for (int j = 0; j < 32; j++) {
            if ((j & 3) == 0 && (j >> 2) >= CEARLY) load_a(next, j >> 2, more);
            float v0 = y[j >> 2][4 * (j & 3)], v1 = y[j >> 2][4 * (j & 3) + 1];
            if (j >= 2) { v0 += y[(j - 2) >> 2][4 * ((j - 2) & 3) + 2]; v1 += y[(j - 2) >> 2][4 * ((j - 2) & 3) + 3]; }
            if (j & 1) R[j >> 1] = shfl_ordered(pack_bf16(v0, v1), lane ^ 16);
            else P[j >> 1] = pack_bf16(v0, v1);
          }
#pragma unroll
          for (int m = 0; m < 16; m++) Q[m] = hadd2(P[m], cA ? R[m] : (m ? R[m - 1] : 0u));
#pragma unroll
          for (int m = 0; m < 8; m++) o[m] = shfl_ordered(pB1 ? Q[2 * m] : (pB2 ? (m ? Q[2 * m - 1] : 0u) : Q[2 * m + 1]), srcB);
#pragma unroll
          for (int m = 0; m < 8; m++) sts32(sto + m * 512, hadd2(pB1 ? Q[2 * m + 1] : Q[2 * m], o[m]));
          fence_async_smem();
          __syncwarp();
          if (lane == 0) mbar_arrive(bars + B_SFULL + wg * 8);
          if (leader && i == 5) PROF(53);
        }
        if (wg == 0) named_bar(6, 256);
      }
    }
    if (kind != 2) {
      const Role ro = get_role(roles);
      const uint32_t pitch = ro.pitch;
      const int s0 = ro.g2_m + wg * 64 + wi * 16 + g;
      const size_t go = (size_t)s0 * D_ + ro.dt * 128 + ro.half * 64 + qd * 8, go8 = (size_t)s0 * D_ + 512 + ro.dt * 16 + ro.half * 8 + qd * 2;
      uint32_t x[2][9], sg[2][9];
      float acc[72];
      mbar_wait_u(bars + B_G2GO + wg * 8, 0);
      gemm_run<0, 0>(acc, XAT + 2 * wg, 0, p, sb, pitch, wg, leader);
#pragma unroll
      for (int J = 0; J < 4; J++) {
        const uint4 v = ldg128(q + go + (J & 1) * 8 * D_ + (J >> 1) * 32);
        x[J & 1][4 * (J >> 1)] = v.x; x[J & 1][4 * (J >> 1) + 1] = v.y; x[J & 1][4 * (J >> 1) + 2] = v.z; x[J & 1][4 * (J >> 1) + 3] = v.w;
      }
      x[0][8] = ldg32(q + go8); x[1][8] = ldg32(q + go8 + 8 * D_);
      const uint4 st0 = ld_l2(gs->stats + s0), st1 = ld_l2(gs->stats + s0 + 8);
      const uint32_t braw0 = ldg16(b2 + s0), braw1 = ldg16(b2 + s0 + 8);
      gemm_run<0, 0>(acc, 20 - XAT, 1, p, sb, pitch, wg, leader);
      {
        const int zw = 8 * wi + (g ^ ((((ro.g2_m >> 6) + wg) & 3) << 1));
        const uint32_t za = sb + ST * pitch + wg * 9216 + qd * 256 + (zw & 3) * 4;
        mbar_wait_u(bars + B_ZFULL, 0);
#pragma unroll
        for (int j = 0; j < 9; j++) {
          sg[0][j] = lds32(za + j * 1024 + (((zw >> 2) ^ (2 * qd)) << 4));
          sg[1][j] = lds32(za + j * 1024 + 128 + (((zw >> 2) ^ (2 * qd + 1)) << 4));
        }
      }
      gemm_run<0, 0>(acc, 1, 1, p, sb, pitch, wg, leader);
#pragma unroll
      for (int j = 0; j < 9; j++) {
        const uint32_t z0 = __byte_perm(sg[0][j], sg[1][j], 0x5410), z1 = __byte_perm(sg[0][j], sg[1][j], 0x7632);
        sg[0][j] = hmul2(ln_apply(x[0][j], st0), z0);
        sg[1][j] = hmul2(ln_apply(x[1][j], st1), z1);
        asm volatile("" : "+r"(sg[0][j]), "+r"(sg[1][j]));
      }
      gemm_run<0, SKEW>(acc, 15 - LAG - 2 * wg, 1, p, sb, pitch, wg, leader);
      const uint32_t rbuf = sb + (68 % ST) * pitch + warp * 2304;
      const uint32_t rdst = mapa(rbuf, ro.half ^ 1), rbar = mapa(bars + B_RFULL + wg * 8, ro.half ^ 1);
      pipe_drain(p, bars, leader);
      if (leader) PROF(9 + 10 * wg);
      if (tid == 128) PROFC(50);
      float cs[36], ck[36];
      split_acc(acc, cs, ck);
      gemm2_part<0, 0, 4 * LAG>(cs, sb, pitch, wg);
      if (KPRE) gemm2_part<72, 0, KPRE>(ck, sb, pitch, wg);
      const float hb0 = fmaf(bf_lo(braw0), 0.5f, __uint_as_float(st0.w)), hb1 = fmaf(bf_lo(braw1), 0.5f, __uint_as_float(st1.w));
      mbar_wait(bars + B_GO, 0);
      wg_wait<KPRE ? 1 : 0>();
      if (leader) PROF(54 + wg);
#pragma unroll
      for (int i = 0; i < 5; i++) {
        const float* c = &cs[8 * i];
        const uint32_t v0 = pack_bf16(fmaf(c[0], 0.5f, hb0), fmaf(c[1], 0.5f, hb0)), v1 = pack_bf16(fmaf(c[2], 0.5f, hb1), fmaf(c[3], 0.5f, hb1));
        if (i < 4) st_async4(rdst + i * 512 + lane * 16, v0, v1, pack_bf16(fmaf(c[4], 0.5f, hb0), fmaf(c[5], 0.5f, hb0)), pack_bf16(fmaf(c[6], 0.5f, hb1), fmaf(c[7], 0.5f, hb1)), rbar);
        else st_async2(rdst + 2048 + lane * 8, v0, v1, rbar);
      }
      if (wg == 1) named_bar(7, 256);
      gemm2_part<72, KPRE, 4 * LAG>(ck, sb, pitch, wg);
      uint32_t rp[18];
      mbar_wait(bars + B_RFULL + wg * 8, 0);
#pragma unroll
      for (int m = 0; m < 4; m++) {
        const uint4 v = lds128(rbuf + m * 512 + lane * 16);
        rp[4 * m] = v.x; rp[4 * m + 1] = v.y; rp[4 * m + 2] = v.z; rp[4 * m + 3] = v.w;
      }
      { const uint2 v = lds64(rbuf + 2048 + lane * 8); rp[16] = v.x; rp[17] = v.y; }
      __nv_bfloat16* o = out + go;
      wg_wait<0>();
      if (leader) PROF(10 + 10 * wg);
      float h[2][4], t[2][4], half = 0.5f;
#pragma unroll
      for (int j = 0; j <= 9; j++) {
        if (j < 9) {
          const uint32_t ra = rp[2 * j], rb = rp[2 * j + 1];
          if (j >= 2) half = fmaf(t[j & 1][3], 0.f, 0.5f);
          h[j & 1][0] = fmaf(ck[4 * j], half, bf_lo(ra)); h[j & 1][1] = fmaf(ck[4 * j + 1], half, bf_hi(ra));
          h[j & 1][2] = fmaf(ck[4 * j + 2], half, bf_lo(rb)); h[j & 1][3] = fmaf(ck[4 * j + 3], half, bf_hi(rb));
#pragma unroll
          for (int u = 0; u < 4; u++) t[j & 1][u] = tanh_ordered(h[j & 1][u]);
        }
        if (j > 0) {
          const int k = j - 1;
          const float* hh = h[k & 1];
          const float* tt = t[k & 1];
          x[0][k] = hfma2(sg[0][k], pack_bf16(fmaf(hh[0], tt[0], hh[0]), fmaf(hh[1], tt[1], hh[1])), x[0][k]);
          x[1][k] = hfma2(sg[1][k], pack_bf16(fmaf(hh[2], tt[2], hh[2]), fmaf(hh[3], tt[3], hh[3])), x[1][k]);
          if ((k & 3) == 3) {
            *(uint4*)(o + (k >> 2) * 32) = make_uint4(x[0][k - 3], x[0][k - 2], x[0][k - 1], x[0][k]);
            *(uint4*)(o + 8 * D_ + (k >> 2) * 32) = make_uint4(x[1][k - 3], x[1][k - 2], x[1][k - 1], x[1][k]);
          }
        }
      }
      *(uint32_t*)(out + go8) = x[0][8];
      *(uint32_t*)(out + go8 + 8 * D_) = x[1][8];
      if (leader) PROF(11 + 7 * wg);
      if (tid == 128) PROFC(51);
    }
  }
}

typedef CUresult (*EncodeFn)(CUtensorMap*, CUtensorMapDataType, cuuint32_t, void*, const cuuint64_t*, const cuuint64_t*, const cuuint32_t*,
                             const cuuint32_t*, CUtensorMapInterleave, CUtensorMapSwizzle, CUtensorMapL2promotion, CUtensorMapFloatOOBfill);

uint32_t role_of_pair(int t) {
  int grp, i;
  if (t < 32) { const int j = t & 7; i = t >> 3; grp = j < 6 ? 1 + j : 12 + 2 * (j - 6); }
  else if (t < 60) { const int j = (t - 32) % 7; i = (t - 32) / 7; grp = j < 5 ? 7 + j : 13 + 2 * (j - 5); }
  else if (t < 62) return 2u | (uint32_t)(14 + 3 * (t - 60)) << 8 | 2u << 16;
  else { grp = 0; i = t - 62; }
  if (grp < 12) return (uint32_t)(i << 2 | grp << 4 | grp << 8 | i << 16);
  const int u = (grp & 1) * 4 + i;
  return (uint32_t)(1 | i << 2 | grp << 4 | (12 + 3 * ((grp - 12) >> 1) + u / 3) << 8 | (u % 3) << 16);
}

}

extern "C" void kernel_launch(void* const* d_in, const int* in_sizes, int n_in, void* d_out, int out_size) {
  (void)in_sizes; (void)n_in; (void)out_size;
  EncodeFn enc = nullptr;
  cudaDriverEntryPointQueryResult qr;
  cudaGetDriverEntryPoint("cuTensorMapEncodeTiled", (void**)&enc, cudaEnableDefault, &qr);
  Scratch* gs = nullptr;
  cudaGetSymbolAddress((void**)&gs, g_scratch);
  void *zp = gs->z, *hp = gs->h, *kvp = gs->kv;
  CUtensorMap tmW1, tmW2, tmZ, tmH, tmK, tmV, tmKV;
  for (int w = 0; w < 2; w++) {
    cuuint64_t gd[2] = {D_, S_};
    cuuint64_t st[1] = {D_ * 2};
    cuuint32_t bx[2] = {64, w ? 33u : 36u};
    cuuint32_t es[2] = {1, 1};
    enc(w ? &tmV : &tmK, CU_TENSOR_MAP_DATA_TYPE_BFLOAT16, 2, d_in[1 + w], gd, st, bx, es, CU_TENSOR_MAP_INTERLEAVE_NONE, CU_TENSOR_MAP_SWIZZLE_NONE,
        CU_TENSOR_MAP_L2_PROMOTION_L2_128B, CU_TENSOR_MAP_FLOAT_OOB_FILL_NONE);
  }
  {
    cuuint64_t gd[4] = {40, D_ / 2, 2, 64};
    cuuint64_t st[3] = {2 * KVT, KVT, 160};
    cuuint32_t bx[4] = {44, KVROWS, 1, 1};
    cuuint32_t es[4] = {1, 1, 1, 1};
    enc(&tmKV, CU_TENSOR_MAP_DATA_TYPE_UINT32, 4, kvp, gd, st, bx, es, CU_TENSOR_MAP_INTERLEAVE_NONE, CU_TENSOR_MAP_SWIZZLE_NONE,
        CU_TENSOR_MAP_L2_PROMOTION_NONE, CU_TENSOR_MAP_FLOAT_OOB_FILL_NONE);
  }
  {
    cuuint64_t gd[3] = {64, 32 * 72, 8};
    cuuint64_t st[2] = {1024, 128};
    cuuint32_t bx[3] = {64, 72, 1};
    cuuint32_t es[3] = {1, 1, 1};
    enc(&tmH, CU_TENSOR_MAP_DATA_TYPE_BFLOAT16, 3, hp, gd, st, bx, es, CU_TENSOR_MAP_INTERLEAVE_NONE, CU_TENSOR_MAP_SWIZZLE_128B,
        CU_TENSOR_MAP_L2_PROMOTION_NONE, CU_TENSOR_MAP_FLOAT_OOB_FILL_NONE);
  }
  for (int w = 0; w < 2; w++) {
    const cuuint64_t M = w ? S_ : F_, K = w ? F_ : S_;
    cuuint64_t gd[3] = {64, K, M / 64};
    cuuint64_t st[2] = {M * 2, 128};
    cuuint32_t bx[3] = {64, 64, 2};
    cuuint32_t es[3] = {1, 1, 1};
    enc(w ? &tmW2 : &tmW1, CU_TENSOR_MAP_DATA_TYPE_BFLOAT16, 3, d_in[w ? 9 : 7], gd, st, bx, es, CU_TENSOR_MAP_INTERLEAVE_NONE,
        CU_TENSOR_MAP_SWIZZLE_128B, CU_TENSOR_MAP_L2_PROMOTION_L2_256B, CU_TENSOR_MAP_FLOAT_OOB_FILL_NONE);
  }
  {
    cuuint64_t gd[2] = {S_, D_};
    cuuint64_t st[1] = {S_ * 2};
    cuuint32_t bx[2] = {64, 72};
    cuuint32_t es[2] = {1, 1};
    enc(&tmZ, CU_TENSOR_MAP_DATA_TYPE_BFLOAT16, 2, zp, gd, st, bx, es, CU_TENSOR_MAP_INTERLEAVE_NONE, CU_TENSOR_MAP_SWIZZLE_128B,
        CU_TENSOR_MAP_L2_PROMOTION_L2_256B, CU_TENSOR_MAP_FLOAT_OOB_FILL_NONE);
  }
  RoleMap roles;
  int dev = 0, sms = 0;
  cudaGetDevice(&dev);
  cudaDeviceGetAttribute(&sms, cudaDevAttrMultiProcessorCount, dev);
  roles.by_sm = sms == NCTA;
  for (int k = 0; k < NCTA / 2; k++) roles.role[k] = role_of_pair(k);
  cudaFuncSetAttribute(fused_kernel, cudaFuncAttributeMaxDynamicSharedMemorySize, SMEM_BYTES);
  fused_kernel<<<NCTA, 384, SMEM_BYTES>>>((const __nv_bfloat16*)d_in[0], gs, (const __nv_bfloat16*)d_in[8], (const __nv_bfloat16*)d_in[3],
                                          (const __nv_bfloat16*)d_in[4], (const __nv_bfloat16*)d_in[5], tmW1, tmW2, tmZ, tmH, tmK, tmV, tmKV,
                                          roles, (const __nv_bfloat16*)d_in[10], (__nv_bfloat16*)d_out);
}
```

```cpp
#include <cuda_runtime.h>
#include <cuda_bf16.h>
#include <cuda.h>
#include <stdint.h>

namespace {

constexpr int S_ = 2048, D_ = 576, F_ = 4608;
constexpr int NCTA = 132, NG2 = 128, NCONV = 6;
constexpr int ST = 5, ASZ = 16384, PITCH_S = ASZ + 144 * 128, PITCH_B = ASZ + 192 * 128;
constexpr int KVIN = (36 + 33) * 128, KVW = 2 * KVIN + 64 * 176;
constexpr int BAR_OFF = ST * PITCH_S + 2 * KVW;
constexpr int SMEM_BYTES = BAR_OFF + 512;
constexpr int LNROT = 120;
constexpr int SKEW = 1;
constexpr int LEAD_S = 3, LEAD_B = 2;
constexpr int CTURN = 14, CPER = 4, CEARLY = 0, CFENCE = 8;
constexpr int TURN = 4, KPRE = 2;
constexpr int XAT = 12;
constexpr int LAG = 4;
constexpr int CBUF = 14464, CH_OFF = 48, CT_OFF = 4192, KVT = 8192;
constexpr int CSTG_OFF = ST * PITCH_S + 3 * CBUF;
constexpr uint32_t SPIN_LIMIT = 1u << 22;

constexpr int FL_H = 0, FL_U = 3, FL_KV = 9, FL_Z = 12, FL_GATE = 13, FL_DONE = 14, FL_N = 15;
struct Scratch {
  uint32_t flags[64 * 32];
  uint4 stats[S_];
  uint8_t h[32 * 72 * 1024];
  uint8_t u[72 * D_ * 128];
  uint8_t kv[D_ * KVT];
  __nv_bfloat16 z[D_ * S_];
};
__device__ __align__(1024) Scratch g_scratch;
extern __shared__ __align__(1024) uint8_t smem_raw[];
#define TUNABLES(X) X(W9, 1200) X(QLATE, 40) X(QDELAY, 400) X(QRAMP, 5) X(A0, 1200) X(AD, 300) X(AN, 2) X(AL, 1500) X(H0, 3100) X(HD, 400) X(HS2, 6) X(HW, 4200) X(LK1, 7) X(LK2, 14) X(KVGO, 8) X(KVGO1, 11) X(CVGO, 31) X(GDELAY, 608) X(GDELAY1, 256) X(ZDELAY, 3000) X(ZRAMP, 40)
#define X(k, v) constexpr int T_##k = v;
TUNABLES(X)
#undef X
#define TN(k) T_##k
struct RoleMap { uint32_t role[NCTA / 2]; uint32_t by_sm; };
#define PROF(i) do {} while (0)
#define PROFG(i) do {} while (0)
#define PROFC(i) do {} while (0)

template<int TB> __device__ __forceinline__ void wgmma_ss(float (&d)[96], uint32_t da, uint32_t db, int sd) {
  asm volatile("{\n.reg .pred p;\n.reg .b64 a, b;\nsetp.ne.b32 p, %98, 0;\nmov.b64 a, {%96, %100};\nmov.b64 b, {%97, %101};\n"
    "wgmma.mma_async.sync.aligned.m64n192k16.f32.bf16.bf16 {%0, %1, %2, %3, %4, %5, %6, %7, %8, %9, %10, %11, %12, %13, %14, %15, %16, %17, %18, %19, %20, %21, %22, %23, %24, %25, %26, %27, %28, %29, %30, %31, %32, %33, %34, %35, %36, %37, %38, %39, %40, %41, %42, %43, %44, %45, %46, %47, %48, %49, %50, %51, %52, %53, %54, %55, %56, %57, %58, %59, %60, %61, %62, %63, %64, %65, %66, %67, %68, %69, %70, %71, %72, %73, %74, %75, %76, %77, %78, %79, %80, %81, %82, %83, %84, %85, %86, %87, %88, %89, %90, %91, %92, %93, %94, %95}, a, b, p, 1, 1, 1, %99;\n}\n"
    : "+f"(d[0]), "+f"(d[1]), "+f"(d[2]), "+f"(d[3]), "+f"(d[4]), "+f"(d[5]), "+f"(d[6]), "+f"(d[7]), "+f"(d[8]), "+f"(d[9]), "+f"(d[10]), "+f"(d[11]), "+f"(d[12]), "+f"(d[13]), "+f"(d[14]), "+f"(d[15]), "+f"(d[16]), "+f"(d[17]), "+f"(d[18]), "+f"(d[19]), "+f"(d[20]), "+f"(d[21]), "+f"(d[22]), "+f"(d[23]), "+f"(d[24]), "+f"(d[25]), "+f"(d[26]), "+f"(d[27]), "+f"(d[28]), "+f"(d[29]), "+f"(d[30]), "+f"(d[31]), "+f"(d[32]), "+f"(d[33]), "+f"(d[34]), "+f"(d[35]), "+f"(d[36]), "+f"(d[37]), "+f"(d[38]), "+f"(d[39]), "+f"(d[40]), "+f"(d[41]), "+f"(d[42]), "+f"(d[43]), "+f"(d[44]), "+f"(d[45]), "+f"(d[46]), "+f"(d[47]), "+f"(d[48]), "+f"(d[49]), "+f"(d[50]), "+f"(d[51]), "+f"(d[52]), "+f"(d[53]), "+f"(d[54]), "+f"(d[55]), "+f"(d[56]), "+f"(d[57]), "+f"(d[58]), "+f"(d[59]), "+f"(d[60]), "+f"(d[61]), "+f"(d[62]), "+f"(d[63]), "+f"(d[64]), "+f"(d[65]), "+f"(d[66]), "+f"(d[67]), "+f"(d[68]), "+f"(d[69]), "+f"(d[70]), "+f"(d[71]), "+f"(d[72]), "+f"(d[73]), "+f"(d[74]), "+f"(d[75]), "+f"(d[76]), "+f"(d[77]), "+f"(d[78]), "+f"(d[79]), "+f"(d[80]), "+f"(d[81]), "+f"(d[82]), "+f"(d[83]), "+f"(d[84]), "+f"(d[85]), "+f"(d[86]), "+f"(d[87]), "+f"(d[88]), "+f"(d[89]), "+f"(d[90]), "+f"(d[91]), "+f"(d[92]), "+f"(d[93]), "+f"(d[94]), "+f"(d[95])
    : "r"(da), "r"(db), "r"(sd), "n"(TB), "r"(0x40000040u), "r"(TB ? 0x40u : 0x40000040u));
}
template<int TB> __device__ __forceinline__ void wgmma_ss(float (&d)[72], uint32_t da, uint32_t db, int sd) {
  asm volatile("{\n.reg .pred p;\n.reg .b64 a, b;\nsetp.ne.b32 p, %74, 0;\nmov.b64 a, {%72, %76};\nmov.b64 b, {%73, %77};\n"
    "wgmma.mma_async.sync.aligned.m64n144k16.f32.bf16.bf16 {%0, %1, %2, %3, %4, %5, %6, %7, %8, %9, %10, %11, %12, %13, %14, %15, %16, %17, %18, %19, %20, %21, %22, %23, %24, %25, %26, %27, %28, %29, %30, %31, %32, %33, %34, %35, %36, %37, %38, %39, %40, %41, %42, %43, %44, %45, %46, %47, %48, %49, %50, %51, %52, %53, %54, %55, %56, %57, %58, %59, %60, %61, %62, %63, %64, %65, %66, %67, %68, %69, %70, %71}, a, b, p, 1, 1, 1, %75;\n}\n"
    : "+f"(d[0]), "+f"(d[1]), "+f"(d[2]), "+f"(d[3]), "+f"(d[4]), "+f"(d[5]), "+f"(d[6]), "+f"(d[7]), "+f"(d[8]), "+f"(d[9]), "+f"(d[10]), "+f"(d[11]), "+f"(d[12]), "+f"(d[13]), "+f"(d[14]), "+f"(d[15]), "+f"(d[16]), "+f"(d[17]), "+f"(d[18]), "+f"(d[19]), "+f"(d[20]), "+f"(d[21]), "+f"(d[22]), "+f"(d[23]), "+f"(d[24]), "+f"(d[25]), "+f"(d[26]), "+f"(d[27]), "+f"(d[28]), "+f"(d[29]), "+f"(d[30]), "+f"(d[31]), "+f"(d[32]), "+f"(d[33]), "+f"(d[34]), "+f"(d[35]), "+f"(d[36]), "+f"(d[37]), "+f"(d[38]), "+f"(d[39]), "+f"(d[40]), "+f"(d[41]), "+f"(d[42]), "+f"(d[43]), "+f"(d[44]), "+f"(d[45]), "+f"(d[46]), "+f"(d[47]), "+f"(d[48]), "+f"(d[49]), "+f"(d[50]), "+f"(d[51]), "+f"(d[52]), "+f"(d[53]), "+f"(d[54]), "+f"(d[55]), "+f"(d[56]), "+f"(d[57]), "+f"(d[58]), "+f"(d[59]), "+f"(d[60]), "+f"(d[61]), "+f"(d[62]), "+f"(d[63]), "+f"(d[64]), "+f"(d[65]), "+f"(d[66]), "+f"(d[67]), "+f"(d[68]), "+f"(d[69]), "+f"(d[70]), "+f"(d[71])
    : "r"(da), "r"(db), "r"(sd), "n"(TB), "r"(0x40000040u), "r"(TB ? 0x40u : 0x40000040u));
}
template<int TB> __device__ __forceinline__ void wgmma_ss(float (&d)[36], uint32_t da, uint32_t db, int sd) {
  asm volatile("{\n.reg .pred p;\n.reg .b64 a, b;\nsetp.ne.b32 p, %38, 0;\nmov.b64 a, {%36, %40};\nmov.b64 b, {%37, %41};\n"
    "wgmma.mma_async.sync.aligned.m64n72k16.f32.bf16.bf16 {%0, %1, %2, %3, %4, %5, %6, %7, %8, %9, %10, %11, %12, %13, %14, %15, %16, %17, %18, %19, %20, %21, %22, %23, %24, %25, %26, %27, %28, %29, %30, %31, %32, %33, %34, %35}, a, b, p, 1, 1, 1, %39;\n}\n"
    : "+f"(d[0]), "+f"(d[1]), "+f"(d[2]), "+f"(d[3]), "+f"(d[4]), "+f"(d[5]), "+f"(d[6]), "+f"(d[7]), "+f"(d[8]), "+f"(d[9]), "+f"(d[10]), "+f"(d[11]), "+f"(d[12]), "+f"(d[13]), "+f"(d[14]), "+f"(d[15]), "+f"(d[16]), "+f"(d[17]), "+f"(d[18]), "+f"(d[19]), "+f"(d[20]), "+f"(d[21]), "+f"(d[22]), "+f"(d[23]), "+f"(d[24]), "+f"(d[25]), "+f"(d[26]), "+f"(d[27]), "+f"(d[28]), "+f"(d[29]), "+f"(d[30]), "+f"(d[31]), "+f"(d[32]), "+f"(d[33]), "+f"(d[34]), "+f"(d[35])
    : "r"(da), "r"(db), "r"(sd), "n"(TB), "r"(0x40000040u), "r"(TB ? 0x40u : 0x40000040u));
}
__device__ __forceinline__ void wgmma_rs_n32(float (&d)[16], uint32_t a0, uint32_t a1, uint32_t a2, uint32_t a3, uint64_t db, int sd) {
  asm volatile("{\n.reg .pred p;\nsetp.ne.b32 p, %21, 0;\n"
    "wgmma.mma_async.sync.aligned.m64n32k16.f32.bf16.bf16 {%0, %1, %2, %3, %4, %5, %6, %7, %8, %9, %10, %11, %12, %13, %14, %15}, {%16, %17, %18, %19}, %20, p, 1, 1, 0;\n}\n"
    : "+f"(d[0]), "+f"(d[1]), "+f"(d[2]), "+f"(d[3]), "+f"(d[4]), "+f"(d[5]), "+f"(d[6]), "+f"(d[7]), "+f"(d[8]), "+f"(d[9]), "+f"(d[10]), "+f"(d[11]), "+f"(d[12]), "+f"(d[13]), "+f"(d[14]), "+f"(d[15])
    : "r"(a0), "r"(a1), "r"(a2), "r"(a3), "l"(db), "r"(sd));
}

__device__ __forceinline__ void wg_fence() { asm volatile("wgmma.fence.sync.aligned;" ::: "memory"); }
__device__ __forceinline__ void wg_commit() { asm volatile("wgmma.commit_group.sync.aligned;" ::: "memory"); }
template <int n> __device__ __forceinline__ void wg_wait() { asm volatile("wgmma.wait_group.sync.aligned %0;" ::"n"(n) : "memory"); }
__device__ __forceinline__ uint64_t mkdesc(uint32_t addr, uint32_t lbo, uint32_t sbo, uint32_t sw) {
  return (uint64_t)((addr & 0x3FFFF) >> 4) | ((uint64_t)(lbo >> 4) << 16) | ((uint64_t)(sbo >> 4) << 32) | ((uint64_t)sw << 62);
}
__device__ __forceinline__ void mbar_init(uint32_t a, int c) { asm volatile("mbarrier.init.shared::cta.b64 [%0], %1;" ::"r"(a), "r"(c)); }
__device__ __forceinline__ void mbar_expect(uint32_t a, uint32_t b) { asm volatile("mbarrier.arrive.expect_tx.shared::cta.b64 _, [%0], %1;" ::"r"(a), "r"(b) : "memory"); }
__device__ __forceinline__ void mbar_arrive(uint32_t a) { asm volatile("mbarrier.arrive.shared::cta.b64 _, [%0];" ::"r"(a) : "memory"); }
__device__ __forceinline__ void mbar_arrive_cluster(uint32_t raddr) { asm volatile("mbarrier.arrive.shared::cluster.b64 _, [%0];" ::"r"(raddr) : "memory"); }
__device__ __forceinline__ uint32_t mapa(uint32_t a, uint32_t cta) { uint32_t r; asm("mapa.shared::cluster.u32 %0, %1, %2;" : "=r"(r) : "r"(a), "r"(cta)); return r; }
__device__ __forceinline__ void mbar_wait(uint32_t a, uint32_t ph) {
  asm volatile(
      "{\n.reg .pred p;\n.reg .u32 c;\nmov.u32 c, 0;\n"
      "WAIT_LOOP:\nmbarrier.try_wait.parity.shared::cta.b64 p, [%0], %1;\n@p bra WAIT_DONE;\n"
      "add.u32 c, c, 1;\nsetp.lt.u32 p, c, %2;\n@p bra WAIT_LOOP;\ntrap;\nWAIT_DONE:\n}" ::"r"(a), "r"(ph), "n"(SPIN_LIMIT) : "memory");
}
__device__ __forceinline__ void mbar_wait_u(uint32_t a, uint32_t ph) {
  asm volatile("{\n.reg .pred p;\nWAIT_LOOP:\nmbarrier.try_wait.parity.shared::cta.b64 p, [%0], %1;\n@!p bra WAIT_LOOP;\n}" ::"r"(a), "r"(ph) : "memory");
}
__device__ __forceinline__ uint32_t desc_lo(uint32_t addr, uint32_t lbo) { return ((addr & 0x3FFFF) >> 4) | ((lbo >> 4) << 16); }
__device__ __forceinline__ void tma2d(uint32_t dst, const CUtensorMap* m, int c0, int c1, uint32_t bar) {
  asm volatile("cp.async.bulk.tensor.2d.shared::cluster.global.mbarrier::complete_tx::bytes [%0], [%1, {%3, %4}], [%2];" ::"r"(dst), "l"(m), "r"(bar), "r"(c0), "r"(c1) : "memory");
}
__device__ __forceinline__ void bulk_g2s(uint32_t dst, const void* src, uint32_t sz, uint32_t bar) {
  asm volatile("cp.async.bulk.shared::cluster.global.mbarrier::complete_tx::bytes [%0], [%1], %2, [%3];" ::"r"(dst), "l"(src), "r"(sz), "r"(bar) : "memory");
}
__device__ __forceinline__ void bulk_s2g(void* dst, uint32_t src, uint32_t sz) {
  asm volatile("cp.async.bulk.global.shared::cta.bulk_group [%0], [%1], %2;" ::"l"(dst), "r"(src), "r"(sz) : "memory");
}
__device__ __forceinline__ uint64_t stream_policy() {
  uint64_t p;
  asm volatile("createpolicy.fractional.L2::evict_first.b64 %0, 1.0;" : "=l"(p));
  return p;
}
__device__ __forceinline__ void tma_weights(uint32_t dst, const CUtensorMap* m, int k0, int mchunk, uint32_t bar, uint64_t pol) {
  asm volatile("cp.async.bulk.tensor.3d.shared::cluster.global.mbarrier::complete_tx::bytes.L2::cache_hint [%0], [%1, {%6, %3, %4}], [%2], %5;"
               ::"r"(dst), "l"(m), "r"(bar), "r"(k0), "r"(mchunk), "l"(pol), "r"(0) : "memory");
}
__device__ __forceinline__ bool elect_one() {
  uint32_t p;
  asm volatile("{\n.reg .pred P;\nelect.sync _|P, 0xffffffff;\nselp.u32 %0, 1, 0, P;\n}" : "=r"(p));
  return p;
}
__device__ __forceinline__ void bulk_g2s_stream(uint32_t dst, const void* src, uint32_t sz, uint32_t bar, uint64_t pol) {
  asm volatile("cp.async.bulk.shared::cluster.global.mbarrier::complete_tx::bytes.L2::cache_hint [%0], [%1], %2, [%3], %4;"
               ::"r"(dst), "l"(src), "r"(sz), "r"(bar), "l"(pol) : "memory");
}
__device__ __forceinline__ void tma3d_store(const CUtensorMap* m, int c1, int c2, uint32_t src) {
  asm volatile("cp.async.bulk.tensor.3d.global.shared::cta.bulk_group [%0, {%4, %2, %3}], [%1];" ::"l"(m), "r"(src), "r"(c1), "r"(c2), "r"(0) : "memory");
}
__device__ __forceinline__ void tma2d_stream(uint32_t dst, const CUtensorMap* m, int c0, int c1, uint32_t bar, uint64_t pol) {
  asm volatile("cp.async.bulk.tensor.2d.shared::cluster.global.mbarrier::complete_tx::bytes.L2::cache_hint [%0], [%1, {%3, %4}], [%2], %5;"
               ::"r"(dst), "l"(m), "r"(bar), "r"(c0), "r"(c1), "l"(pol) : "memory");
}
__device__ __forceinline__ void tma4d_store(const CUtensorMap* m, int c1, int c2, int c3, uint32_t src) {
  asm volatile("cp.async.bulk.tensor.4d.global.shared::cta.bulk_group [%0, {%5, %2, %3, %4}], [%1];" ::"l"(m), "r"(src), "r"(c1), "r"(c2), "r"(c3), "r"(0) : "memory");
}
__device__ __forceinline__ void bulk_commit() { asm volatile("cp.async.bulk.commit_group;" ::: "memory"); }
__device__ __forceinline__ void bulk_wait_all() { asm volatile("cp.async.bulk.wait_group 0;" ::: "memory"); }
__device__ __forceinline__ void fence_async_smem() { asm volatile("fence.proxy.async.shared::cta;" ::: "memory"); }
__device__ __forceinline__ void fence_async_global() { asm volatile("fence.proxy.async.global;" ::: "memory"); }
__device__ __forceinline__ void named_bar(int id, int n) { asm volatile("bar.sync %0, %1;" ::"r"(id), "r"(n) : "memory"); }
__device__ __forceinline__ void named_arrive(int id, int n) { asm volatile("bar.arrive %0, %1;" ::"r"(id), "r"(n) : "memory"); }
__device__ __forceinline__ void flag_add(uint32_t* f, int i, uint32_t v) { asm volatile("red.relaxed.gpu.global.add.u32 [%0], %1;" ::"l"(f + i * 32), "r"(v) : "memory"); }
__device__ __forceinline__ uint32_t flag_ld(uint32_t* f, int i) { uint32_t v; asm volatile("ld.relaxed.gpu.global.u32 %0, [%1];" : "=r"(v) : "l"(f + i * 32) : "memory"); return v; }
__device__ __forceinline__ void prefetch_map(const CUtensorMap* m) { asm volatile("prefetch.tensormap [%0];" ::"l"(m) : "memory"); }
__device__ __forceinline__ void stsm4_t(uint32_t a, uint32_t r0, uint32_t r1, uint32_t r2, uint32_t r3) {
  asm volatile("stmatrix.sync.aligned.m8n8.x4.trans.shared.b16 [%0], {%1, %2, %3, %4};" ::"r"(a), "r"(r0), "r"(r1), "r"(r2), "r"(r3) : "memory");
}
__device__ __forceinline__ uint32_t lds32(uint32_t a) { uint32_t v; asm volatile("ld.shared.u32 %0, [%1];" : "=r"(v) : "r"(a) : "memory"); return v; }
__device__ __forceinline__ void sts32(uint32_t a, uint32_t v) { asm volatile("st.shared.u32 [%0], %1;" ::"r"(a), "r"(v) : "memory"); }
__device__ __forceinline__ uint4 ld_l2(const uint4* p) { uint4 v; asm volatile("ld.relaxed.gpu.global.v4.u32 {%0, %1, %2, %3}, [%4];" : "=r"(v.x), "=r"(v.y), "=r"(v.z), "=r"(v.w) : "l"(p) : "memory"); return v; }
__device__ __forceinline__ void sts128(uint32_t a, uint32_t x, uint32_t y, uint32_t z, uint32_t w) { asm volatile("st.shared.v4.u32 [%0], {%1, %2, %3, %4};" ::"r"(a), "r"(x), "r"(y), "r"(z), "r"(w) : "memory"); }
__device__ __forceinline__ uint4 lds128(uint32_t a) { uint4 v; asm volatile("ld.shared.v4.u32 {%0, %1, %2, %3}, [%4];" : "=r"(v.x), "=r"(v.y), "=r"(v.z), "=r"(v.w) : "r"(a) : "memory"); return v; }
__device__ __forceinline__ void st_async4(uint32_t raddr, uint32_t a, uint32_t b, uint32_t c, uint32_t d, uint32_t rbar) {
  asm volatile("st.async.weak.shared::cluster.mbarrier::complete_tx::bytes.v4.b32 [%0], {%1, %2, %3, %4}, [%5];" ::"r"(raddr), "r"(a), "r"(b), "r"(c), "r"(d), "r"(rbar) : "memory");
}
__device__ __forceinline__ uint32_t pack_bf16(float lo, float hi) { uint32_t r; asm("cvt.rn.bf16x2.f32 %0, %1, %2;" : "=r"(r) : "f"(hi), "f"(lo)); return r; }
__device__ __forceinline__ float bf_lo(uint32_t v) { return __uint_as_float(v << 16); }
__device__ __forceinline__ float bf_hi(uint32_t v) { return __uint_as_float(v & 0xffff0000u); }
__device__ __forceinline__ float bf_round(float x) { return bf_lo(pack_bf16(x, 0.f)); }
__device__ __forceinline__ uint32_t hmul2(uint32_t a, uint32_t b) { uint32_t r; asm("mul.rn.bf16x2 %0, %1, %2;" : "=r"(r) : "r"(a), "r"(b)); return r; }
__device__ __forceinline__ uint32_t hsub2(uint32_t a, uint32_t b) { uint32_t r; asm("sub.rn.bf16x2 %0, %1, %2;" : "=r"(r) : "r"(a), "r"(b)); return r; }
__device__ __forceinline__ uint32_t hfma2(uint32_t a, uint32_t b, uint32_t c) { uint32_t r; asm("fma.rn.bf16x2 %0, %1, %2, %3;" : "=r"(r) : "r"(a), "r"(b), "r"(c)); return r; }
__device__ __forceinline__ uint4 ldg128(const void* p) { uint4 v; asm volatile("ld.global.nc.v4.u32 {%0, %1, %2, %3}, [%4];" : "=r"(v.x), "=r"(v.y), "=r"(v.z), "=r"(v.w) : "l"(p)); return v; }
__device__ __forceinline__ uint32_t ldg16(const void* p) { uint32_t v; asm volatile("ld.global.nc.u16 %0, [%1];" : "=r"(v) : "l"(p)); return v; }
__device__ __forceinline__ float tanh_ordered(float x) { float y; asm volatile("tanh.approx.f32 %0, %1;" : "=f"(y) : "f"(x)); return y; }
__device__ __forceinline__ void mma16816(float (&d)[4], uint32_t a0, uint32_t a1, uint32_t a2, uint32_t a3, uint32_t b0, uint32_t b1) {
  asm("mma.sync.aligned.m16n8k16.row.col.f32.bf16.bf16.f32 {%0, %1, %2, %3}, {%4, %5, %6, %7}, {%8, %9}, {%0, %1, %2, %3};"
      : "+f"(d[0]), "+f"(d[1]), "+f"(d[2]), "+f"(d[3]) : "r"(a0), "r"(a1), "r"(a2), "r"(a3), "r"(b0), "r"(b1));
}
__device__ __forceinline__ uint32_t hadd2(uint32_t a, uint32_t b) { uint32_t r; asm("add.rn.bf16x2 %0, %1, %2;" : "=r"(r) : "r"(a), "r"(b)); return r; }
__device__ __forceinline__ uint32_t ldg32(const void* p) { uint32_t v; asm volatile("ld.global.nc.L1::no_allocate.u32 %0, [%1];" : "=r"(v) : "l"(p)); return v; }
__device__ __forceinline__ uint2 lds64(uint32_t a) { uint2 v; asm volatile("ld.shared.v2.u32 {%0, %1}, [%2];" : "=r"(v.x), "=r"(v.y) : "r"(a) : "memory"); return v; }
__device__ __forceinline__ uint32_t lds32_if(uint32_t a, uint32_t on) {
  uint32_t v;
  asm volatile("{\n.reg .pred p;\nsetp.ne.u32 p, %2, 0;\n@p ld.shared.u32 %0, [%1];\n}" : "=r"(v) : "r"(a), "r"(on) : "memory");
  return v;
}
__device__ __forceinline__ uint32_t clock_now() { uint32_t t; asm volatile("mov.u32 %0, %%clock;" : "=r"(t)); return t; }
__device__ __forceinline__ uint32_t time_now() { uint32_t t; asm volatile("mov.u32 %0, %%globaltimer_lo;" : "=r"(t)); return t; }
__device__ __forceinline__ void spin_until(uint32_t t0, uint32_t n) { while (clock_now() - t0 < n) {} }
__device__ __forceinline__ uint2 ldg64_if(const void* p, uint32_t on) {
  uint2 v;
  asm volatile("{\n.reg .pred p;\nsetp.ne.u32 p, %3, 0;\n@p ld.global.nc.v2.u32 {%0, %1}, [%2];\n}" : "=r"(v.x), "=r"(v.y) : "l"(p), "r"(on));
  return v;
}
template <class T> __device__ __forceinline__ T pin(T v) { asm volatile("" : "+r"(v)); return v; }
__device__ __forceinline__ void st_async2(uint32_t raddr, uint32_t a, uint32_t b, uint32_t rbar) {
  asm volatile("st.async.weak.shared::cluster.mbarrier::complete_tx::bytes.v2.b32 [%0], {%1, %2}, [%3];" ::"r"(raddr), "r"(a), "r"(b), "r"(rbar) : "memory");
}
__device__ __forceinline__ void bulk_prefetch(const void* src, uint32_t sz, uint64_t pol) {
  asm volatile("cp.async.bulk.prefetch.L2.global.L2::cache_hint [%0], %1, %2;" ::"l"(src), "r"(sz), "l"(pol) : "memory");
}
__device__ __forceinline__ void bulk_wait_read() { asm volatile("cp.async.bulk.wait_group.read 0;" ::: "memory"); }
__device__ __forceinline__ uint32_t shfl_ordered(uint32_t v, int src) { uint32_t r; asm volatile("shfl.sync.idx.b32 %0, %1, %2, 0x1f, 0xffffffff;" : "=r"(r) : "r"(v), "r"(src)); return r; }
__device__ __forceinline__ int chan_pos(int d) {
  return d < 512 ? 72 * (d >> 6) + ((d & 33) | ((d & 6) << 2) | ((d >> 2) & 6)) : 72 * ((d - 512) >> 3) + 64 + (d & 7);
}

struct Ring {
  uint32_t s, ph;
  __device__ __forceinline__ void next() { if (++s == ST) { s = 0; ph ^= 1; } }
};
constexpr int B_FULL = 0, B_GO = 40, B_CFULL = 48, B_SEMPTY = 80, B_ZFULL = 96, B_RFULL = 104, B_UDONE = 120, B_KFULL = 136, B_RAW = 168, B_CVGO = 248, B_PEER = 256, B_G2GO = 264, B_KVGO = 280,
              B_EMPTY = 296, B_G1DONE = 336,
              B_CEMPTY = 344, B_SFULL = 376, B_USTG = 392, B_END = 408;

__device__ __forceinline__ void wait_counter(uint32_t* f, int idx, uint32_t want, uint32_t first, uint32_t nap) {
#pragma unroll 1
  for (uint32_t spins = 0; first != want; spins++) {
    if (nap && spins) __nanosleep(nap);
    first = flag_ld(f, idx);
    if (spins > SPIN_LIMIT) asm volatile("trap;");
  }
  fence_async_global();
}

__device__ __forceinline__ void gate_arrive(uint32_t* f, uint32_t back) {
  asm volatile("red.relaxed.gpu.global.max.u32 [%0], %1;" ::"l"(f + FL_GATE * 32 + 1), "r"(time_now() - back) : "memory");
  flag_add(f, FL_GATE, 1);
}

__device__ __forceinline__ float ln_rinv(float var) {
  float rt, rinv;
  asm("sqrt.approx.ftz.f32 %0, %1;" : "=f"(rt) : "f"(bf_round(bf_round(var) + 1e-5f)));
  asm("rcp.approx.ftz.f32 %0, %1;" : "=f"(rinv) : "f"(bf_round(rt)));
  return rinv;
}
__device__ __forceinline__ uint32_t ln_apply(uint32_t x, const uint4& st) {
  const uint32_t d = hsub2(x, st.x);
  return hfma2(d, st.y, hmul2(d, st.z));
}

__device__ __forceinline__ void polling_done(uint32_t* f, int lane) {
  unsigned old = 0;
  if (lane == 0) asm volatile("atom.relaxed.gpu.global.add.u32 %0, [%1], 1;" : "=r"(old) : "l"(f + FL_DONE * 32) : "memory");
  old = __shfl_sync(0xffffffffu, old, 0);
  if (old == NCTA + NG2 - 1) {
    if (lane < FL_N) *(uint2*)(f + lane * 32) = make_uint2(0u, 0u);
  }
}

struct Pipe { Ring r; uint32_t prev; bool pending; int cnt; };
__device__ __forceinline__ void pipe_drain(Pipe& p, uint32_t bars, bool leader) {
  wg_wait<0>();
  if (leader) mbar_arrive(bars + B_EMPTY + p.prev * 8);
  p.pending = false;
}
template <int TB, int LEAD, int R>
__device__ __forceinline__ void gemm_run(float (&acc)[R], int n, int accumulate, Pipe& p, uint32_t sb, uint32_t pitch, int wg, bool leader) {
  const uint32_t bars = sb + BAR_OFF;
  const uint32_t dA0 = desc_lo(sb + wg * 8192, 8192), dB0 = desc_lo(sb + ASZ, TB ? 128 : 16);
  constexpr int KB_STEP = TB ? 16 : 2;
#pragma unroll 1
  for (int kb = 0; kb < n; kb++) {
    if (LEAD && kb == n - LEAD && wg == 1) { if (TB) pipe_drain(p, bars, leader); named_bar(8, 256); }
    mbar_wait(bars + B_FULL + p.r.s * 8, p.r.ph);
    if (kb == 0 && !accumulate && threadIdx.x == 0) { PROF(21 + TB); PROFC(49 - 2 * TB); }
    const uint32_t dA = dA0 + p.r.s * (pitch >> 4), dB = dB0 + p.r.s * (pitch >> 4);
    wg_fence();
    wgmma_ss<TB>(acc, dA, dB, accumulate | kb);
#pragma unroll
    for (int k = 1; k < 4; k++) wgmma_ss<TB>(acc, dA + k * 128, dB + k * KB_STEP, 1);
    wg_commit();
    wg_wait<1>();
    if (p.pending && leader) mbar_arrive(bars + B_EMPTY + p.prev * 8);
    p.pending = true;
    p.prev = p.r.s;
    p.r.next();
  }
  if (LEAD && wg == 0) named_arrive(8, 256);
}

template <int BROW0, int I0, int I1>
__device__ __forceinline__ void gemm2_part(float (&c)[36], uint32_t sb, uint32_t pitch, int wg) {
  const uint32_t dA0 = desc_lo(sb + wg * 8192, 8192), dB0 = desc_lo(sb + ASZ + BROW0 * 128, 16);
  wg_fence();
#pragma unroll
  for (int i = I0; i < I1; i++) {
    const int step = 68 - LAG + (i >> 2);
    if ((i & 3) == 0 && BROW0 == 0) mbar_wait_u(sb + BAR_OFF + B_FULL + (step % ST) * 8, (step / ST) & 1);
    if (i == 4 * LAG - TURN && BROW0 && wg == 0) named_arrive(7, 256);
    wgmma_ss<0>(c, dA0 + (step % ST) * (pitch >> 4) + (i & 3) * 128, dB0 + (step % ST) * (pitch >> 4) + (i & 3) * 2, 1);
  }
  wg_commit();
}
__device__ __forceinline__ void split_acc(const float (&acc)[72], float (&a)[36], float (&b)[36]) {
#pragma unroll
  for (int i = 0; i < 36; i++) { asm volatile("mov.b32 %0, %1;" : "=f"(a[i]) : "f"(acc[i])); asm volatile("mov.b32 %0, %1;" : "=f"(b[i]) : "f"(acc[36 + i])); }
}
template <int NV, int R, class Slice>
__device__ __forceinline__ void gelu_store(const float (&acc)[R], uint32_t bias0, uint32_t bias1, uint32_t sa, Slice slice) {
  const float hbias0 = 0.5f * bf_lo(pin(bias0)), hbias1 = 0.5f * bf_lo(pin(bias1));
  float hx[2][4], t[2][4], half = 0.5f;
  uint32_t pk[4];
#pragma unroll
  for (int j = 0; j <= NV / 4; j++) {
    if (j < NV / 4) {
      if (j >= 2) half = fmaf(t[j & 1][1], 0.f, 0.5f);
#pragma unroll
      for (int u = 0; u < 4; u++) {
        hx[j & 1][u] = fmaf(acc[4 * j + u], half, (u & 2) ? hbias1 : hbias0);
        t[j & 1][u] = tanh_ordered(hx[j & 1][u] * fmaf(hx[j & 1][u] * hx[j & 1][u], 0.2854192651f, 1.5957691216f));
      }
    }
    if (j > 0) {
      const float *hh = hx[(j - 1) & 1], *tt = t[(j - 1) & 1];
      pk[2 * ((j - 1) & 1)] = pack_bf16(fmaf(hh[0], tt[0], hh[0]), fmaf(hh[1], tt[1], hh[1]));
      pk[2 * ((j - 1) & 1) + 1] = pack_bf16(fmaf(hh[2], tt[2], hh[2]), fmaf(hh[3], tt[3], hh[3]));
      if (!(j & 1)) { stsm4_t(sa + (j - 2) * 1024, pk[0], pk[1], pk[2], pk[3]); slice(j / 2 - 1); }
    }
  }
}
struct Role { int half, kind, g2_m, dt, g1_mt, g1_nt, cs; uint32_t pitch; };
__device__ __forceinline__ Role get_role(const RoleMap& roles) {
  uint32_t b, sm;
  asm volatile("mov.u32 %0, %%ctaid.x;" : "=r"(b));
  asm volatile("mov.u32 %0, %%smid;" : "=r"(sm));
  const uint32_t w = roles.role[(roles.by_sm ? sm : b) >> 1];
  const int half = b & 1, kind = w & 3, m = (w >> 4) & 15, dt = (w >> 2) & 3;
  return Role{half, kind, m * 128, dt, half * 18 + (int)((w >> 8) & 31), (int)(w >> 16), (m * 4 + dt) * 2 + half, kind ? (uint32_t)PITCH_B : (uint32_t)PITCH_S};
}
__device__ __forceinline__ int g2_block(int half, int j) { return half * 36 + (j < 12 ? 2 * j : j < 24 ? 2 * j - 23 : j); }
__device__ __forceinline__ int conv_chan(int cs, int i) { return (3 * (cs >> 5) + (i >> 1)) * 64 + ((2 * cs) & 63) + (i & 1); }
__device__ __forceinline__ uint32_t conv_buf(uint32_t sb, int b) { return sb + (b == 3 ? (36 % ST) * PITCH_S : ST * PITCH_S + b * CBUF); }

__global__ void __cluster_dims__(2, 1, 1) __launch_bounds__(384, 1)
fused_kernel(const __nv_bfloat16* __restrict__ q, Scratch* __restrict__ gs, const __nv_bfloat16* __restrict__ b1,
             const __nv_bfloat16* __restrict__ shiftk, const __nv_bfloat16* __restrict__ ssmk, const __nv_bfloat16* __restrict__ ssmD,
             const __grid_constant__ CUtensorMap tmW1, const __grid_constant__ CUtensorMap tmW2, const __grid_constant__ CUtensorMap tmZ,
             const __grid_constant__ CUtensorMap tmH, const __grid_constant__ CUtensorMap tmK, const __grid_constant__ CUtensorMap tmV,
             const __grid_constant__ CUtensorMap tmKV, const __grid_constant__ CUtensorMap tmKL, const __grid_constant__ RoleMap roles, const __nv_bfloat16* __restrict__ b2,
             __nv_bfloat16* __restrict__ out) {
  const int cta = blockIdx.x;
  const int tid = threadIdx.x;
  if (tid == 288) PROFG(0);

  const uint32_t t_start = clock_now();
  if (tid == 256) { prefetch_map(&tmW1); prefetch_map(&tmH); }
  const int lc = (cta + LNROT) & 127;
  const uint32_t do_ln = cta < 128 && tid < 256;
  const int oct = lc + (tid & 128), ln_row = oct * 8 + ((tid >> 4) & 7), l16 = tid & 15;
  uint2 xr[9];
  if (do_ln && oct >= TN(QLATE)) spin_until(t_start, TN(QDELAY) + TN(QRAMP) * oct / 2);
#pragma unroll
  for (int i = 0; i < 9; i++) xr[i] = ldg64_if(q + (size_t)ln_row * D_ + i * 64 + l16 * 4, do_ln);
  if (tid == 0) PROF(32);
  const int warp = __shfl_sync(0xffffffffu, tid >> 5, 0);
  const uint32_t sb = __shfl_sync(0xffffffffu, (uint32_t)__cvta_generic_to_shared(smem_raw), 0);
  const uint32_t bars = sb + BAR_OFF;
  const int lane = tid & 31;
  const int wg = warp >> 2;
  constexpr int LN_OFF = ST * PITCH_B;

  if (warp < 8 || warp == 11) {
    asm volatile("barrier.cluster.arrive.relaxed.aligned;" ::: "memory");
    const int hq = (lane & 16) >> 3, hb = (lane & 16) + hq;
    float da[3][4] = {};
#pragma unroll
    for (int i = 0; i < 9; i++) mma16816(da[i % 3], xr[i].x, 0x3f803f80u, xr[i].y, 0x3f803f80u, xr[i].x, xr[i].y);
    const float r1 = ((da[0][2] + da[0][3]) + (da[1][2] + da[1][3])) + (da[2][2] + da[2][3]);
    const float r2 = (lane & 4) ? (da[0][1] + da[1][1]) + da[2][1] : (da[0][0] + da[1][0]) + da[2][0];
    const float s1 = __shfl_sync(0xffffffffu, r1, hq) + __shfl_sync(0xffffffffu, r1, hq + 1);
    const float s2 = (__shfl_sync(0xffffffffu, r2, hb) + __shfl_sync(0xffffffffu, r2, hb + 4)) + (__shfl_sync(0xffffffffu, r2, hb + 9) + __shfl_sync(0xffffffffu, r2, hb + 13));
    if (tid == 0) { asm volatile("" ::"f"(s2) : "memory"); PROF(27); }
    const float mean = s1 * (1.f / D_), var = fmaxf(fmaf(-mean, mean, s2 * (1.f / D_)), 0.f);
    const float rinv = ln_rinv(var), rinv2 = ln_rinv(var * rinv * rinv), scale = rinv * rinv2, shift = -bf_round((mean - bf_round(mean)) * rinv) * rinv2;
    const uint32_t m2 = pack_bf16(mean, mean), hi2 = pack_bf16(scale, scale), lo2 = pack_bf16(scale - bf_lo(hi2), scale - bf_lo(hi2)), sh2 = pack_bf16(shift, shift);
    const uint32_t hi1 = pack_bf16(rinv, rinv);
    asm volatile("{\n.reg .pred p;\nsetp.eq.u32 p, %5, 0;\n@p st.shared.v4.u32 [%0], {%1, %2, %3, %4};\n}" ::"r"(sb + LN_OFF + 18432 + tid), "r"(m2), "r"(hi1),
                 "r"(pack_bf16(rinv - bf_lo(hi1), rinv - bf_lo(hi1))), "r"(0u), "r"(tid & 0x10f) : "memory");
    const uint32_t g0 = 4 * (l16 >> 3) + 2 * (l16 & 1), hrow = sb + LN_OFF + ((tid >> 7) & 1) * 9216 + (tid & 0x70);
    const uint32_t hs0 = hrow + g0 * 128 + ((l16 >> 1) & 3) * 4, hs8 = ((hrow + (l16 >> 1) * 1152) ^ ((l16 >> 1) << 4)) + 1024 + (l16 & 1) * 8;
    uint32_t w[18];
#pragma unroll
    for (int i = 0; i < 18; i++) {
      const uint32_t d = hsub2((i & 1) ? xr[i >> 1].y : xr[i >> 1].x, m2);
      asm("max.u32 %0, %1, 1;" : "=r"(w[i]) : "r"(hfma2(d, hi2, hfma2(d, lo2, sh2))));
    }
#pragma unroll
    for (int i = 0; i < 16; i++) {
      const int gi = 9 * (i >> 1) + (i & 1);
      asm volatile("{\n.reg .pred p;\nsetp.ne.u32 p, %2, 0;\n@p st.shared.u32 [%0], %1;\n}" ::"r"((hs0 ^ ((g0 * 16 + (gi & 7) * 16) & 0x70)) + gi * 128), "r"(w[i]), "r"(do_ln) : "memory");
    }
    asm volatile("{\n.reg .pred p;\nsetp.ne.u32 p, %3, 0;\n@p st.shared.v2.u32 [%0], {%1, %2};\n}" ::"r"(hs8), "r"(w[16]), "r"(w[17]), "r"(do_ln) : "memory");
    if (tid == 224) PROF(13);
    fence_async_smem();
    if (warp < 8) named_arrive(wg, 160);
  } else if (warp != 8) {
    spin_until(t_start, TN(W9));
  }

  if (wg == 2) {
    asm volatile("setmaxnreg.dec.sync.aligned.u32 56;");
    auto store_h = [&](int w) {
      named_bar(w, 160);
      if (cta < 128 && elect_one()) {
        tma3d_store(&tmH, ((lc >> 3) + 16 * w) * 72, lc & 7, sb + LN_OFF + w * 9216);
        bulk_s2g(gs->stats + (lc + 128 * w) * 8, sb + LN_OFF + 18432 + w * 128, 128);
        bulk_commit();
      }
    };
    auto publish_h = [&](int w) {
      if (cta < 128 && elect_one()) { bulk_wait_all(); flag_add(gs->flags, FL_H + (w ? 2 : lc >> 6), 1); }
      __syncwarp();
    };
    uint32_t look = 0;
    if (warp == 11) {
      if (lc >= 64) spin_until(t_start, TN(HW));
      store_h(0);
      look = flag_ld(gs->flags, FL_H);
      if (lc < 64) publish_h(0);
      if (lane == 0) PROF(1);
    } else {
      if (elect_one()) {
        if (warp == 8) {
#pragma unroll
          for (int o = 0; o < B_GO; o += 8) mbar_init(bars + o, 1);
        } else if (warp == 9) {
#pragma unroll
          for (int o = B_GO; o < B_RAW + 40; o += 8) mbar_init(bars + o, 1);
        } else {
#pragma unroll
          for (int o = B_RAW + 40; o < B_END; o += 8) mbar_init(bars + o, o < B_EMPTY ? 1 : o < B_CEMPTY ? 2 : 4);
        }
        asm volatile("fence.mbarrier_init.release.cluster;" ::: "memory");
      }
      __syncwarp();
      asm volatile("barrier.cluster.arrive.relaxed.aligned;" ::: "memory");
      if (warp == 9) { prefetch_map(&tmK); prefetch_map(&tmV); prefetch_map(&tmKV); prefetch_map(&tmKL); prefetch_map(&tmW2); prefetch_map(&tmZ); }
      if (tid == 256) PROF(35);
    }
    const Role ro = get_role(roles);
    if (warp != 8) asm volatile("barrier.cluster.wait.aligned;" ::: "memory");
    if (warp == 11) {
      Ring r{0, 1};
      const uint32_t bsz = ro.pitch - ASZ;
      const uint8_t* src = gs->h + ro.g1_nt * bsz + ST * 73728;
      named_bar(10, 64);
#pragma unroll 1
      for (int i = ST; i < 32; i++) {
        if (i == ST || i == 8 || i == 16) wait_counter(gs->flags, FL_H + (i >> 3), i == 16 ? 128u : 64u, look, 0);
        if (i == TN(LK1) || i == TN(LK2)) look = flag_ld(gs->flags, FL_H + (i >> 3) + 1);
        mbar_wait(bars + B_EMPTY + r.s * 8, r.ph ^ 1);
        if (elect_one()) bulk_g2s(sb + r.s * ro.pitch + ASZ, src, bsz, bars + B_FULL + r.s * 8);
        if (i == ST && lane == 0) PROF(25);
        if (i == TN(HS2)) store_h(1);
        if (i == TN(HS2) + 2 || (i == ST && lc >= 64)) publish_h(i != ST);
        if (i == TN(KVGO1) && lane == 0) mbar_arrive(bars + B_KVGO + 8);
        if (i == TN(KVGO) && lane == 0) mbar_arrive(bars + B_KVGO);
        if (i == TN(CVGO) && lane == 0) mbar_arrive(bars + B_CVGO);
        src += 73728;
        r.next();
      }
      if (ro.kind != 2) {
        look = 0;
#pragma unroll 1
        for (int j = 0; j < 36; j++) {
          const uint8_t* su = gs->u + ((size_t)g2_block(ro.half, j) * D_ + ro.dt * 144) * 128;
          if (j == 0 || j == 12 || j == 24) wait_counter(gs->flags, FL_U + ro.half * 3 + j / 12, j == 24 ? 36u : 48u, look, 100);
          if (ro.kind ? j == 4 : j < 2) mbar_wait_u(bars + B_UDONE + (j ? 8 : 0), 0);
          mbar_wait(bars + B_EMPTY + r.s * 8, r.ph ^ 1);
          if (elect_one()) {
            bulk_g2s(sb + r.s * ro.pitch + ASZ, su + (ro.half ^ 1) * 9216, 9216, bars + B_FULL + r.s * 8);
            bulk_g2s(sb + r.s * ro.pitch + ASZ + 9216, su + ro.half * 9216, 9216, bars + B_FULL + r.s * 8);
          }
          if (j == 9 || j == 21) look = flag_ld(gs->flags, FL_U + ro.half * 3 + j / 12 + 1);
          if (j == 0 && lane == 0) PROF(8);
          r.next();
        }
#pragma unroll 1
        for (int o = lane; o < ST * 73728 / 16 / NG2; o += 32) ((uint4*)gs->h)[ro.cs * (ST * 73728 / 16 / NG2) + o] = make_uint4(0u, 0u, 0u, 0u);
      }
      polling_done(gs->flags, lane);
    } else if (warp == 8) {
      const uint64_t pol = stream_policy();
      Ring r{0, 0};
#pragma unroll 1
      for (int i = 0; i < 32; i++) {
        if (i < ST) spin_until(t_start, TN(A0) + i * TN(AD) + (i >= TN(AN) ? TN(AL) : 0));
        if (i == ST) {
          asm volatile("barrier.cluster.wait.aligned;" ::: "memory");
          if (roles.by_sm) {
            uint32_t sm;
            asm volatile("mov.u32 %0, %%smid;" : "=r"(sm));
            if (elect_one()) { mbar_expect(bars + B_PEER, 8); st_async2(mapa(bars + B_END, ro.half ^ 1), sm, sm, mapa(bars + B_PEER, ro.half ^ 1)); }
            mbar_wait_u(bars + B_PEER, 0);
            if ((lds32(bars + B_END) ^ sm) != 1 || sm >= NCTA) asm volatile("trap;");
          }
        }
        if (i >= ST) mbar_wait(bars + B_EMPTY + r.s * 8, r.ph ^ 1);
        if (elect_one()) {
          mbar_expect(bars + B_FULL + r.s * 8, ro.pitch);
          tma_weights(sb + r.s * ro.pitch, &tmW1, i * 64, ro.g1_mt * 2, bars + B_FULL + r.s * 8, pol);
        }
        r.next();
      }
      if (ro.kind != 2) {
#pragma unroll 1
        for (int j = 0; j < 36; j++) {
          if (j == 4 && ro.kind == 0) mbar_wait_u(bars + B_CEMPTY + 24, 0);
          mbar_wait(bars + B_EMPTY + r.s * 8, r.ph ^ 1);
          if (elect_one()) {
            mbar_expect(bars + B_FULL + r.s * 8, PITCH_S);
            tma_weights(sb + r.s * ro.pitch, &tmW2, g2_block(ro.half, j) * 64, ro.g2_m >> 6, bars + B_FULL + r.s * 8, pol);
          }
          r.next();
        }
        if (lane < 2) mbar_expect(bars + B_RFULL + lane * 8, 9216);
        __syncwarp();
        mbar_wait(bars + B_EMPTY + r.s * 8, r.ph ^ 1);
        if (lane == 0) mbar_arrive_cluster(mapa(bars + B_GO, ro.half ^ 1));
      }
      if (lane == 0) PROF(28);
    } else {
      const uint64_t pol = stream_policy();
      {
        const uint32_t hb = (ro.pitch - ASZ) >> 1, raw = bars + B_RAW + (warp - 9) * 40, dst = sb + ASZ + (warp - 9) * hb;
        const uint8_t* src = gs->h + (2 * ro.g1_nt + warp - 9) * hb;
        auto fetch_h = [&](int i) { if (elect_one()) { mbar_expect(raw + i * 8, hb); bulk_g2s(dst + i * ro.pitch, src + i * 73728, hb, raw + i * 8); } };
        int next = 0;
#pragma unroll 1
        for (int i = -1; i < ST; i++) {
          if (i >= 0) {
#pragma unroll 1
            for (uint32_t tries = 0;; tries++) {
              mbar_wait_u(raw + i * 8, tries & 1);
              if (lane == 0 && i == 0) PROF(29 + warp);
              const uint32_t pa = dst + i * ro.pitch + lane * 32 + (lane >> 2) * 4;
              uint32_t m = 1;
#pragma unroll
              for (int j = 0; j < 12; j++) m = min(m, lds32(pa + (j < 9 || ro.kind ? j : 0) * 1024));
              if (__all_sync(0xffffffffu, m)) break;
              if (lane == 0) PROF(26);
              fetch_h(i);
            }
            if (elect_one()) asm volatile("mbarrier.complete_tx.relaxed.cta.shared::cta.b64 [%0], %1;" ::"r"(bars + B_FULL + i * 8), "r"(hb) : "memory");
          }
#pragma unroll 1
          for (const int end = min(next + 2, ST); next < end; next++) {
            if (i < 0) spin_until(t_start, TN(H0) + next * TN(HD));
            fetch_h(next);
            if (next == 0 && tid == 288) PROF(3);
          }
          if (i < 0 && warp == 10) named_arrive(10, 64);
        }
      }
      if (ro.kind == 0) {
        mbar_wait_u(bars + B_KVGO + (warp - 9) * 8, 0);
        const int cs = ro.cs, grp = (cs / 3) * 2 + warp - 9, cb0 = (cs % 3) * 3;
        const uint32_t kin_s = sb + ST * PITCH_S + (warp - 9) * KVW, kout = kin_s + 2 * KVIN, fb = bars + B_KFULL + (warp - 9) * 16;
        auto fetch = [&](int i) {
          if (elect_one()) {
            mbar_expect(fb + (i & 1) * 8, KVIN);
            tma2d_stream(kin_s + (i & 1) * KVIN, &tmK, (cb0 + i) * 64, grp * 32 - 4, fb + (i & 1) * 8, pol);
            tma2d_stream(kin_s + (i & 1) * KVIN + 4608, &tmV, (cb0 + i) * 64, grp * 32 - 1, fb + (i & 1) * 8, pol);
          }
        };
        fetch(0);
        uint4 shk = ldg128(shiftk + (cb0 * 64 + lane * 2) * 4);
        const uint32_t dskip = ldg16(ssmD + conv_chan(cs, lane < NCONV ? lane : 0));
#pragma unroll 1
        for (int i = 0; i < 3; i++) {
          const uint32_t w0 = __byte_perm(shk.x, shk.z, 0x5410), w1 = __byte_perm(shk.x, shk.z, 0x7632);
          const uint32_t w2 = __byte_perm(shk.y, shk.w, 0x5410), w3 = __byte_perm(shk.y, shk.w, 0x7632);
          const uint32_t ka = kin_s + (i & 1) * KVIN + lane * 4;
          mbar_wait_u(fb + (i & 1) * 8, i >> 1);
          if (tid == 288 && i < 2) PROF(30 + i);
          if (i < 2) fetch(i + 1);
          shk = ldg128(i < 2 ? shiftk + ((cb0 + i + 1) * 64 + lane * 2) * 4 : ssmk + (size_t)conv_chan(cs, lane < NCONV ? lane : 0) * S_);
          uint32_t kr[8], vr[8], t1, t2, t3, xp;
          {
            const uint32_t k0 = lds32(ka), k1 = lds32(ka + 128), k2 = lds32(ka + 256), k3 = lds32(ka + 384), v0 = lds32(ka + 4608);
#pragma unroll
            for (int j = 0; j < 8; j++) { kr[j] = lds32(ka + 512 + j * 128); vr[j] = lds32(ka + 4736 + j * 128); }
            xp = hmul2(hfma2(k3, w0, hfma2(k2, w1, hfma2(k1, w2, hmul2(k0, w3)))), v0);
            t1 = hfma2(k3, w1, hfma2(k2, w2, hmul2(k1, w3)));
            t2 = hfma2(k3, w2, hmul2(k2, w3));
            t3 = hmul2(k3, w3);
          }
#pragma unroll 1
          for (int o = 0; o < 4; o++) {
            const uint32_t from = ka + o * 1024, to = kout + (o >> 1) * 5120 + lane * 80 + (o & 1) * 32;
#pragma unroll
            for (int m = 0; m < 8; m += 4) {
              uint32_t x[4];
#pragma unroll
              for (int j = 0; j < 4; j++) {
                x[j] = hmul2(hfma2(kr[m + j], w0, t1), vr[m + j]);
                t1 = hfma2(kr[m + j], w1, t2);
                t2 = hfma2(kr[m + j], w2, t3);
                t3 = hmul2(kr[m + j], w3);
              }
#pragma unroll
              for (int c = 0; c < 2; c++) {
                const uint32_t sel = c ? 0x7632 : 0x5410;
                sts128(to + c * 2560 + m * 4, __byte_perm(x[0], xp, sel), __byte_perm(x[1], x[0], sel), __byte_perm(x[2], x[1], sel), __byte_perm(x[3], x[2], sel));
              }
#pragma unroll
              for (int j = m; j < m + 4; j++) { kr[j] = lds32_if(from + 1536 + j * 128, o < 3); vr[j] = lds32_if(from + 5760 + j * 128, o < 3); }
              xp = x[3];
            }
            if (o & 1) {
              fence_async_smem();
              __syncwarp();
              if (elect_one()) {
                bulk_wait_all();
                if (o == 1 && i) flag_add(gs->flags, FL_KV + i - 1, 1);
                tma4d_store(&tmKV, (cb0 + i) * 32, 0, 2 * grp + (o >> 1), kout + (o >> 1) * 5120);
                bulk_commit();
              }
              __syncwarp();
            }
          }
        }
        shk.x = __byte_perm(pack_bf16(bf_lo(shk.x) + bf_lo(dskip), 0.f), shk.x, 0x7610);
        look = flag_ld(gs->flags, FL_KV + warp - 9);
        if (elect_one()) {
          bulk_wait_all();
          flag_add(gs->flags, FL_KV + 2, 1);
          bulk_prefetch(ssmk + (size_t)conv_chan(cs, 2 * (warp - 9)) * S_, 2 * S_ * 2, pol);
          if (warp == 9) PROFG(2);
        }
        __syncwarp();
#pragma unroll 1
        for (int i = warp == 9 ? 0 : 2; i < (warp == 9 ? 2 : NCONV); i++) {
          const int b = i & 3, d = conv_chan(cs, i);
          const uint32_t base = conv_buf(sb, b), cf = bars + B_CFULL + b * 8;
          if (!(i & 1)) wait_counter(gs->flags, FL_KV + (i >> 1), 192u, i < 4 ? look : 0u, 200);
          if (i == 0 || i == 2) mbar_wait_u(bars + B_CVGO, 0);
          if (i == 0 && lane == 0) PROF(23);
          if (i == 3) {
            mbar_wait_u(bars + B_G1DONE, 0);
            if (elect_one()) bulk_prefetch(ssmk + (size_t)conv_chan(cs, 4) * S_, 2 * S_ * 2, pol);
          }
          if (i >= 4) mbar_wait_u(bars + B_CEMPTY + b * 8, 0);
          if (lane == i) sts128(base + CH_OFF, shk.x, shk.y, shk.z, shk.w);
          if (lane >= 27) sts128(base + (lane >= 29 ? CH_OFF + (lane - 32) * 16 : CT_OFF + (lane - 27) * 16), 0u, 0u, 0u, 0u);
          fence_async_smem();
          __syncwarp();
          if (elect_one()) {
            mbar_expect(cf, 4080 + 128 + 63 * 160);
            bulk_g2s(base + CT_OFF + 32, gs->kv + (size_t)d * KVT, 128, cf);
            asm volatile("cp.async.bulk.tensor.3d.shared::cluster.global.mbarrier::complete_tx::bytes [%0], [%1, {%3, %3, %4}], [%2];"
                         ::"r"(base + CT_OFF + 160), "l"(&tmKL), "r"(cf), "r"(0), "r"(d) : "memory");
            bulk_g2s_stream(base + CH_OFF + 16, ssmk + (size_t)d * S_ + 8, 4080, cf, pol);
          }
        }
      }
      if (warp == 9) {
        if (elect_one()) {
          const uint32_t bsz = ro.pitch - ASZ;
#pragma unroll 1
          for (int w = 0; w < 2; w++) {
            const uint32_t src = sb + (ro.kind ? (w ? (36 % ST) * PITCH_B + ASZ : ST * PITCH_B) : ((32 % ST) + w) * PITCH_S + ASZ);
            mbar_wait_u(bars + B_USTG + w * 8, 0);
            bulk_s2g(gs->u + (size_t)(2 * ro.g1_mt + w) * D_ * 128 + ro.g1_nt * bsz, src, bsz);
            bulk_commit();
            if (ro.kind && w == 0) gate_arrive(gs->flags, TN(GDELAY) - 512);
            bulk_wait_read();
            mbar_arrive(bars + B_UDONE + w * 8);
            bulk_wait_all();
            flag_add(gs->flags, FL_U + ro.half * 3 + (ro.kind ? 2 : w), 1);
            PROFG(5 + 12 * w);
          }
          if (ro.kind == 0) {
#pragma unroll 1
            for (int i = 0; i < NCONV; i++) {
              mbar_wait_u(bars + B_SFULL + (i & 1) * 8, (i >> 1) & 1);
              bulk_s2g(gs->z + (size_t)chan_pos(conv_chan(ro.cs, i)) * S_, sb + CSTG_OFF + (i & 1) * 4096, 4096);
              bulk_commit();
              if (i == NCONV - 3) gate_arrive(gs->flags, 0);
              bulk_wait_read();
              mbar_arrive(bars + B_SEMPTY + (i & 1) * 8);
            }
            bulk_wait_all();
            flag_add(gs->flags, FL_Z, 1);
            PROFG(6);
          }
        }
      } else if (ro.kind != 2) {
        mbar_wait_u(bars + B_UDONE, 0);
        uint2 gate;
#pragma unroll 1
        for (uint32_t spins = 0;; spins++) {
          asm volatile("ld.relaxed.gpu.global.v2.u32 {%0, %1}, [%2];" : "=r"(gate.x), "=r"(gate.y) : "l"(gs->flags + FL_GATE * 32) : "memory");
          if (gate.x == NCTA) break;
          __nanosleep(100);
          if (spins > SPIN_LIMIT) asm volatile("trap;");
        }
        if (lane == 0) PROF(46);
#pragma unroll 1
        for (int w = 0; w < 2; w++) {
          while (time_now() - gate.y < TN(GDELAY) + w * TN(GDELAY1)) {}
          if (lane == 0) mbar_arrive(bars + B_G2GO + w * 8);
          if (lane == 0 && w == 0) PROF(24);
        }
        wait_counter(gs->flags, FL_Z, 96u, 0, 300);
        spin_until(clock_now(), TN(ZDELAY) + TN(ZRAMP) * cta);
        if (elect_one()) {
          mbar_expect(bars + B_ZFULL, 18432);
          tma2d(sb + ST * ro.pitch, &tmZ, ro.g2_m, ro.dt * 144 + ro.half * 72, bars + B_ZFULL);
          tma2d(sb + ST * ro.pitch + 9216, &tmZ, ro.g2_m + 64, ro.dt * 144 + ro.half * 72, bars + B_ZFULL);
          PROFG(7);
        }
        polling_done(gs->flags, lane);
      }
    }
  } else {
    asm volatile("setmaxnreg.inc.sync.aligned.u32 224;");
    const int wi = warp & 3, g = lane >> 2, qd = lane & 3, wt = tid & 127;
    const bool leader = wt == 0;
    Pipe p{{0, 0}, 0, false, 0};
    asm volatile("barrier.cluster.wait.aligned;" ::: "memory");
    int kind;
    {
      const Role ro = get_role(roles);
      kind = ro.kind;
      const int f0 = ro.g1_mt * 128 + wg * 64 + wi * 16 + g;
      uint32_t bias0 = ldg16(b1 + f0), bias1 = ldg16(b1 + f0 + 8);
      const uint32_t so = ((lane >> 4) * 8 + (lane & 7)) * 128 + (((2 * wi + ((lane >> 3) & 1)) ^ (lane & 7)) << 4);
      if (kind) {
        float acc[96];
        gemm_run<1, LEAD_B>(acc, 32, 0, p, sb, PITCH_B, wg, leader);
        pipe_drain(p, bars, leader);
        if (wg) mbar_wait_u(bars + B_EMPTY + (36 % ST) * 8, ((36 / ST) & 1) ^ 1);
        if (leader) PROF(4 + 10 * wg);
        uint32_t sa = sb + (wg ? (36 % ST) * PITCH_B + ASZ : ST * PITCH_B) + so;
#pragma unroll 1
        for (int c = 0; c < 4; c++, sa += 6144) {
          gelu_store<24>(acc, bias0, bias1, sa, [](int) {});
#pragma unroll
          for (int i = 0; i < 72; i++) acc[i] = acc[i + 24];
        }
        fence_async_smem();
        __syncwarp();
        if (lane == 0) mbar_arrive(bars + B_USTG + wg * 8);
        if (leader) PROF(15 + wg);
      } else {
        const int cB = (g >> 1) & 1, cA = g >> 2, b = 2 * wi + (g & 1);
        const uint32_t toff = pin(CT_OFF + (40 * (2 * cA + cB) + 8 + b - 2 * qd) * 4);
        uint32_t a[16][4];
        auto load_a = [&](uint32_t base, int t, uint32_t on) {
          const uint32_t pt = base + toff + (t >> 1) * 1280 + (t & 1) * 64;
          a[t][0] = lds32_if(pt + 32, on); a[t][1] = lds32_if(pt + 672, on); a[t][2] = lds32_if(pt, on); a[t][3] = lds32_if(pt + 640, on);
        };
        {
          float acc[72];
          gemm_run<1, LEAD_S>(acc, 32, 0, p, sb, PITCH_S, wg, leader);
          if (wg == 1) named_arrive(6, 256);
          mbar_wait_u(bars + B_EMPTY + ((32 % ST) + wg) * 8, ((32 / ST) & 1) ^ 1);
          mbar_wait_u(bars + B_CFULL + wg * 8, 0);
          pipe_drain(p, bars, leader);
          if (leader) mbar_arrive(bars + B_G1DONE);
          if (leader) PROF(4 + 10 * wg);
          if (tid == 128) PROFC(48);
          gelu_store<72>(acc, bias0, bias1, sb + ((32 % ST) + wg) * PITCH_S + ASZ + so, [&](int t) { if (t < 8) load_a(conv_buf(sb, wg), t, 1); });
          fence_async_smem();
          __syncwarp();
          if (lane == 0) mbar_arrive(bars + B_USTG + wg * 8);
          if (leader) PROF(15 + wg);
        }
        const int phi = 2 * cA + (qd >> 1) + cB, pp = cB ? (phi & 3) : ((phi + 3) & 3);
        const int srcB = pin(((pp >> 1) << 4) | ((cB ^ 1) << 3) | ((g & 1) << 2) | ((pp & 1) << 1) | (qd & 1));
        const bool pB1 = cB && phi < 4, pB2 = cB && phi == 4;
        const int word = (8 * cB + 2 * (phi & 3) + (qd & 1)) * 8 + b;
        const uint32_t sto = pin(sb + CSTG_OFF + wg * 4096 + (word ^ (((word >> 5) & 3) << 1)) * 4);
#pragma unroll 1
        for (int i = wg; i < NCONV; i += 2) {
          const uint32_t base = conv_buf(sb, i & 3), next = conv_buf(sb, (i + 2) & 3);
          const uint64_t dH = mkdesc(base + CH_OFF, 16, 128, 0);
          float y[8][16];
          named_bar(6 + wg, 256);
          wg_fence();
#pragma unroll
          for (int t = 0; t < 16; t++) {
            if (t >= 8 && t % CFENCE == 0) wg_fence();
            if (t == CTURN) named_arrive(7 - wg, 256);
#pragma unroll
            for (int cb = t >> 1; cb < 8; cb++) {
              wgmma_rs_n32(y[cb], a[t][0], a[t][1], a[t][2], a[t][3], dH + (32 * cb - 32 * (t >> 1) - 2 * (t & 1) - 1), t);
              const int n = 8 * t - (t >> 1) * ((t - 1) >> 1) - (t >> 1) + cb + 1;
              if (n % CPER == 0 && n / CPER <= 8) load_a(base, 7 + n / CPER, 1);
            }
            if (t == 7 && CEARLY) wg_commit();
          }
          wg_commit();
          const bool more = i + 2 < NCONV;
          if (more) mbar_wait_u(bars + B_CFULL + ((i + 2) & 3) * 8, (i + 2) >> 2);
          mbar_wait_u(bars + B_SEMPTY + wg * 8, ((i >> 1) & 1) ^ 1);
          if (CEARLY) wg_wait<1>();
#pragma unroll
          for (int t = 0; t < CEARLY; t++) load_a(next, t, more);
          wg_wait<0>();
          if (lane == 0) mbar_arrive(bars + B_CEMPTY + (i & 3) * 8);
          if (leader) PROF(40 + i);
          uint32_t P[16], Q[16], R[16], o[8];
#pragma unroll
          for (int j = 0; j < 32; j++) {
            if ((j & 3) == 0 && (j >> 2) >= CEARLY) load_a(next, j >> 2, more);
            float v0 = y[j >> 2][4 * (j & 3)], v1 = y[j >> 2][4 * (j & 3) + 1];
            if (j >= 2) { v0 += y[(j - 2) >> 2][4 * ((j - 2) & 3) + 2]; v1 += y[(j - 2) >> 2][4 * ((j - 2) & 3) + 3]; }
            if (j & 1) R[j >> 1] = shfl_ordered(pack_bf16(v0, v1), lane ^ 16);
            else P[j >> 1] = pack_bf16(v0, v1);
          }
#pragma unroll
          for (int m = 0; m < 16; m++) Q[m] = hadd2(P[m], cA ? R[m] : (m ? R[m - 1] : 0u));
#pragma unroll
          for (int m = 0; m < 8; m++) o[m] = shfl_ordered(pB1 ? Q[2 * m] : (pB2 ? (m ? Q[2 * m - 1] : 0u) : Q[2 * m + 1]), srcB);
#pragma unroll
          for (int m = 0; m < 8; m++) sts32(sto + m * 512, hadd2(pB1 ? Q[2 * m + 1] : Q[2 * m], o[m]));
          fence_async_smem();
          __syncwarp();
          if (lane == 0) mbar_arrive(bars + B_SFULL + wg * 8);
          if (leader && i == 5) PROF(53);
        }
        if (wg == 0) named_bar(6, 256);
      }
    }
    if (kind != 2) {
      const Role ro = get_role(roles);
      const uint32_t pitch = ro.pitch;
      const int s0 = ro.g2_m + wg * 64 + wi * 16 + g;
      const size_t go = (size_t)s0 * D_ + ro.dt * 128 + ro.half * 64 + qd * 8, go8 = (size_t)s0 * D_ + 512 + ro.dt * 16 + ro.half * 8 + qd * 2;
      uint32_t x[2][9], sg[2][9];
      float acc[72];
      mbar_wait_u(bars + B_G2GO + wg * 8, 0);
      gemm_run<0, 0>(acc, XAT + 2 * wg, 0, p, sb, pitch, wg, leader);
#pragma unroll
      for (int J = 0; J < 4; J++) {
        const uint4 v = ldg128(q + go + (J & 1) * 8 * D_ + (J >> 1) * 32);
        x[J & 1][4 * (J >> 1)] = v.x; x[J & 1][4 * (J >> 1) + 1] = v.y; x[J & 1][4 * (J >> 1) + 2] = v.z; x[J & 1][4 * (J >> 1) + 3] = v.w;
      }
      x[0][8] = ldg32(q + go8); x[1][8] = ldg32(q + go8 + 8 * D_);
      const uint4 st0 = ld_l2(gs->stats + s0), st1 = ld_l2(gs->stats + s0 + 8);
      const uint32_t braw0 = ldg16(b2 + s0), braw1 = ldg16(b2 + s0 + 8);
      gemm_run<0, 0>(acc, 20 - XAT, 1, p, sb, pitch, wg, leader);
      {
        const int zw = 8 * wi + (g ^ ((((ro.g2_m >> 6) + wg) & 3) << 1));
        const uint32_t za = sb + ST * pitch + wg * 9216 + qd * 256 + (zw & 3) * 4;
        mbar_wait_u(bars + B_ZFULL, 0);
#pragma unroll
        for (int j = 0; j < 9; j++) {
          sg[0][j] = lds32(za + j * 1024 + (((zw >> 2) ^ (2 * qd)) << 4));
          sg[1][j] = lds32(za + j * 1024 + 128 + (((zw >> 2) ^ (2 * qd + 1)) << 4));
        }
      }
      gemm_run<0, 0>(acc, 1, 1, p, sb, pitch, wg, leader);
#pragma unroll
      for (int j = 0; j < 9; j++) {
        const uint32_t z0 = __byte_perm(sg[0][j], sg[1][j], 0x5410), z1 = __byte_perm(sg[0][j], sg[1][j], 0x7632);
        sg[0][j] = hmul2(ln_apply(x[0][j], st0), z0);
        sg[1][j] = hmul2(ln_apply(x[1][j], st1), z1);
        asm volatile("" : "+r"(sg[0][j]), "+r"(sg[1][j]));
      }
      gemm_run<0, SKEW>(acc, 15 - LAG - 2 * wg, 1, p, sb, pitch, wg, leader);
      const uint32_t rbuf = sb + (68 % ST) * pitch + warp * 2304;
      const uint32_t rdst = mapa(rbuf, ro.half ^ 1), rbar = mapa(bars + B_RFULL + wg * 8, ro.half ^ 1);
      pipe_drain(p, bars, leader);
      if (leader) PROF(9 + 10 * wg);
      if (tid == 128) PROFC(50);
      float cs[36], ck[36];
      split_acc(acc, cs, ck);
      gemm2_part<0, 0, 4 * LAG>(cs, sb, pitch, wg);
      if (KPRE) gemm2_part<72, 0, KPRE>(ck, sb, pitch, wg);
      const float hb0 = fmaf(bf_lo(braw0), 0.5f, __uint_as_float(st0.w)), hb1 = fmaf(bf_lo(braw1), 0.5f, __uint_as_float(st1.w));
      mbar_wait(bars + B_GO, 0);
      wg_wait<KPRE ? 1 : 0>();
      if (leader) PROF(54 + wg);
#pragma unroll
      for (int i = 0; i < 5; i++) {
        const float* c = &cs[8 * i];
        const uint32_t v0 = pack_bf16(fmaf(c[0], 0.5f, hb0), fmaf(c[1], 0.5f, hb0)), v1 = pack_bf16(fmaf(c[2], 0.5f, hb1), fmaf(c[3], 0.5f, hb1));
        if (i < 4) st_async4(rdst + i * 512 + lane * 16, v0, v1, pack_bf16(fmaf(c[4], 0.5f, hb0), fmaf(c[5], 0.5f, hb0)), pack_bf16(fmaf(c[6], 0.5f, hb1), fmaf(c[7], 0.5f, hb1)), rbar);
        else st_async2(rdst + 2048 + lane * 8, v0, v1, rbar);
      }
      if (wg == 1) named_bar(7, 256);
      gemm2_part<72, KPRE, 4 * LAG>(ck, sb, pitch, wg);
      uint32_t rp[18];
      mbar_wait(bars + B_RFULL + wg * 8, 0);
#pragma unroll
      for (int m = 0; m < 4; m++) {
        const uint4 v = lds128(rbuf + m * 512 + lane * 16);
        rp[4 * m] = v.x; rp[4 * m + 1] = v.y; rp[4 * m + 2] = v.z; rp[4 * m + 3] = v.w;
      }
      { const uint2 v = lds64(rbuf + 2048 + lane * 8); rp[16] = v.x; rp[17] = v.y; }
      __nv_bfloat16* o = out + go;
      wg_wait<0>();
      if (leader) PROF(10 + 10 * wg);
      float h[2][4], t[2][4], half = 0.5f;
#pragma unroll
      for (int j = 0; j <= 9; j++) {
        if (j < 9) {
          const uint32_t ra = rp[2 * j], rb = rp[2 * j + 1];
          if (j >= 2) half = fmaf(t[j & 1][3], 0.f, 0.5f);
          h[j & 1][0] = fmaf(ck[4 * j], half, bf_lo(ra)); h[j & 1][1] = fmaf(ck[4 * j + 1], half, bf_hi(ra));
          h[j & 1][2] = fmaf(ck[4 * j + 2], half, bf_lo(rb)); h[j & 1][3] = fmaf(ck[4 * j + 3], half, bf_hi(rb));
#pragma unroll
          for (int u = 0; u < 4; u++) t[j & 1][u] = tanh_ordered(h[j & 1][u]);
        }
        if (j > 0) {
          const int k = j - 1;
          const float* hh = h[k & 1];
          const float* tt = t[k & 1];
          x[0][k] = hfma2(sg[0][k], pack_bf16(fmaf(hh[0], tt[0], hh[0]), fmaf(hh[1], tt[1], hh[1])), x[0][k]);
          x[1][k] = hfma2(sg[1][k], pack_bf16(fmaf(hh[2], tt[2], hh[2]), fmaf(hh[3], tt[3], hh[3])), x[1][k]);
          if ((k & 3) == 3) {
            *(uint4*)(o + (k >> 2) * 32) = make_uint4(x[0][k - 3], x[0][k - 2], x[0][k - 1], x[0][k]);
            *(uint4*)(o + 8 * D_ + (k >> 2) * 32) = make_uint4(x[1][k - 3], x[1][k - 2], x[1][k - 1], x[1][k]);
          }
        }
      }
      *(uint32_t*)(out + go8) = x[0][8];
      *(uint32_t*)(out + go8 + 8 * D_) = x[1][8];
      if (leader) PROF(11 + 7 * wg);
      if (tid == 128) PROFC(51);
    }
  }
}

typedef CUresult (*EncodeFn)(CUtensorMap*, CUtensorMapDataType, cuuint32_t, void*, const cuuint64_t*, const cuuint64_t*, const cuuint32_t*,
                             const cuuint32_t*, CUtensorMapInterleave, CUtensorMapSwizzle, CUtensorMapL2promotion, CUtensorMapFloatOOBfill);

uint32_t role_of_pair(int t) {
  int grp, i;
  if (t < 32) { const int j = t & 7; i = t >> 3; grp = j < 6 ? 1 + j : 12 + 2 * (j - 6); }
  else if (t < 60) { const int j = (t - 32) % 7; i = (t - 32) / 7; grp = j < 5 ? 7 + j : 13 + 2 * (j - 5); }
  else if (t < 62) return 2u | (uint32_t)(14 + 3 * (t - 60)) << 8 | 2u << 16;
  else { grp = 0; i = t - 62; }
  if (grp < 12) return (uint32_t)(i << 2 | grp << 4 | grp << 8 | i << 16);
  const int u = (grp & 1) * 4 + i;
  return (uint32_t)(1 | i << 2 | grp << 4 | (12 + 3 * ((grp - 12) >> 1) + u / 3) << 8 | (u % 3) << 16);
}

}

extern "C" void kernel_launch(void* const* d_in, const int* in_sizes, int n_in, void* d_out, int out_size) {
  (void)in_sizes; (void)n_in; (void)out_size;
  EncodeFn enc = nullptr;
  cudaDriverEntryPointQueryResult qr;
  cudaGetDriverEntryPoint("cuTensorMapEncodeTiled", (void**)&enc, cudaEnableDefault, &qr);
  Scratch* gs = nullptr;
  cudaGetSymbolAddress((void**)&gs, g_scratch);
  void *zp = gs->z, *hp = gs->h, *kvp = gs->kv;
  CUtensorMap tmW1, tmW2, tmZ, tmH, tmK, tmV, tmKV, tmKL;
  for (int w = 0; w < 2; w++) {
    cuuint64_t gd[2] = {D_, S_};
    cuuint64_t st[1] = {D_ * 2};
    cuuint32_t bx[2] = {64, w ? 33u : 36u};
    cuuint32_t es[2] = {1, 1};
    enc(w ? &tmV : &tmK, CU_TENSOR_MAP_DATA_TYPE_BFLOAT16, 2, d_in[1 + w], gd, st, bx, es, CU_TENSOR_MAP_INTERLEAVE_NONE, CU_TENSOR_MAP_SWIZZLE_NONE,
        CU_TENSOR_MAP_L2_PROMOTION_L2_128B, CU_TENSOR_MAP_FLOAT_OOB_FILL_NONE);
  }
  {
    cuuint64_t gd[4] = {16, D_ / 2, 2, 128};
    cuuint64_t st[3] = {2 * KVT, KVT, 64};
    cuuint32_t bx[4] = {20, 32, 2, 1};
    cuuint32_t es[4] = {1, 1, 1, 1};
    enc(&tmKV, CU_TENSOR_MAP_DATA_TYPE_UINT32, 4, kvp, gd, st, bx, es, CU_TENSOR_MAP_INTERLEAVE_NONE, CU_TENSOR_MAP_SWIZZLE_NONE,
        CU_TENSOR_MAP_L2_PROMOTION_NONE, CU_TENSOR_MAP_FLOAT_OOB_FILL_NONE);
  }
  {
    cuuint64_t gd[3] = {40, 63, D_};
    cuuint64_t st[2] = {128, KVT};
    cuuint32_t bx[3] = {40, 63, 1};
    cuuint32_t es[3] = {1, 1, 1};
    enc(&tmKL, CU_TENSOR_MAP_DATA_TYPE_UINT32, 3, gs->kv + 96, gd, st, bx, es, CU_TENSOR_MAP_INTERLEAVE_NONE, CU_TENSOR_MAP_SWIZZLE_NONE,
        CU_TENSOR_MAP_L2_PROMOTION_NONE, CU_TENSOR_MAP_FLOAT_OOB_FILL_NONE);
  }
  {
    cuuint64_t gd[3] = {64, 32 * 72, 8};
    cuuint64_t st[2] = {1024, 128};
    cuuint32_t bx[3] = {64, 72, 1};
    cuuint32_t es[3] = {1, 1, 1};
    enc(&tmH, CU_TENSOR_MAP_DATA_TYPE_BFLOAT16, 3, hp, gd, st, bx, es, CU_TENSOR_MAP_INTERLEAVE_NONE, CU_TENSOR_MAP_SWIZZLE_128B,
        CU_TENSOR_MAP_L2_PROMOTION_NONE, CU_TENSOR_MAP_FLOAT_OOB_FILL_NONE);
  }
  for (int w = 0; w < 2; w++) {
    const cuuint64_t M = w ? S_ : F_, K = w ? F_ : S_;
    cuuint64_t gd[3] = {64, K, M / 64};
    cuuint64_t st[2] = {M * 2, 128};
    cuuint32_t bx[3] = {64, 64, 2};
    cuuint32_t es[3] = {1, 1, 1};
    enc(w ? &tmW2 : &tmW1, CU_TENSOR_MAP_DATA_TYPE_BFLOAT16, 3, d_in[w ? 9 : 7], gd, st, bx, es, CU_TENSOR_MAP_INTERLEAVE_NONE,
        CU_TENSOR_MAP_SWIZZLE_128B, CU_TENSOR_MAP_L2_PROMOTION_L2_256B, CU_TENSOR_MAP_FLOAT_OOB_FILL_NONE);
  }
  {
    cuuint64_t gd[2] = {S_, D_};
    cuuint64_t st[1] = {S_ * 2};
    cuuint32_t bx[2] = {64, 72};
    cuuint32_t es[2] = {1, 1};
    enc(&tmZ, CU_TENSOR_MAP_DATA_TYPE_BFLOAT16, 2, zp, gd, st, bx, es, CU_TENSOR_MAP_INTERLEAVE_NONE, CU_TENSOR_MAP_SWIZZLE_128B,
        CU_TENSOR_MAP_L2_PROMOTION_L2_256B, CU_TENSOR_MAP_FLOAT_OOB_FILL_NONE);
  }
  RoleMap roles;
  int dev = 0, sms = 0;
  cudaGetDevice(&dev);
  cudaDeviceGetAttribute(&sms, cudaDevAttrMultiProcessorCount, dev);
  roles.by_sm = sms == NCTA;
  for (int k = 0; k < NCTA / 2; k++) roles.role[k] = role_of_pair(k);
  cudaFuncSetAttribute(fused_kernel, cudaFuncAttributeMaxDynamicSharedMemorySize, SMEM_BYTES);
  fused_kernel<<<NCTA, 384, SMEM_BYTES>>>((const __nv_bfloat16*)d_in[0], gs, (const __nv_bfloat16*)d_in[8], (const __nv_bfloat16*)d_in[3],
                                          (const __nv_bfloat16*)d_in[4], (const __nv_bfloat16*)d_in[5], tmW1, tmW2, tmZ, tmH, tmK, tmV, tmKV, tmKL,
                                          roles, (const __nv_bfloat16*)d_in[10], (__nv_bfloat16*)d_out);
}
```

```cpp
#include <cuda_runtime.h>
#include <cuda_bf16.h>
#include <cuda.h>
#include <stdint.h>

namespace {

constexpr int S_ = 2048, D_ = 576, F_ = 4608;
constexpr int NCTA = 132, NG2 = 128, NCONV = 6;
constexpr int ST = 5, ASZ = 16384, PITCH_S = ASZ + 144 * 128, PITCH_B = ASZ + 192 * 128;
constexpr int KVIN = (36 + 33) * 128, KVW = 2 * KVIN + 64 * 176;
constexpr int BAR_OFF = ST * PITCH_S + 2 * KVW;
constexpr int SMEM_BYTES = BAR_OFF + 512;
constexpr int LNROT = 120;
constexpr int SKEW = 1;
constexpr int LEAD_S = 3, LEAD_B = 2;
constexpr int CTURN = 14, CPER = 4, CEARLY = 0, CFENCE = 8;
constexpr int TURN = 4, KPRE = 2;
constexpr int XAT = 12, GLAG = 2, GDEP = 0, GPRIO = 9;
constexpr int LAG = 4;
constexpr int CBUF = 14464, CH_OFF = 48, CT_OFF = 4192, KVT = 8192;
constexpr int CSTG_OFF = ST * PITCH_S + 3 * CBUF;
constexpr uint32_t SPIN_LIMIT = 1u << 22;

constexpr int FL_H = 0, FL_U = 3, FL_KV = 9, FL_Z = 12, FL_GATE = 13, FL_DONE = 14, FL_N = 15;
struct Scratch {
  uint32_t flags[64 * 32];
  uint4 stats[S_];
  uint8_t h[32 * 72 * 1024];
  uint8_t u[72 * D_ * 128];
  uint8_t kv[D_ * KVT];
  __nv_bfloat16 z[D_ * S_];
};
__device__ __align__(1024) Scratch g_scratch;
extern __shared__ __align__(1024) uint8_t smem_raw[];
#define TUNABLES(X) X(W9, 1200) X(QLATE, 40) X(QDELAY, 400) X(QRAMP, 5) X(A0, 1200) X(AD, 300) X(AN, 2) X(AL, 1500) X(H0, 3100) X(HD, 400) X(HS2, 6) X(HW, 4200) X(LK1, 7) X(LK2, 14) X(KVGO, 8) X(KVGO1, 11) X(CVGO, 31) X(GDELAY, 608) X(GDELAY1, 256) X(ZDELAY, 3000) X(ZRAMP, 40)
#define X(k, v) constexpr int T_##k = v;
TUNABLES(X)
#undef X
#define TN(k) T_##k
struct RoleMap { uint32_t role[NCTA / 2]; uint32_t by_sm; };
#define PROF(i) do {} while (0)
#define PROFG(i) do {} while (0)
#define PROFC(i) do {} while (0)

template<int TB> __device__ __forceinline__ void wgmma_ss(float (&d)[96], uint32_t da, uint32_t db, int sd) {
  asm volatile("{\n.reg .pred p;\n.reg .b64 a, b;\nsetp.ne.b32 p, %98, 0;\nmov.b64 a, {%96, %100};\nmov.b64 b, {%97, %101};\n"
    "wgmma.mma_async.sync.aligned.m64n192k16.f32.bf16.bf16 {%0, %1, %2, %3, %4, %5, %6, %7, %8, %9, %10, %11, %12, %13, %14, %15, %16, %17, %18, %19, %20, %21, %22, %23, %24, %25, %26, %27, %28, %29, %30, %31, %32, %33, %34, %35, %36, %37, %38, %39, %40, %41, %42, %43, %44, %45, %46, %47, %48, %49, %50, %51, %52, %53, %54, %55, %56, %57, %58, %59, %60, %61, %62, %63, %64, %65, %66, %67, %68, %69, %70, %71, %72, %73, %74, %75, %76, %77, %78, %79, %80, %81, %82, %83, %84, %85, %86, %87, %88, %89, %90, %91, %92, %93, %94, %95}, a, b, p, 1, 1, 1, %99;\n}\n"
    : "+f"(d[0]), "+f"(d[1]), "+f"(d[2]), "+f"(d[3]), "+f"(d[4]), "+f"(d[5]), "+f"(d[6]), "+f"(d[7]), "+f"(d[8]), "+f"(d[9]), "+f"(d[10]), "+f"(d[11]), "+f"(d[12]), "+f"(d[13]), "+f"(d[14]), "+f"(d[15]), "+f"(d[16]), "+f"(d[17]), "+f"(d[18]), "+f"(d[19]), "+f"(d[20]), "+f"(d[21]), "+f"(d[22]), "+f"(d[23]), "+f"(d[24]), "+f"(d[25]), "+f"(d[26]), "+f"(d[27]), "+f"(d[28]), "+f"(d[29]), "+f"(d[30]), "+f"(d[31]), "+f"(d[32]), "+f"(d[33]), "+f"(d[34]), "+f"(d[35]), "+f"(d[36]), "+f"(d[37]), "+f"(d[38]), "+f"(d[39]), "+f"(d[40]), "+f"(d[41]), "+f"(d[42]), "+f"(d[43]), "+f"(d[44]), "+f"(d[45]), "+f"(d[46]), "+f"(d[47]), "+f"(d[48]), "+f"(d[49]), "+f"(d[50]), "+f"(d[51]), "+f"(d[52]), "+f"(d[53]), "+f"(d[54]), "+f"(d[55]), "+f"(d[56]), "+f"(d[57]), "+f"(d[58]), "+f"(d[59]), "+f"(d[60]), "+f"(d[61]), "+f"(d[62]), "+f"(d[63]), "+f"(d[64]), "+f"(d[65]), "+f"(d[66]), "+f"(d[67]), "+f"(d[68]), "+f"(d[69]), "+f"(d[70]), "+f"(d[71]), "+f"(d[72]), "+f"(d[73]), "+f"(d[74]), "+f"(d[75]), "+f"(d[76]), "+f"(d[77]), "+f"(d[78]), "+f"(d[79]), "+f"(d[80]), "+f"(d[81]), "+f"(d[82]), "+f"(d[83]), "+f"(d[84]), "+f"(d[85]), "+f"(d[86]), "+f"(d[87]), "+f"(d[88]), "+f"(d[89]), "+f"(d[90]), "+f"(d[91]), "+f"(d[92]), "+f"(d[93]), "+f"(d[94]), "+f"(d[95])
    : "r"(da), "r"(db), "r"(sd), "n"(TB), "r"(0x40000040u), "r"(TB ? 0x40u : 0x40000040u));
}
template<int TB> __device__ __forceinline__ void wgmma_ss(float (&d)[72], uint32_t da, uint32_t db, int sd) {
  asm volatile("{\n.reg .pred p;\n.reg .b64 a, b;\nsetp.ne.b32 p, %74, 0;\nmov.b64 a, {%72, %76};\nmov.b64 b, {%73, %77};\n"
    "wgmma.mma_async.sync.aligned.m64n144k16.f32.bf16.bf16 {%0, %1, %2, %3, %4, %5, %6, %7, %8, %9, %10, %11, %12, %13, %14, %15, %16, %17, %18, %19, %20, %21, %22, %23, %24, %25, %26, %27, %28, %29, %30, %31, %32, %33, %34, %35, %36, %37, %38, %39, %40, %41, %42, %43, %44, %45, %46, %47, %48, %49, %50, %51, %52, %53, %54, %55, %56, %57, %58, %59, %60, %61, %62, %63, %64, %65, %66, %67, %68, %69, %70, %71}, a, b, p, 1, 1, 1, %75;\n}\n"
    : "+f"(d[0]), "+f"(d[1]), "+f"(d[2]), "+f"(d[3]), "+f"(d[4]), "+f"(d[5]), "+f"(d[6]), "+f"(d[7]), "+f"(d[8]), "+f"(d[9]), "+f"(d[10]), "+f"(d[11]), "+f"(d[12]), "+f"(d[13]), "+f"(d[14]), "+f"(d[15]), "+f"(d[16]), "+f"(d[17]), "+f"(d[18]), "+f"(d[19]), "+f"(d[20]), "+f"(d[21]), "+f"(d[22]), "+f"(d[23]), "+f"(d[24]), "+f"(d[25]), "+f"(d[26]), "+f"(d[27]), "+f"(d[28]), "+f"(d[29]), "+f"(d[30]), "+f"(d[31]), "+f"(d[32]), "+f"(d[33]), "+f"(d[34]), "+f"(d[35]), "+f"(d[36]), "+f"(d[37]), "+f"(d[38]), "+f"(d[39]), "+f"(d[40]), "+f"(d[41]), "+f"(d[42]), "+f"(d[43]), "+f"(d[44]), "+f"(d[45]), "+f"(d[46]), "+f"(d[47]), "+f"(d[48]), "+f"(d[49]), "+f"(d[50]), "+f"(d[51]), "+f"(d[52]), "+f"(d[53]), "+f"(d[54]), "+f"(d[55]), "+f"(d[56]), "+f"(d[57]), "+f"(d[58]), "+f"(d[59]), "+f"(d[60]), "+f"(d[61]), "+f"(d[62]), "+f"(d[63]), "+f"(d[64]), "+f"(d[65]), "+f"(d[66]), "+f"(d[67]), "+f"(d[68]), "+f"(d[69]), "+f"(d[70]), "+f"(d[71])
    : "r"(da), "r"(db), "r"(sd), "n"(TB), "r"(0x40000040u), "r"(TB ? 0x40u : 0x40000040u));
}
template<int TB> __device__ __forceinline__ void wgmma_ss(float (&d)[36], uint32_t da, uint32_t db, int sd) {
  asm volatile("{\n.reg .pred p;\n.reg .b64 a, b;\nsetp.ne.b32 p, %38, 0;\nmov.b64 a, {%36, %40};\nmov.b64 b, {%37, %41};\n"
    "wgmma.mma_async.sync.aligned.m64n72k16.f32.bf16.bf16 {%0, %1, %2, %3, %4, %5, %6, %7, %8, %9, %10, %11, %12, %13, %14, %15, %16, %17, %18, %19, %20, %21, %22, %23, %24, %25, %26, %27, %28, %29, %30, %31, %32, %33, %34, %35}, a, b, p, 1, 1, 1, %39;\n}\n"
    : "+f"(d[0]), "+f"(d[1]), "+f"(d[2]), "+f"(d[3]), "+f"(d[4]), "+f"(d[5]), "+f"(d[6]), "+f"(d[7]), "+f"(d[8]), "+f"(d[9]), "+f"(d[10]), "+f"(d[11]), "+f"(d[12]), "+f"(d[13]), "+f"(d[14]), "+f"(d[15]), "+f"(d[16]), "+f"(d[17]), "+f"(d[18]), "+f"(d[19]), "+f"(d[20]), "+f"(d[21]), "+f"(d[22]), "+f"(d[23]), "+f"(d[24]), "+f"(d[25]), "+f"(d[26]), "+f"(d[27]), "+f"(d[28]), "+f"(d[29]), "+f"(d[30]), "+f"(d[31]), "+f"(d[32]), "+f"(d[33]), "+f"(d[34]), "+f"(d[35])
    : "r"(da), "r"(db), "r"(sd), "n"(TB), "r"(0x40000040u), "r"(TB ? 0x40u : 0x40000040u));
}
__device__ __forceinline__ void wgmma_rs_n32(float (&d)[16], uint32_t a0, uint32_t a1, uint32_t a2, uint32_t a3, uint64_t db, int sd) {
  asm volatile("{\n.reg .pred p;\nsetp.ne.b32 p, %21, 0;\n"
    "wgmma.mma_async.sync.aligned.m64n32k16.f32.bf16.bf16 {%0, %1, %2, %3, %4, %5, %6, %7, %8, %9, %10, %11, %12, %13, %14, %15}, {%16, %17, %18, %19}, %20, p, 1, 1, 0;\n}\n"
    : "+f"(d[0]), "+f"(d[1]), "+f"(d[2]), "+f"(d[3]), "+f"(d[4]), "+f"(d[5]), "+f"(d[6]), "+f"(d[7]), "+f"(d[8]), "+f"(d[9]), "+f"(d[10]), "+f"(d[11]), "+f"(d[12]), "+f"(d[13]), "+f"(d[14]), "+f"(d[15])
    : "r"(a0), "r"(a1), "r"(a2), "r"(a3), "l"(db), "r"(sd));
}

__device__ __forceinline__ void wg_fence() { asm volatile("wgmma.fence.sync.aligned;" ::: "memory"); }
__device__ __forceinline__ void wg_commit() { asm volatile("wgmma.commit_group.sync.aligned;" ::: "memory"); }
template <int n> __device__ __forceinline__ void wg_wait() { asm volatile("wgmma.wait_group.sync.aligned %0;" ::"n"(n) : "memory"); }
__device__ __forceinline__ uint64_t mkdesc(uint32_t addr, uint32_t lbo, uint32_t sbo, uint32_t sw) {
  return (uint64_t)((addr & 0x3FFFF) >> 4) | ((uint64_t)(lbo >> 4) << 16) | ((uint64_t)(sbo >> 4) << 32) | ((uint64_t)sw << 62);
}
__device__ __forceinline__ void mbar_init(uint32_t a, int c) { asm volatile("mbarrier.init.shared::cta.b64 [%0], %1;" ::"r"(a), "r"(c)); }
__device__ __forceinline__ void mbar_expect(uint32_t a, uint32_t b) { asm volatile("mbarrier.arrive.expect_tx.shared::cta.b64 _, [%0], %1;" ::"r"(a), "r"(b) : "memory"); }
__device__ __forceinline__ void mbar_arrive(uint32_t a) { asm volatile("mbarrier.arrive.shared::cta.b64 _, [%0];" ::"r"(a) : "memory"); }
__device__ __forceinline__ void mbar_arrive_cluster(uint32_t raddr) { asm volatile("mbarrier.arrive.shared::cluster.b64 _, [%0];" ::"r"(raddr) : "memory"); }
__device__ __forceinline__ uint32_t mapa(uint32_t a, uint32_t cta) { uint32_t r; asm("mapa.shared::cluster.u32 %0, %1, %2;" : "=r"(r) : "r"(a), "r"(cta)); return r; }
__device__ __forceinline__ void mbar_wait(uint32_t a, uint32_t ph) {
  asm volatile(
      "{\n.reg .pred p;\n.reg .u32 c;\nmov.u32 c, 0;\n"
      "WAIT_LOOP:\nmbarrier.try_wait.parity.shared::cta.b64 p, [%0], %1;\n@p bra WAIT_DONE;\n"
      "add.u32 c, c, 1;\nsetp.lt.u32 p, c, %2;\n@p bra WAIT_LOOP;\ntrap;\nWAIT_DONE:\n}" ::"r"(a), "r"(ph), "n"(SPIN_LIMIT) : "memory");
}
__device__ __forceinline__ void mbar_wait_u(uint32_t a, uint32_t ph) {
  asm volatile("{\n.reg .pred p;\nWAIT_LOOP:\nmbarrier.try_wait.parity.shared::cta.b64 p, [%0], %1;\n@!p bra WAIT_LOOP;\n}" ::"r"(a), "r"(ph) : "memory");
}
__device__ __forceinline__ uint32_t desc_lo(uint32_t addr, uint32_t lbo) { return ((addr & 0x3FFFF) >> 4) | ((lbo >> 4) << 16); }
__device__ __forceinline__ void tma2d(uint32_t dst, const CUtensorMap* m, int c0, int c1, uint32_t bar) {
  asm volatile("cp.async.bulk.tensor.2d.shared::cluster.global.mbarrier::complete_tx::bytes [%0], [%1, {%3, %4}], [%2];" ::"r"(dst), "l"(m), "r"(bar), "r"(c0), "r"(c1) : "memory");
}
__device__ __forceinline__ void bulk_g2s(uint32_t dst, const void* src, uint32_t sz, uint32_t bar) {
  asm volatile("cp.async.bulk.shared::cluster.global.mbarrier::complete_tx::bytes [%0], [%1], %2, [%3];" ::"r"(dst), "l"(src), "r"(sz), "r"(bar) : "memory");
}
__device__ __forceinline__ void bulk_s2g(void* dst, uint32_t src, uint32_t sz) {
  asm volatile("cp.async.bulk.global.shared::cta.bulk_group [%0], [%1], %2;" ::"l"(dst), "r"(src), "r"(sz) : "memory");
}
__device__ __forceinline__ uint64_t stream_policy() {
  uint64_t p;
  asm volatile("createpolicy.fractional.L2::evict_first.b64 %0, 1.0;" : "=l"(p));
  return p;
}
__device__ __forceinline__ void tma_weights(uint32_t dst, const CUtensorMap* m, int k0, int mchunk, uint32_t bar, uint64_t pol) {
  asm volatile("cp.async.bulk.tensor.3d.shared::cluster.global.mbarrier::complete_tx::bytes.L2::cache_hint [%0], [%1, {%6, %3, %4}], [%2], %5;"
               ::"r"(dst), "l"(m), "r"(bar), "r"(k0), "r"(mchunk), "l"(pol), "r"(0) : "memory");
}
__device__ __forceinline__ bool elect_one() {
  uint32_t p;
  asm volatile("{\n.reg .pred P;\nelect.sync _|P, 0xffffffff;\nselp.u32 %0, 1, 0, P;\n}" : "=r"(p));
  return p;
}
__device__ __forceinline__ void bulk_g2s_stream(uint32_t dst, const void* src, uint32_t sz, uint32_t bar, uint64_t pol) {
  asm volatile("cp.async.bulk.shared::cluster.global.mbarrier::complete_tx::bytes.L2::cache_hint [%0], [%1], %2, [%3], %4;"
               ::"r"(dst), "l"(src), "r"(sz), "r"(bar), "l"(pol) : "memory");
}
__device__ __forceinline__ void tma3d_store(const CUtensorMap* m, int c1, int c2, uint32_t src) {
  asm volatile("cp.async.bulk.tensor.3d.global.shared::cta.bulk_group [%0, {%4, %2, %3}], [%1];" ::"l"(m), "r"(src), "r"(c1), "r"(c2), "r"(0) : "memory");
}
__device__ __forceinline__ void tma2d_stream(uint32_t dst, const CUtensorMap* m, int c0, int c1, uint32_t bar, uint64_t pol) {
  asm volatile("cp.async.bulk.tensor.2d.shared::cluster.global.mbarrier::complete_tx::bytes.L2::cache_hint [%0], [%1, {%3, %4}], [%2], %5;"
               ::"r"(dst), "l"(m), "r"(bar), "r"(c0), "r"(c1), "l"(pol) : "memory");
}
__device__ __forceinline__ void tma4d_store(const CUtensorMap* m, int c1, int c2, int c3, uint32_t src) {
  asm volatile("cp.async.bulk.tensor.4d.global.shared::cta.bulk_group [%0, {%5, %2, %3, %4}], [%1];" ::"l"(m), "r"(src), "r"(c1), "r"(c2), "r"(c3), "r"(0) : "memory");
}
__device__ __forceinline__ void bulk_commit() { asm volatile("cp.async.bulk.commit_group;" ::: "memory"); }
__device__ __forceinline__ void bulk_wait_all() { asm volatile("cp.async.bulk.wait_group 0;" ::: "memory"); }
__device__ __forceinline__ void fence_async_smem() { asm volatile("fence.proxy.async.shared::cta;" ::: "memory"); }
__device__ __forceinline__ void fence_async_global() { asm volatile("fence.proxy.async.global;" ::: "memory"); }
__device__ __forceinline__ void named_bar(int id, int n) { asm volatile("bar.sync %0, %1;" ::"r"(id), "r"(n) : "memory"); }
__device__ __forceinline__ void named_arrive(int id, int n) { asm volatile("bar.arrive %0, %1;" ::"r"(id), "r"(n) : "memory"); }
__device__ __forceinline__ void flag_add(uint32_t* f, int i, uint32_t v) { asm volatile("red.relaxed.gpu.global.add.u32 [%0], %1;" ::"l"(f + i * 32), "r"(v) : "memory"); }
__device__ __forceinline__ uint32_t flag_ld(uint32_t* f, int i) { uint32_t v; asm volatile("ld.relaxed.gpu.global.u32 %0, [%1];" : "=r"(v) : "l"(f + i * 32) : "memory"); return v; }
__device__ __forceinline__ void prefetch_map(const CUtensorMap* m) { asm volatile("prefetch.tensormap [%0];" ::"l"(m) : "memory"); }
__device__ __forceinline__ void stsm4_t(uint32_t a, uint32_t r0, uint32_t r1, uint32_t r2, uint32_t r3) {
  asm volatile("stmatrix.sync.aligned.m8n8.x4.trans.shared.b16 [%0], {%1, %2, %3, %4};" ::"r"(a), "r"(r0), "r"(r1), "r"(r2), "r"(r3) : "memory");
}
__device__ __forceinline__ uint32_t lds32(uint32_t a) { uint32_t v; asm volatile("ld.shared.u32 %0, [%1];" : "=r"(v) : "r"(a) : "memory"); return v; }
__device__ __forceinline__ void sts32(uint32_t a, uint32_t v) { asm volatile("st.shared.u32 [%0], %1;" ::"r"(a), "r"(v) : "memory"); }
__device__ __forceinline__ uint4 ld_l2(const uint4* p) { uint4 v; asm volatile("ld.relaxed.gpu.global.v4.u32 {%0, %1, %2, %3}, [%4];" : "=r"(v.x), "=r"(v.y), "=r"(v.z), "=r"(v.w) : "l"(p) : "memory"); return v; }
__device__ __forceinline__ void sts128(uint32_t a, uint32_t x, uint32_t y, uint32_t z, uint32_t w) { asm volatile("st.shared.v4.u32 [%0], {%1, %2, %3, %4};" ::"r"(a), "r"(x), "r"(y), "r"(z), "r"(w) : "memory"); }
__device__ __forceinline__ uint4 lds128(uint32_t a) { uint4 v; asm volatile("ld.shared.v4.u32 {%0, %1, %2, %3}, [%4];" : "=r"(v.x), "=r"(v.y), "=r"(v.z), "=r"(v.w) : "r"(a) : "memory"); return v; }
__device__ __forceinline__ void st_async4(uint32_t raddr, uint32_t a, uint32_t b, uint32_t c, uint32_t d, uint32_t rbar) {
  asm volatile("st.async.weak.shared::cluster.mbarrier::complete_tx::bytes.v4.b32 [%0], {%1, %2, %3, %4}, [%5];" ::"r"(raddr), "r"(a), "r"(b), "r"(c), "r"(d), "r"(rbar) : "memory");
}
__device__ __forceinline__ uint32_t pack_bf16(float lo, float hi) { uint32_t r; asm("cvt.rn.bf16x2.f32 %0, %1, %2;" : "=r"(r) : "f"(hi), "f"(lo)); return r; }
__device__ __forceinline__ float bf_lo(uint32_t v) { return __uint_as_float(v << 16); }
__device__ __forceinline__ float bf_hi(uint32_t v) { return __uint_as_float(v & 0xffff0000u); }
__device__ __forceinline__ float bf_round(float x) { return bf_lo(pack_bf16(x, 0.f)); }
__device__ __forceinline__ uint32_t hmul2(uint32_t a, uint32_t b) { uint32_t r; asm("mul.rn.bf16x2 %0, %1, %2;" : "=r"(r) : "r"(a), "r"(b)); return r; }
__device__ __forceinline__ uint32_t hsub2(uint32_t a, uint32_t b) { uint32_t r; asm("sub.rn.bf16x2 %0, %1, %2;" : "=r"(r) : "r"(a), "r"(b)); return r; }
__device__ __forceinline__ uint32_t hfma2(uint32_t a, uint32_t b, uint32_t c) { uint32_t r; asm("fma.rn.bf16x2 %0, %1, %2, %3;" : "=r"(r) : "r"(a), "r"(b), "r"(c)); return r; }
__device__ __forceinline__ uint4 ldg128(const void* p) { uint4 v; asm volatile("ld.global.nc.v4.u32 {%0, %1, %2, %3}, [%4];" : "=r"(v.x), "=r"(v.y), "=r"(v.z), "=r"(v.w) : "l"(p)); return v; }
__device__ __forceinline__ uint32_t ldg16(const void* p) { uint32_t v; asm volatile("ld.global.nc.u16 %0, [%1];" : "=r"(v) : "l"(p)); return v; }
__device__ __forceinline__ float tanh_ordered(float x) { float y; asm volatile("tanh.approx.f32 %0, %1;" : "=f"(y) : "f"(x)); return y; }
__device__ __forceinline__ uint32_t tanh2_ordered(uint32_t x) { uint32_t y; asm volatile("tanh.approx.bf16x2 %0, %1;" : "=r"(y) : "r"(x)); return y; }
__device__ __forceinline__ void mma16816(float (&d)[4], uint32_t a0, uint32_t a1, uint32_t a2, uint32_t a3, uint32_t b0, uint32_t b1) {
  asm("mma.sync.aligned.m16n8k16.row.col.f32.bf16.bf16.f32 {%0, %1, %2, %3}, {%4, %5, %6, %7}, {%8, %9}, {%0, %1, %2, %3};"
      : "+f"(d[0]), "+f"(d[1]), "+f"(d[2]), "+f"(d[3]) : "r"(a0), "r"(a1), "r"(a2), "r"(a3), "r"(b0), "r"(b1));
}
__device__ __forceinline__ uint32_t hadd2(uint32_t a, uint32_t b) { uint32_t r; asm("add.rn.bf16x2 %0, %1, %2;" : "=r"(r) : "r"(a), "r"(b)); return r; }
__device__ __forceinline__ uint32_t ldg32(const void* p) { uint32_t v; asm volatile("ld.global.nc.L1::no_allocate.u32 %0, [%1];" : "=r"(v) : "l"(p)); return v; }
__device__ __forceinline__ uint2 lds64(uint32_t a) { uint2 v; asm volatile("ld.shared.v2.u32 {%0, %1}, [%2];" : "=r"(v.x), "=r"(v.y) : "r"(a) : "memory"); return v; }
__device__ __forceinline__ uint32_t lds32_if(uint32_t a, uint32_t on) {
  uint32_t v;
  asm volatile("{\n.reg .pred p;\nsetp.ne.u32 p, %2, 0;\n@p ld.shared.u32 %0, [%1];\n}" : "=r"(v) : "r"(a), "r"(on) : "memory");
  return v;
}
__device__ __forceinline__ uint32_t clock_now() { uint32_t t; asm volatile("mov.u32 %0, %%clock;" : "=r"(t)); return t; }
__device__ __forceinline__ uint32_t time_now() { uint32_t t; asm volatile("mov.u32 %0, %%globaltimer_lo;" : "=r"(t)); return t; }
__device__ __forceinline__ void spin_until(uint32_t t0, uint32_t n) { while (clock_now() - t0 < n) {} }
__device__ __forceinline__ uint2 ldg64_if(const void* p, uint32_t on) {
  uint2 v;
  asm volatile("{\n.reg .pred p;\nsetp.ne.u32 p, %3, 0;\n@p ld.global.nc.v2.u32 {%0, %1}, [%2];\n}" : "=r"(v.x), "=r"(v.y) : "l"(p), "r"(on));
  return v;
}
template <class T> __device__ __forceinline__ T pin(T v) { asm volatile("" : "+r"(v)); return v; }
__device__ __forceinline__ void st_async2(uint32_t raddr, uint32_t a, uint32_t b, uint32_t rbar) {
  asm volatile("st.async.weak.shared::cluster.mbarrier::complete_tx::bytes.v2.b32 [%0], {%1, %2}, [%3];" ::"r"(raddr), "r"(a), "r"(b), "r"(rbar) : "memory");
}
__device__ __forceinline__ void bulk_prefetch(const void* src, uint32_t sz, uint64_t pol) {
  asm volatile("cp.async.bulk.prefetch.L2.global.L2::cache_hint [%0], %1, %2;" ::"l"(src), "r"(sz), "l"(pol) : "memory");
}
__device__ __forceinline__ void bulk_wait_read() { asm volatile("cp.async.bulk.wait_group.read 0;" ::: "memory"); }
__device__ __forceinline__ uint32_t shfl_ordered(uint32_t v, int src) { uint32_t r; asm volatile("shfl.sync.idx.b32 %0, %1, %2, 0x1f, 0xffffffff;" : "=r"(r) : "r"(v), "r"(src)); return r; }
__device__ __forceinline__ int chan_pos(int d) {
  return d < 512 ? 72 * (d >> 6) + ((d & 33) | ((d & 6) << 2) | ((d >> 2) & 6)) : 72 * ((d - 512) >> 3) + 64 + (d & 7);
}

struct Ring {
  uint32_t s, ph;
  __device__ __forceinline__ void next() { if (++s == ST) { s = 0; ph ^= 1; } }
};
constexpr int B_FULL = 0, B_GO = 40, B_CFULL = 48, B_SEMPTY = 80, B_ZFULL = 96, B_RFULL = 104, B_UDONE = 120, B_KFULL = 136, B_RAW = 168, B_CVGO = 248, B_PEER = 256, B_G2GO = 264, B_KVGO = 280,
              B_EMPTY = 296, B_G1DONE = 336,
              B_CEMPTY = 344, B_SFULL = 376, B_USTG = 392, B_END = 408;

__device__ __forceinline__ void wait_counter(uint32_t* f, int idx, uint32_t want, uint32_t first, uint32_t nap) {
#pragma unroll 1
  for (uint32_t spins = 0; first != want; spins++) {
    if (nap && spins) __nanosleep(nap);
    first = flag_ld(f, idx);
    if (spins > SPIN_LIMIT) asm volatile("trap;");
  }
  fence_async_global();
}

__device__ __forceinline__ void gate_arrive(uint32_t* f, uint32_t back) {
  asm volatile("red.relaxed.gpu.global.max.u32 [%0], %1;" ::"l"(f + FL_GATE * 32 + 1), "r"(time_now() - back) : "memory");
  flag_add(f, FL_GATE, 1);
}

__device__ __forceinline__ float ln_rinv(float var) {
  float rt, rinv;
  asm("sqrt.approx.ftz.f32 %0, %1;" : "=f"(rt) : "f"(bf_round(bf_round(var) + 1e-5f)));
  asm("rcp.approx.ftz.f32 %0, %1;" : "=f"(rinv) : "f"(bf_round(rt)));
  return rinv;
}
__device__ __forceinline__ uint32_t ln_apply(uint32_t x, const uint4& st) {
  const uint32_t d = hsub2(x, st.x);
  return hfma2(d, st.y, hmul2(d, st.z));
}

__device__ __forceinline__ void polling_done(uint32_t* f, int lane) {
  unsigned old = 0;
  if (lane == 0) asm volatile("atom.relaxed.gpu.global.add.u32 %0, [%1], 1;" : "=r"(old) : "l"(f + FL_DONE * 32) : "memory");
  old = __shfl_sync(0xffffffffu, old, 0);
  if (old == NCTA + NG2 - 1) {
    if (lane < FL_N) *(uint2*)(f + lane * 32) = make_uint2(0u, 0u);
  }
}

struct Pipe { Ring r; uint32_t prev; bool pending; int cnt; };
__device__ __forceinline__ void pipe_drain(Pipe& p, uint32_t bars, bool leader) {
  wg_wait<0>();
  if (leader) mbar_arrive(bars + B_EMPTY + p.prev * 8);
  p.pending = false;
}
template <int TB, int LEAD, int R>
__device__ __forceinline__ void gemm_run(float (&acc)[R], int n, int accumulate, Pipe& p, uint32_t sb, uint32_t pitch, int wg, bool leader) {
  const uint32_t bars = sb + BAR_OFF;
  const uint32_t dA0 = desc_lo(sb + wg * 8192, 8192), dB0 = desc_lo(sb + ASZ, TB ? 128 : 16);
  constexpr int KB_STEP = TB ? 16 : 2;
#pragma unroll 1
  for (int kb = 0; kb < n; kb++) {
    if (LEAD && kb == n - LEAD && wg == 1) { if (TB) pipe_drain(p, bars, leader); named_bar(8, 256); }
    mbar_wait(bars + B_FULL + p.r.s * 8, p.r.ph);
    if (kb == 0 && !accumulate && threadIdx.x == 0) { PROF(21 + TB); PROFC(49 - 2 * TB); }
    const uint32_t dA = dA0 + p.r.s * (pitch >> 4), dB = dB0 + p.r.s * (pitch >> 4);
    wg_fence();
    wgmma_ss<TB>(acc, dA, dB, accumulate | kb);
#pragma unroll
    for (int k = 1; k < 4; k++) wgmma_ss<TB>(acc, dA + k * 128, dB + k * KB_STEP, 1);
    wg_commit();
    wg_wait<1>();
    if (p.pending && leader) mbar_arrive(bars + B_EMPTY + p.prev * 8);
    p.pending = true;
    p.prev = p.r.s;
    p.r.next();
  }
  if (LEAD && wg == 0) named_arrive(8, 256);
}

template <int BROW0, int I0, int I1>
__device__ __forceinline__ void gemm2_part(float (&c)[36], uint32_t sb, uint32_t pitch, int wg) {
  const uint32_t dA0 = desc_lo(sb + wg * 8192, 8192), dB0 = desc_lo(sb + ASZ + BROW0 * 128, 16);
  wg_fence();
#pragma unroll
  for (int i = I0; i < I1; i++) {
    const int step = 68 - LAG + (i >> 2);
    if ((i & 3) == 0 && BROW0 == 0) mbar_wait_u(sb + BAR_OFF + B_FULL + (step % ST) * 8, (step / ST) & 1);
    if (i == 4 * LAG - TURN && BROW0 && wg == 0) named_arrive(7, 256);
    wgmma_ss<0>(c, dA0 + (step % ST) * (pitch >> 4) + (i & 3) * 128, dB0 + (step % ST) * (pitch >> 4) + (i & 3) * 2, 1);
  }
  wg_commit();
}
__device__ __forceinline__ void split_acc(const float (&acc)[72], float (&a)[36], float (&b)[36]) {
#pragma unroll
  for (int i = 0; i < 36; i++) { asm volatile("mov.b32 %0, %1;" : "=f"(a[i]) : "f"(acc[i])); asm volatile("mov.b32 %0, %1;" : "=f"(b[i]) : "f"(acc[36 + i])); }
}
template <int NV, int R, class Slice>
__device__ __forceinline__ void gelu_store(const float (&acc)[R], uint32_t bias0, uint32_t bias1, uint32_t sa, uint32_t zero, Slice slice) {
  const uint32_t bb[2] = {pin(bias0) * 0x10001u, pin(bias1) * 0x10001u};
  uint32_t x[2][4], t[2][4], dep[NV / 8], c3 = 0x3d123d12u;
#pragma unroll
  for (int j = 0; j <= NV / 8; j++) {
    if (j < NV / 8) {
      if (j >= GLAG) c3 = (dep[j - GLAG] & zero) | 0x3d123d12u;
#pragma unroll
      for (int u = 0; u < 4; u++) {
        x[j & 1][u] = hadd2(pack_bf16(acc[8 * j + 2 * u], acc[8 * j + 2 * u + 1]), bb[u & 1]);
        t[j & 1][u] = tanh2_ordered(hmul2(x[j & 1][u], hfma2(hmul2(x[j & 1][u], c3), x[j & 1][u], 0x3f4c3f4cu)));
      }
    }
    if (j > 0) {
      const uint32_t *xx = x[(j - 1) & 1], *tt = t[(j - 1) & 1];
      stsm4_t(sa + (j - 1) * 2048, hfma2(xx[0], tt[0], xx[0]), hfma2(xx[1], tt[1], xx[1]), hfma2(xx[2], tt[2], xx[2]), hfma2(xx[3], tt[3], xx[3]));
      dep[j - 1] = slice(j - 1);
    }
  }
}
struct Role { int half, kind, g2_m, dt, g1_mt, g1_nt, cs; uint32_t pitch; };
__device__ __forceinline__ Role get_role(const RoleMap& roles) {
  uint32_t b, sm;
  asm volatile("mov.u32 %0, %%ctaid.x;" : "=r"(b));
  asm volatile("mov.u32 %0, %%smid;" : "=r"(sm));
  const uint32_t w = roles.role[(roles.by_sm ? sm : b) >> 1];
  const int half = b & 1, kind = w & 3, m = (w >> 4) & 15, dt = (w >> 2) & 3;
  return Role{half, kind, m * 128, dt, half * 18 + (int)((w >> 8) & 31), (int)(w >> 16), (m * 4 + dt) * 2 + half, kind ? (uint32_t)PITCH_B : (uint32_t)PITCH_S};
}
__device__ __forceinline__ int g2_block(int half, int j) { return half * 36 + (j < 12 ? 2 * j : j < 24 ? 2 * j - 23 : j); }
__device__ __forceinline__ int conv_chan(int cs, int i) { return (3 * (cs >> 5) + (i >> 1)) * 64 + ((2 * cs) & 63) + (i & 1); }
__device__ __forceinline__ uint32_t conv_buf(uint32_t sb, int b) { return sb + (b == 3 ? (36 % ST) * PITCH_S : ST * PITCH_S + b * CBUF); }

__global__ void __cluster_dims__(2, 1, 1) __launch_bounds__(384, 1)
fused_kernel(const __nv_bfloat16* __restrict__ q, Scratch* __restrict__ gs, const __nv_bfloat16* __restrict__ b1,
             const __nv_bfloat16* __restrict__ shiftk, const __nv_bfloat16* __restrict__ ssmk, const __nv_bfloat16* __restrict__ ssmD,
             const __grid_constant__ CUtensorMap tmW1, const __grid_constant__ CUtensorMap tmW2, const __grid_constant__ CUtensorMap tmZ,
             const __grid_constant__ CUtensorMap tmH, const __grid_constant__ CUtensorMap tmK, const __grid_constant__ CUtensorMap tmV,
             const __grid_constant__ CUtensorMap tmKV, const __grid_constant__ CUtensorMap tmKL, const __grid_constant__ RoleMap roles, const __nv_bfloat16* __restrict__ b2,
             __nv_bfloat16* __restrict__ out) {
  const int cta = blockIdx.x;
  const int tid = threadIdx.x;
  if (tid == 288) PROFG(0);

  const uint32_t t_start = clock_now();
  if (tid == 256) { prefetch_map(&tmW1); prefetch_map(&tmH); }
  const int lc = (cta + LNROT) & 127;
  const uint32_t do_ln = cta < 128 && tid < 256;
  const int oct = lc + (tid & 128), ln_row = oct * 8 + ((tid >> 4) & 7), l16 = tid & 15;
  uint2 xr[9];
  if (do_ln && oct >= TN(QLATE)) spin_until(t_start, TN(QDELAY) + TN(QRAMP) * oct / 2);
#pragma unroll
  for (int i = 0; i < 9; i++) xr[i] = ldg64_if(q + (size_t)ln_row * D_ + i * 64 + l16 * 4, do_ln);
  if (tid == 0) PROF(32);
  const int warp = __shfl_sync(0xffffffffu, tid >> 5, 0);
  const uint32_t sb = __shfl_sync(0xffffffffu, (uint32_t)__cvta_generic_to_shared(smem_raw), 0);
  const uint32_t bars = sb + BAR_OFF;
  const int lane = tid & 31;
  const int wg = warp >> 2;
  constexpr int LN_OFF = ST * PITCH_B;

  if (warp < 8 || warp == 11) {
    asm volatile("barrier.cluster.arrive.relaxed.aligned;" ::: "memory");
    const int hq = (lane & 16) >> 3, hb = (lane & 16) + hq;
    float da[3][4] = {};
#pragma unroll
    for (int i = 0; i < 9; i++) mma16816(da[i % 3], xr[i].x, 0x3f803f80u, xr[i].y, 0x3f803f80u, xr[i].x, xr[i].y);
    const float r1 = ((da[0][2] + da[0][3]) + (da[1][2] + da[1][3])) + (da[2][2] + da[2][3]);
    const float r2 = (lane & 4) ? (da[0][1] + da[1][1]) + da[2][1] : (da[0][0] + da[1][0]) + da[2][0];
    const float s1 = __shfl_sync(0xffffffffu, r1, hq) + __shfl_sync(0xffffffffu, r1, hq + 1);
    const float s2 = (__shfl_sync(0xffffffffu, r2, hb) + __shfl_sync(0xffffffffu, r2, hb + 4)) + (__shfl_sync(0xffffffffu, r2, hb + 9) + __shfl_sync(0xffffffffu, r2, hb + 13));
    if (tid == 0) { asm volatile("" ::"f"(s2) : "memory"); PROF(27); }
    const float mean = s1 * (1.f / D_), var = fmaxf(fmaf(-mean, mean, s2 * (1.f / D_)), 0.f);
    const float rinv = ln_rinv(var), rinv2 = ln_rinv(var * rinv * rinv), scale = rinv * rinv2, shift = -bf_round((mean - bf_round(mean)) * rinv) * rinv2;
    const uint32_t m2 = pack_bf16(mean, mean), hi2 = pack_bf16(scale, scale), lo2 = pack_bf16(scale - bf_lo(hi2), scale - bf_lo(hi2)), sh2 = pack_bf16(shift, shift);
    const uint32_t hi1 = pack_bf16(rinv, rinv);
    asm volatile("{\n.reg .pred p;\nsetp.eq.u32 p, %5, 0;\n@p st.shared.v4.u32 [%0], {%1, %2, %3, %4};\n}" ::"r"(sb + LN_OFF + 18432 + tid), "r"(m2), "r"(hi1),
                 "r"(pack_bf16(rinv - bf_lo(hi1), rinv - bf_lo(hi1))), "r"(0u), "r"(tid & 0x10f) : "memory");
    const uint32_t g0 = 4 * (l16 >> 3) + 2 * (l16 & 1), hrow = sb + LN_OFF + ((tid >> 7) & 1) * 9216 + (tid & 0x70);
    const uint32_t hs0 = hrow + g0 * 128 + ((l16 >> 1) & 3) * 4, hs8 = ((hrow + (l16 >> 1) * 1152) ^ ((l16 >> 1) << 4)) + 1024 + (l16 & 1) * 8;
    uint32_t w[18];
#pragma unroll
    for (int i = 0; i < 18; i++) {
      const uint32_t d = hsub2((i & 1) ? xr[i >> 1].y : xr[i >> 1].x, m2);
      asm("max.u32 %0, %1, 1;" : "=r"(w[i]) : "r"(hfma2(d, hi2, hfma2(d, lo2, sh2))));
    }
#pragma unroll
    for (int i = 0; i < 16; i++) {
      const int gi = 9 * (i >> 1) + (i & 1);
      asm volatile("{\n.reg .pred p;\nsetp.ne.u32 p, %2, 0;\n@p st.shared.u32 [%0], %1;\n}" ::"r"((hs0 ^ ((g0 * 16 + (gi & 7) * 16) & 0x70)) + gi * 128), "r"(w[i]), "r"(do_ln) : "memory");
    }
    asm volatile("{\n.reg .pred p;\nsetp.ne.u32 p, %3, 0;\n@p st.shared.v2.u32 [%0], {%1, %2};\n}" ::"r"(hs8), "r"(w[16]), "r"(w[17]), "r"(do_ln) : "memory");
    if (tid == 224) PROF(13);
    fence_async_smem();
    if (warp < 8) named_arrive(wg, 160);
  } else if (warp != 8) {
    spin_until(t_start, TN(W9));
  }

  if (wg == 2) {
    asm volatile("setmaxnreg.dec.sync.aligned.u32 56;");
    auto store_h = [&](int w) {
      named_bar(w, 160);
      if (cta < 128 && elect_one()) {
        tma3d_store(&tmH, ((lc >> 3) + 16 * w) * 72, lc & 7, sb + LN_OFF + w * 9216);
        bulk_s2g(gs->stats + (lc + 128 * w) * 8, sb + LN_OFF + 18432 + w * 128, 128);
        bulk_commit();
      }
    };
    auto publish_h = [&](int w) {
      if (cta < 128 && elect_one()) { bulk_wait_all(); flag_add(gs->flags, FL_H + (w ? 2 : lc >> 6), 1); }
      __syncwarp();
    };
    uint32_t look = 0;
    if (warp == 11) {
      if (lc >= 64) spin_until(t_start, TN(HW));
      store_h(0);
      look = flag_ld(gs->flags, FL_H);
      if (lc < 64) publish_h(0);
      if (lane == 0) PROF(1);
    } else {
      if (elect_one()) {
        if (warp == 8) {
#pragma unroll
          for (int o = 0; o < B_GO; o += 8) mbar_init(bars + o, 1);
        } else if (warp == 9) {
#pragma unroll
          for (int o = B_GO; o < B_RAW + 40; o += 8) mbar_init(bars + o, 1);
        } else {
#pragma unroll
          for (int o = B_RAW + 40; o < B_END; o += 8) mbar_init(bars + o, o < B_EMPTY ? 1 : o < B_CEMPTY ? 2 : 4);
        }
        asm volatile("fence.mbarrier_init.release.cluster;" ::: "memory");
      }
      __syncwarp();
      asm volatile("barrier.cluster.arrive.relaxed.aligned;" ::: "memory");
      if (warp == 9) { prefetch_map(&tmK); prefetch_map(&tmV); prefetch_map(&tmKV); prefetch_map(&tmKL); prefetch_map(&tmW2); prefetch_map(&tmZ); }
      if (tid == 256) PROF(35);
    }
    const Role ro = get_role(roles);
    if (warp != 8) asm volatile("barrier.cluster.wait.aligned;" ::: "memory");
    if (warp == 11) {
      Ring r{0, 1};
      const uint32_t bsz = ro.pitch - ASZ;
      const uint8_t* src = gs->h + ro.g1_nt * bsz + ST * 73728;
      named_bar(10, 64);
#pragma unroll 1
      for (int i = ST; i < 32; i++) {
        if (i == ST || i == 8 || i == 16) wait_counter(gs->flags, FL_H + (i >> 3), i == 16 ? 128u : 64u, look, 0);
        if (i == TN(LK1) || i == TN(LK2)) look = flag_ld(gs->flags, FL_H + (i >> 3) + 1);
        mbar_wait(bars + B_EMPTY + r.s * 8, r.ph ^ 1);
        if (elect_one()) bulk_g2s(sb + r.s * ro.pitch + ASZ, src, bsz, bars + B_FULL + r.s * 8);
        if (i == ST && lane == 0) PROF(25);
        if (i == TN(HS2)) store_h(1);
        if (i == TN(HS2) + 2 || (i == ST && lc >= 64)) publish_h(i != ST);
        if (i == TN(KVGO1) && lane == 0) mbar_arrive(bars + B_KVGO + 8);
        if (i == TN(KVGO) && lane == 0) mbar_arrive(bars + B_KVGO);
        if (i == TN(CVGO) && lane == 0) mbar_arrive(bars + B_CVGO);
        src += 73728;
        r.next();
      }
      if (ro.kind != 2) {
        look = 0;
#pragma unroll 1
        for (int j = 0; j < 36; j++) {
          const uint8_t* su = gs->u + ((size_t)g2_block(ro.half, j) * D_ + ro.dt * 144) * 128;
          if (j == 0 || j == 12 || j == 24) wait_counter(gs->flags, FL_U + ro.half * 3 + j / 12, j == 24 ? 36u : 48u, look, 100);
          if (ro.kind ? j == 4 : j < 2) mbar_wait_u(bars + B_UDONE + (j ? 8 : 0), 0);
          mbar_wait(bars + B_EMPTY + r.s * 8, r.ph ^ 1);
          if (elect_one()) {
            bulk_g2s(sb + r.s * ro.pitch + ASZ, su + (ro.half ^ 1) * 9216, 9216, bars + B_FULL + r.s * 8);
            bulk_g2s(sb + r.s * ro.pitch + ASZ + 9216, su + ro.half * 9216, 9216, bars + B_FULL + r.s * 8);
          }
          if (j == 9 || j == 21) look = flag_ld(gs->flags, FL_U + ro.half * 3 + j / 12 + 1);
          if (j == 0 && lane == 0) PROF(8);
          r.next();
        }
#pragma unroll 1
        for (int o = lane; o < ST * 73728 / 16 / NG2; o += 32) ((uint4*)gs->h)[ro.cs * (ST * 73728 / 16 / NG2) + o] = make_uint4(0u, 0u, 0u, 0u);
      }
      polling_done(gs->flags, lane);
    } else if (warp == 8) {
      const uint64_t pol = stream_policy();
      Ring r{0, 0};
#pragma unroll 1
      for (int i = 0; i < 32; i++) {
        if (i < ST) spin_until(t_start, TN(A0) + i * TN(AD) + (i >= TN(AN) ? TN(AL) : 0));
        if (i == ST) {
          asm volatile("barrier.cluster.wait.aligned;" ::: "memory");
          if (roles.by_sm) {
            uint32_t sm;
            asm volatile("mov.u32 %0, %%smid;" : "=r"(sm));
            if (elect_one()) { mbar_expect(bars + B_PEER, 8); st_async2(mapa(bars + B_END, ro.half ^ 1), sm, sm, mapa(bars + B_PEER, ro.half ^ 1)); }
            mbar_wait_u(bars + B_PEER, 0);
            if ((lds32(bars + B_END) ^ sm) != 1 || sm >= NCTA) asm volatile("trap;");
          }
        }
        if (i >= ST) mbar_wait(bars + B_EMPTY + r.s * 8, r.ph ^ 1);
        if (elect_one()) {
          mbar_expect(bars + B_FULL + r.s * 8, ro.pitch);
          tma_weights(sb + r.s * ro.pitch, &tmW1, i * 64, ro.g1_mt * 2, bars + B_FULL + r.s * 8, pol);
        }
        r.next();
      }
      if (ro.kind != 2) {
#pragma unroll 1
        for (int j = 0; j < 36; j++) {
          if (j == 4 && ro.kind == 0) mbar_wait_u(bars + B_CEMPTY + 24, 0);
          mbar_wait(bars + B_EMPTY + r.s * 8, r.ph ^ 1);
          if (elect_one()) {
            mbar_expect(bars + B_FULL + r.s * 8, PITCH_S);
            tma_weights(sb + r.s * ro.pitch, &tmW2, g2_block(ro.half, j) * 64, ro.g2_m >> 6, bars + B_FULL + r.s * 8, pol);
          }
          r.next();
        }
        if (lane < 2) mbar_expect(bars + B_RFULL + lane * 8, 9216);
        __syncwarp();
        mbar_wait(bars + B_EMPTY + r.s * 8, r.ph ^ 1);
        if (lane == 0) mbar_arrive_cluster(mapa(bars + B_GO, ro.half ^ 1));
      }
      if (lane == 0) PROF(28);
    } else {
      const uint64_t pol = stream_policy();
      {
        const uint32_t hb = (ro.pitch - ASZ) >> 1, raw = bars + B_RAW + (warp - 9) * 40, dst = sb + ASZ + (warp - 9) * hb;
        const uint8_t* src = gs->h + (2 * ro.g1_nt + warp - 9) * hb;
        auto fetch_h = [&](int i) { if (elect_one()) { mbar_expect(raw + i * 8, hb); bulk_g2s(dst + i * ro.pitch, src + i * 73728, hb, raw + i * 8); } };
        int next = 0;
#pragma unroll 1
        for (int i = -1; i < ST; i++) {
          if (i >= 0) {
#pragma unroll 1
            for (uint32_t tries = 0;; tries++) {
              mbar_wait_u(raw + i * 8, tries & 1);
              if (lane == 0 && i == 0) PROF(29 + warp);
              const uint32_t pa = dst + i * ro.pitch + lane * 32 + (lane >> 2) * 4;
              uint32_t m = 1;
#pragma unroll
              for (int j = 0; j < 12; j++) m = min(m, lds32(pa + (j < 9 || ro.kind ? j : 0) * 1024));
              if (__all_sync(0xffffffffu, m)) break;
              if (lane == 0) PROF(26);
              fetch_h(i);
            }
            if (elect_one()) asm volatile("mbarrier.complete_tx.relaxed.cta.shared::cta.b64 [%0], %1;" ::"r"(bars + B_FULL + i * 8), "r"(hb) : "memory");
          }
#pragma unroll 1
          for (const int end = min(next + 2, ST); next < end; next++) {
            if (i < 0) spin_until(t_start, TN(H0) + next * TN(HD));
            fetch_h(next);
            if (next == 0 && tid == 288) PROF(3);
          }
          if (i < 0 && warp == 10) named_arrive(10, 64);
        }
      }
      if (ro.kind == 0) {
        mbar_wait_u(bars + B_KVGO + (warp - 9) * 8, 0);
        const int cs = ro.cs, grp = (cs / 3) * 2 + warp - 9, cb0 = (cs % 3) * 3;
        const uint32_t kin_s = sb + ST * PITCH_S + (warp - 9) * KVW, kout = kin_s + 2 * KVIN, fb = bars + B_KFULL + (warp - 9) * 16;
        auto fetch = [&](int i) {
          if (elect_one()) {
            mbar_expect(fb + (i & 1) * 8, KVIN);
            tma2d_stream(kin_s + (i & 1) * KVIN, &tmK, (cb0 + i) * 64, grp * 32 - 4, fb + (i & 1) * 8, pol);
            tma2d_stream(kin_s + (i & 1) * KVIN + 4608, &tmV, (cb0 + i) * 64, grp * 32 - 1, fb + (i & 1) * 8, pol);
          }
        };
        fetch(0);
        uint4 shk = ldg128(shiftk + (cb0 * 64 + lane * 2) * 4);
        const uint32_t dskip = ldg16(ssmD + conv_chan(cs, lane < NCONV ? lane : 0));
#pragma unroll 1
        for (int i = 0; i < 3; i++) {
          const uint32_t w0 = __byte_perm(shk.x, shk.z, 0x5410), w1 = __byte_perm(shk.x, shk.z, 0x7632);
          const uint32_t w2 = __byte_perm(shk.y, shk.w, 0x5410), w3 = __byte_perm(shk.y, shk.w, 0x7632);
          const uint32_t ka = kin_s + (i & 1) * KVIN + lane * 4;
          mbar_wait_u(fb + (i & 1) * 8, i >> 1);
          if (tid == 288 && i < 2) PROF(30 + i);
          if (i < 2) fetch(i + 1);
          shk = ldg128(i < 2 ? shiftk + ((cb0 + i + 1) * 64 + lane * 2) * 4 : ssmk + (size_t)conv_chan(cs, lane < NCONV ? lane : 0) * S_);
          uint32_t kr[8], vr[8], t1, t2, t3, xp;
          {
            const uint32_t k0 = lds32(ka), k1 = lds32(ka + 128), k2 = lds32(ka + 256), k3 = lds32(ka + 384), v0 = lds32(ka + 4608);
#pragma unroll
            for (int j = 0; j < 8; j++) { kr[j] = lds32(ka + 512 + j * 128); vr[j] = lds32(ka + 4736 + j * 128); }
            xp = hmul2(hfma2(k3, w0, hfma2(k2, w1, hfma2(k1, w2, hmul2(k0, w3)))), v0);
            t1 = hfma2(k3, w1, hfma2(k2, w2, hmul2(k1, w3)));
            t2 = hfma2(k3, w2, hmul2(k2, w3));
            t3 = hmul2(k3, w3);
          }
#pragma unroll 1
          for (int o = 0; o < 4; o++) {
            const uint32_t from = ka + o * 1024, to = kout + (o >> 1) * 5120 + lane * 80 + (o & 1) * 32;
#pragma unroll
            for (int m = 0; m < 8; m += 4) {
              uint32_t x[4];
#pragma unroll
              for (int j = 0; j < 4; j++) {
                x[j] = hmul2(hfma2(kr[m + j], w0, t1), vr[m + j]);
                t1 = hfma2(kr[m + j], w1, t2);
                t2 = hfma2(kr[m + j], w2, t3);
                t3 = hmul2(kr[m + j], w3);
              }
#pragma unroll
              for (int c = 0; c < 2; c++) {
                const uint32_t sel = c ? 0x7632 : 0x5410;
                sts128(to + c * 2560 + m * 4, __byte_perm(x[0], xp, sel), __byte_perm(x[1], x[0], sel), __byte_perm(x[2], x[1], sel), __byte_perm(x[3], x[2], sel));
              }
#pragma unroll
              for (int j = m; j < m + 4; j++) { kr[j] = lds32_if(from + 1536 + j * 128, o < 3); vr[j] = lds32_if(from + 5760 + j * 128, o < 3); }
              xp = x[3];
            }
            if (o & 1) {
              fence_async_smem();
              __syncwarp();
              if (elect_one()) {
                bulk_wait_all();
                if (o == 1 && i) flag_add(gs->flags, FL_KV + i - 1, 1);
                tma4d_store(&tmKV, (cb0 + i) * 32, 0, 2 * grp + (o >> 1), kout + (o >> 1) * 5120);
                bulk_commit();
              }
              __syncwarp();
            }
          }
        }
        shk.x = __byte_perm(pack_bf16(bf_lo(shk.x) + bf_lo(dskip), 0.f), shk.x, 0x7610);
        look = flag_ld(gs->flags, FL_KV + warp - 9);
        if (elect_one()) {
          bulk_wait_all();
          flag_add(gs->flags, FL_KV + 2, 1);
          bulk_prefetch(ssmk + (size_t)conv_chan(cs, 2 * (warp - 9)) * S_, 2 * S_ * 2, pol);
          if (warp == 9) PROFG(2);
        }
        __syncwarp();
#pragma unroll 1
        for (int i = warp == 9 ? 0 : 2; i < (warp == 9 ? 2 : NCONV); i++) {
          const int b = i & 3, d = conv_chan(cs, i);
          const uint32_t base = conv_buf(sb, b), cf = bars + B_CFULL + b * 8;
          if (!(i & 1)) wait_counter(gs->flags, FL_KV + (i >> 1), 192u, i < 4 ? look : 0u, 200);
          if (i == 0 || i == 2) mbar_wait_u(bars + B_CVGO, 0);
          if (i == 1 || i == 2) spin_until(clock_now(), i * 1000 - 400);
          if (i == 0 && lane == 0) PROF(23);
          if (i == 3) {
            mbar_wait_u(bars + B_G1DONE, 0);
            if (elect_one()) bulk_prefetch(ssmk + (size_t)conv_chan(cs, 4) * S_, 2 * S_ * 2, pol);
          }
          if (i >= 4) mbar_wait_u(bars + B_CEMPTY + b * 8, 0);
          if (lane == i) sts128(base + CH_OFF, shk.x, shk.y, shk.z, shk.w);
          if (lane >= 27) sts128(base + (lane >= 29 ? CH_OFF + (lane - 32) * 16 : CT_OFF + (lane - 27) * 16), 0u, 0u, 0u, 0u);
          fence_async_smem();
          __syncwarp();
          if (elect_one()) {
            mbar_expect(cf, 4080 + 128 + 63 * 160);
            bulk_g2s(base + CT_OFF + 32, gs->kv + (size_t)d * KVT, 128, cf);
            asm volatile("cp.async.bulk.tensor.3d.shared::cluster.global.mbarrier::complete_tx::bytes [%0], [%1, {%3, %3, %4}], [%2];"
                         ::"r"(base + CT_OFF + 160), "l"(&tmKL), "r"(cf), "r"(0), "r"(d) : "memory");
            bulk_g2s_stream(base + CH_OFF + 16, ssmk + (size_t)d * S_ + 8, 4080, cf, pol);
          }
        }
      }
      if (warp == 9) {
        if (elect_one()) {
          const uint32_t bsz = ro.pitch - ASZ;
#pragma unroll 1
          for (int w = 0; w < 2; w++) {
            const uint32_t src = sb + (ro.kind ? (w ? (36 % ST) * PITCH_B + ASZ : ST * PITCH_B) : ((32 % ST) + w) * PITCH_S + ASZ);
            mbar_wait_u(bars + B_USTG + w * 8, 0);
            bulk_s2g(gs->u + (size_t)(2 * ro.g1_mt + w) * D_ * 128 + ro.g1_nt * bsz, src, bsz);
            bulk_commit();
            if (ro.kind && w == 0) gate_arrive(gs->flags, TN(GDELAY) - 512);
            bulk_wait_read();
            mbar_arrive(bars + B_UDONE + w * 8);
            bulk_wait_all();
            flag_add(gs->flags, FL_U + ro.half * 3 + (ro.kind ? 2 : w), 1);
            PROFG(5 + 12 * w);
          }
          if (ro.kind == 0) {
#pragma unroll 1
            for (int i = 0; i < NCONV; i++) {
              mbar_wait_u(bars + B_SFULL + (i & 1) * 8, (i >> 1) & 1);
              bulk_s2g(gs->z + (size_t)chan_pos(conv_chan(ro.cs, i)) * S_, sb + CSTG_OFF + (i & 1) * 4096, 4096);
              bulk_commit();
              if (i == NCONV - 3) gate_arrive(gs->flags, 0);
              bulk_wait_read();
              mbar_arrive(bars + B_SEMPTY + (i & 1) * 8);
            }
            bulk_wait_all();
            flag_add(gs->flags, FL_Z, 1);
            PROFG(6);
          }
        }
      } else if (ro.kind != 2) {
        mbar_wait_u(bars + B_UDONE, 0);
        uint2 gate;
#pragma unroll 1
        for (uint32_t spins = 0;; spins++) {
          asm volatile("ld.relaxed.gpu.global.v2.u32 {%0, %1}, [%2];" : "=r"(gate.x), "=r"(gate.y) : "l"(gs->flags + FL_GATE * 32) : "memory");
          if (gate.x == NCTA) break;
          __nanosleep(100);
          if (spins > SPIN_LIMIT) asm volatile("trap;");
        }
        if (lane == 0) PROF(46);
#pragma unroll 1
        for (int w = 0; w < 2; w++) {
          while (time_now() - gate.y < TN(GDELAY) + w * TN(GDELAY1)) {}
          if (lane == 0) mbar_arrive(bars + B_G2GO + w * 8);
          if (lane == 0 && w == 0) PROF(24);
        }
        wait_counter(gs->flags, FL_Z, 96u, 0, 300);
        spin_until(clock_now(), TN(ZDELAY) + TN(ZRAMP) * cta);
        if (elect_one()) {
          mbar_expect(bars + B_ZFULL, 18432);
          tma2d(sb + ST * ro.pitch, &tmZ, ro.g2_m, ro.dt * 144 + ro.half * 72, bars + B_ZFULL);
          tma2d(sb + ST * ro.pitch + 9216, &tmZ, ro.g2_m + 64, ro.dt * 144 + ro.half * 72, bars + B_ZFULL);
          PROFG(7);
        }
        polling_done(gs->flags, lane);
      }
    }
  } else {
    asm volatile("setmaxnreg.inc.sync.aligned.u32 224;");
    const int wi = warp & 3, g = lane >> 2, qd = lane & 3, wt = tid & 127;
    const bool leader = wt == 0;
    Pipe p{{0, 0}, 0, false, 0};
    asm volatile("barrier.cluster.wait.aligned;" ::: "memory");
    int kind;
    {
      const Role ro = get_role(roles);
      kind = ro.kind;
      const int f0 = ro.g1_mt * 128 + wg * 64 + wi * 16 + g;
      uint32_t bias0 = ldg16(b1 + f0), bias1 = ldg16(b1 + f0 + 8);
      const uint32_t so = ((lane >> 4) * 8 + (lane & 7)) * 128 + (((2 * wi + ((lane >> 3) & 1)) ^ (lane & 7)) << 4);
      if (kind) {
        float acc[96];
        gemm_run<1, LEAD_B>(acc, 32, 0, p, sb, PITCH_B, wg, leader);
        pipe_drain(p, bars, leader);
        if (wg) mbar_wait_u(bars + B_EMPTY + (36 % ST) * 8, ((36 / ST) & 1) ^ 1);
        if (leader) PROF(4 + 10 * wg);
        uint32_t sa = sb + (wg ? (36 % ST) * PITCH_B + ASZ : ST * PITCH_B) + so;
#pragma unroll 1
        for (int c = 0; c < 4; c++, sa += 6144) {
          gelu_store<24>(acc, bias0, bias1, sa, 0u, [](int) { return 0u; });
#pragma unroll
          for (int i = 0; i < 72; i++) acc[i] = acc[i + 24];
        }
        fence_async_smem();
        __syncwarp();
        if (lane == 0) mbar_arrive(bars + B_USTG + wg * 8);
        if (leader) PROF(15 + wg);
      } else {
        const int cB = (g >> 1) & 1, cA = g >> 2, b = 2 * wi + (g & 1);
        const uint32_t toff = pin(CT_OFF + (40 * (2 * cA + cB) + 8 + b - 2 * qd) * 4);
        uint32_t a[16][4];
        auto load_a = [&](uint32_t base, int t, uint32_t on) {
          const uint32_t pt = base + toff + (t >> 1) * 1280 + (t & 1) * 64;
          a[t][0] = lds32_if(pt + 32, on); a[t][1] = lds32_if(pt + 672, on); a[t][2] = lds32_if(pt, on); a[t][3] = lds32_if(pt + 640, on);
        };
        {
          float acc[72];
          gemm_run<1, LEAD_S>(acc, 32, 0, p, sb, PITCH_S, wg, leader);
          if (wg == 1) named_arrive(6, 256);
          mbar_wait_u(bars + B_EMPTY + ((32 % ST) + wg) * 8, ((32 / ST) & 1) ^ 1);
          mbar_wait_u(bars + B_CFULL + wg * 8, 0);
          pipe_drain(p, bars, leader);
          if (leader) mbar_arrive(bars + B_G1DONE);
          if (leader) PROF(4 + 10 * wg);
          if (tid == 128) PROFC(48);
          if (GPRIO < 9 && wg == 1) named_bar(11, 256);
          gelu_store<72>(acc, bias0, bias1, sb + ((32 % ST) + wg) * PITCH_S + ASZ + so, roles.by_sm >> 1, [&](int t) {
            if (t < 8) load_a(conv_buf(sb, wg), t, 1);
            if (t == GPRIO && wg == 0) named_arrive(11, 256);
            return a[t & 7][GDEP];
          });
          fence_async_smem();
          __syncwarp();
          if (lane == 0) mbar_arrive(bars + B_USTG + wg * 8);
          if (leader) PROF(15 + wg);
        }
        const int phi = 2 * cA + (qd >> 1) + cB, pp = cB ? (phi & 3) : ((phi + 3) & 3);
        const int srcB = pin(((pp >> 1) << 4) | ((cB ^ 1) << 3) | ((g & 1) << 2) | ((pp & 1) << 1) | (qd & 1));
        const bool pB1 = cB && phi < 4, pB2 = cB && phi == 4;
        const int word = (8 * cB + 2 * (phi & 3) + (qd & 1)) * 8 + b;
        const uint32_t sto = pin(sb + CSTG_OFF + wg * 4096 + (word ^ (((word >> 5) & 3) << 1)) * 4);
#pragma unroll 1
        for (int i = wg; i < NCONV; i += 2) {
          const uint32_t base = conv_buf(sb, i & 3), next = conv_buf(sb, (i + 2) & 3);
          const uint64_t dH = mkdesc(base + CH_OFF, 16, 128, 0);
          float y[8][16];
          named_bar(6 + wg, 256);
          wg_fence();
#pragma unroll
          for (int t = 0; t < 16; t++) {
            if (t >= 8 && t % CFENCE == 0) wg_fence();
            if (t == CTURN) named_arrive(7 - wg, 256);
#pragma unroll
            for (int cb = t >> 1; cb < 8; cb++) {
              wgmma_rs_n32(y[cb], a[t][0], a[t][1], a[t][2], a[t][3], dH + (32 * cb - 32 * (t >> 1) - 2 * (t & 1) - 1), t);
              const int n = 8 * t - (t >> 1) * ((t - 1) >> 1) - (t >> 1) + cb + 1;
              if (n % CPER == 0 && n / CPER <= 8) load_a(base, 7 + n / CPER, 1);
            }
            if (t == 7 && CEARLY) wg_commit();
          }
          wg_commit();
          const bool more = i + 2 < NCONV;
          if (more) mbar_wait_u(bars + B_CFULL + ((i + 2) & 3) * 8, (i + 2) >> 2);
          mbar_wait_u(bars + B_SEMPTY + wg * 8, ((i >> 1) & 1) ^ 1);
          if (CEARLY) wg_wait<1>();
#pragma unroll
          for (int t = 0; t < CEARLY; t++) load_a(next, t, more);
          wg_wait<0>();
          if (lane == 0) mbar_arrive(bars + B_CEMPTY + (i & 3) * 8);
          if (leader) PROF(40 + i);
          uint32_t P[16], Q[16], R[16], o[8];
#pragma unroll
          for (int j = 0; j < 32; j++) {
            if ((j & 3) == 0 && (j >> 2) >= CEARLY) load_a(next, j >> 2, more);
            float v0 = y[j >> 2][4 * (j & 3)], v1 = y[j >> 2][4 * (j & 3) + 1];
            if (j >= 2) { v0 += y[(j - 2) >> 2][4 * ((j - 2) & 3) + 2]; v1 += y[(j - 2) >> 2][4 * ((j - 2) & 3) + 3]; }
            if (j & 1) R[j >> 1] = shfl_ordered(pack_bf16(v0, v1), lane ^ 16);
            else P[j >> 1] = pack_bf16(v0, v1);
          }
#pragma unroll
          for (int m = 0; m < 16; m++) Q[m] = hadd2(P[m], cA ? R[m] : (m ? R[m - 1] : 0u));
#pragma unroll
          for (int m = 0; m < 8; m++) o[m] = shfl_ordered(pB1 ? Q[2 * m] : (pB2 ? (m ? Q[2 * m - 1] : 0u) : Q[2 * m + 1]), srcB);
#pragma unroll
          for (int m = 0; m < 8; m++) sts32(sto + m * 512, hadd2(pB1 ? Q[2 * m + 1] : Q[2 * m], o[m]));
          fence_async_smem();
          __syncwarp();
          if (lane == 0) mbar_arrive(bars + B_SFULL + wg * 8);
          if (leader && i == 5) PROF(53);
        }
        if (wg == 0) named_bar(6, 256);
      }
    }
    if (kind != 2) {
      const Role ro = get_role(roles);
      const uint32_t pitch = ro.pitch;
      const int s0 = ro.g2_m + wg * 64 + wi * 16 + g;
      const size_t go = (size_t)s0 * D_ + ro.dt * 128 + ro.half * 64 + qd * 8, go8 = (size_t)s0 * D_ + 512 + ro.dt * 16 + ro.half * 8 + qd * 2;
      uint32_t x[2][9], sg[2][9];
      float acc[72];
      mbar_wait_u(bars + B_G2GO + wg * 8, 0);
      gemm_run<0, 0>(acc, XAT + 2 * wg, 0, p, sb, pitch, wg, leader);
#pragma unroll
      for (int J = 0; J < 4; J++) {
        const uint4 v = ldg128(q + go + (J & 1) * 8 * D_ + (J >> 1) * 32);
        x[J & 1][4 * (J >> 1)] = v.x; x[J & 1][4 * (J >> 1) + 1] = v.y; x[J & 1][4 * (J >> 1) + 2] = v.z; x[J & 1][4 * (J >> 1) + 3] = v.w;
      }
      x[0][8] = ldg32(q + go8); x[1][8] = ldg32(q + go8 + 8 * D_);
      const uint4 st0 = ld_l2(gs->stats + s0), st1 = ld_l2(gs->stats + s0 + 8);
      const uint32_t braw0 = ldg16(b2 + s0), braw1 = ldg16(b2 + s0 + 8);
      gemm_run<0, 0>(acc, 20 - XAT, 1, p, sb, pitch, wg, leader);
      {
        const int zw = 8 * wi + (g ^ ((((ro.g2_m >> 6) + wg) & 3) << 1));
        const uint32_t za = sb + ST * pitch + wg * 9216 + qd * 256 + (zw & 3) * 4;
        mbar_wait_u(bars + B_ZFULL, 0);
#pragma unroll
        for (int j = 0; j < 9; j++) {
          sg[0][j] = lds32(za + j * 1024 + (((zw >> 2) ^ (2 * qd)) << 4));
          sg[1][j] = lds32(za + j * 1024 + 128 + (((zw >> 2) ^ (2 * qd + 1)) << 4));
        }
      }
      gemm_run<0, 0>(acc, 1, 1, p, sb, pitch, wg, leader);
#pragma unroll
      for (int j = 0; j < 9; j++) {
        const uint32_t z0 = __byte_perm(sg[0][j], sg[1][j], 0x5410), z1 = __byte_perm(sg[0][j], sg[1][j], 0x7632);
        sg[0][j] = hmul2(ln_apply(x[0][j], st0), z0);
        sg[1][j] = hmul2(ln_apply(x[1][j], st1), z1);
        asm volatile("" : "+r"(sg[0][j]), "+r"(sg[1][j]));
      }
      gemm_run<0, SKEW>(acc, 15 - LAG - 2 * wg, 1, p, sb, pitch, wg, leader);
      const uint32_t rbuf = sb + (68 % ST) * pitch + warp * 2304;
      const uint32_t rdst = mapa(rbuf, ro.half ^ 1), rbar = mapa(bars + B_RFULL + wg * 8, ro.half ^ 1);
      pipe_drain(p, bars, leader);
      if (leader) PROF(9 + 10 * wg);
      if (tid == 128) PROFC(50);
      float cs[36], ck[36];
      split_acc(acc, cs, ck);
      gemm2_part<0, 0, 4 * LAG>(cs, sb, pitch, wg);
      if (KPRE) gemm2_part<72, 0, KPRE>(ck, sb, pitch, wg);
      const float hb0 = fmaf(bf_lo(braw0), 0.5f, __uint_as_float(st0.w)), hb1 = fmaf(bf_lo(braw1), 0.5f, __uint_as_float(st1.w));
      mbar_wait(bars + B_GO, 0);
      wg_wait<KPRE ? 1 : 0>();
      if (leader) PROF(54 + wg);
#pragma unroll
      for (int i = 0; i < 5; i++) {
        const float* c = &cs[8 * i];
        const uint32_t v0 = pack_bf16(fmaf(c[0], 0.25f, hb0), fmaf(c[1], 0.25f, hb0)), v1 = pack_bf16(fmaf(c[2], 0.25f, hb1), fmaf(c[3], 0.25f, hb1));
        if (i < 4) st_async4(rdst + i * 512 + lane * 16, v0, v1, pack_bf16(fmaf(c[4], 0.25f, hb0), fmaf(c[5], 0.25f, hb0)), pack_bf16(fmaf(c[6], 0.25f, hb1), fmaf(c[7], 0.25f, hb1)), rbar);
        else st_async2(rdst + 2048 + lane * 8, v0, v1, rbar);
      }
      if (wg == 1) named_bar(7, 256);
      gemm2_part<72, KPRE, 4 * LAG>(ck, sb, pitch, wg);
      uint32_t rp[18];
      mbar_wait(bars + B_RFULL + wg * 8, 0);
#pragma unroll
      for (int m = 0; m < 4; m++) {
        const uint4 v = lds128(rbuf + m * 512 + lane * 16);
        rp[4 * m] = v.x; rp[4 * m + 1] = v.y; rp[4 * m + 2] = v.z; rp[4 * m + 3] = v.w;
      }
      { const uint2 v = lds64(rbuf + 2048 + lane * 8); rp[16] = v.x; rp[17] = v.y; }
      __nv_bfloat16* o = out + go;
      wg_wait<0>();
      if (leader) PROF(10 + 10 * wg);
      float h[2][4], t[2][4], half = 0.25f;
#pragma unroll
      for (int j = 0; j <= 9; j++) {
        if (j < 9) {
          const uint32_t ra = rp[2 * j], rb = rp[2 * j + 1];
          if (j >= 2) half = fmaf(t[j & 1][3], 0.f, 0.25f);
          h[j & 1][0] = fmaf(ck[4 * j], half, bf_lo(ra)); h[j & 1][1] = fmaf(ck[4 * j + 1], half, bf_hi(ra));
          h[j & 1][2] = fmaf(ck[4 * j + 2], half, bf_lo(rb)); h[j & 1][3] = fmaf(ck[4 * j + 3], half, bf_hi(rb));
#pragma unroll
          for (int u = 0; u < 4; u++) t[j & 1][u] = tanh_ordered(h[j & 1][u]);
        }
        if (j > 0) {
          const int k = j - 1;
          const float* hh = h[k & 1];
          const float* tt = t[k & 1];
          x[0][k] = hfma2(sg[0][k], pack_bf16(fmaf(hh[0], tt[0], hh[0]), fmaf(hh[1], tt[1], hh[1])), x[0][k]);
          x[1][k] = hfma2(sg[1][k], pack_bf16(fmaf(hh[2], tt[2], hh[2]), fmaf(hh[3], tt[3], hh[3])), x[1][k]);
          if ((k & 3) == 3) {
            *(uint4*)(o + (k >> 2) * 32) = make_uint4(x[0][k - 3], x[0][k - 2], x[0][k - 1], x[0][k]);
            *(uint4*)(o + 8 * D_ + (k >> 2) * 32) = make_uint4(x[1][k - 3], x[1][k - 2], x[1][k - 1], x[1][k]);
          }
        }
      }
      *(uint32_t*)(out + go8) = x[0][8];
      *(uint32_t*)(out + go8 + 8 * D_) = x[1][8];
      if (leader) PROF(11 + 7 * wg);
      if (tid == 128) PROFC(51);
    }
  }
}

typedef CUresult (*EncodeFn)(CUtensorMap*, CUtensorMapDataType, cuuint32_t, void*, const cuuint64_t*, const cuuint64_t*, const cuuint32_t*,
                             const cuuint32_t*, CUtensorMapInterleave, CUtensorMapSwizzle, CUtensorMapL2promotion, CUtensorMapFloatOOBfill);

uint32_t role_of_pair(int t) {
  int grp, i;
  if (t < 32) { const int j = t & 7; i = t >> 3; grp = j < 6 ? 1 + j : 12 + 2 * (j - 6); }
  else if (t < 60) { const int j = (t - 32) % 7; i = (t - 32) / 7; grp = j < 5 ? 7 + j : 13 + 2 * (j - 5); }
  else if (t < 62) return 2u | (uint32_t)(14 + 3 * (t - 60)) << 8 | 2u << 16;
  else { grp = 0; i = t - 62; }
  if (grp < 12) return (uint32_t)(i << 2 | grp << 4 | grp << 8 | i << 16);
  const int u = (grp & 1) * 4 + i;
  return (uint32_t)(1 | i << 2 | grp << 4 | (12 + 3 * ((grp - 12) >> 1) + u / 3) << 8 | (u % 3) << 16);
}

}

extern "C" void kernel_launch(void* const* d_in, const int* in_sizes, int n_in, void* d_out, int out_size) {
  (void)in_sizes; (void)n_in; (void)out_size;
  EncodeFn enc = nullptr;
  cudaDriverEntryPointQueryResult qr;
  cudaGetDriverEntryPoint("cuTensorMapEncodeTiled", (void**)&enc, cudaEnableDefault, &qr);
  Scratch* gs = nullptr;
  cudaGetSymbolAddress((void**)&gs, g_scratch);
  void *zp = gs->z, *hp = gs->h, *kvp = gs->kv;
  CUtensorMap tmW1, tmW2, tmZ, tmH, tmK, tmV, tmKV, tmKL;
  for (int w = 0; w < 2; w++) {
    cuuint64_t gd[2] = {D_, S_};
    cuuint64_t st[1] = {D_ * 2};
    cuuint32_t bx[2] = {64, w ? 33u : 36u};
    cuuint32_t es[2] = {1, 1};
    enc(w ? &tmV : &tmK, CU_TENSOR_MAP_DATA_TYPE_BFLOAT16, 2, d_in[1 + w], gd, st, bx, es, CU_TENSOR_MAP_INTERLEAVE_NONE, CU_TENSOR_MAP_SWIZZLE_NONE,
        CU_TENSOR_MAP_L2_PROMOTION_L2_128B, CU_TENSOR_MAP_FLOAT_OOB_FILL_NONE);
  }
  {
    cuuint64_t gd[4] = {16, D_ / 2, 2, 128};
    cuuint64_t st[3] = {2 * KVT, KVT, 64};
    cuuint32_t bx[4] = {20, 32, 2, 1};
    cuuint32_t es[4] = {1, 1, 1, 1};
    enc(&tmKV, CU_TENSOR_MAP_DATA_TYPE_UINT32, 4, kvp, gd, st, bx, es, CU_TENSOR_MAP_INTERLEAVE_NONE, CU_TENSOR_MAP_SWIZZLE_NONE,
        CU_TENSOR_MAP_L2_PROMOTION_NONE, CU_TENSOR_MAP_FLOAT_OOB_FILL_NONE);
  }
  {
    cuuint64_t gd[3] = {40, 63, D_};
    cuuint64_t st[2] = {128, KVT};
    cuuint32_t bx[3] = {40, 63, 1};
    cuuint32_t es[3] = {1, 1, 1};
    enc(&tmKL, CU_TENSOR_MAP_DATA_TYPE_UINT32, 3, gs->kv + 96, gd, st, bx, es, CU_TENSOR_MAP_INTERLEAVE_NONE, CU_TENSOR_MAP_SWIZZLE_NONE,
        CU_TENSOR_MAP_L2_PROMOTION_NONE, CU_TENSOR_MAP_FLOAT_OOB_FILL_NONE);
  }
  {
    cuuint64_t gd[3] = {64, 32 * 72, 8};
    cuuint64_t st[2] = {1024, 128};
    cuuint32_t bx[3] = {64, 72, 1};
    cuuint32_t es[3] = {1, 1, 1};
    enc(&tmH, CU_TENSOR_MAP_DATA_TYPE_BFLOAT16, 3, hp, gd, st, bx, es, CU_TENSOR_MAP_INTERLEAVE_NONE, CU_TENSOR_MAP_SWIZZLE_128B,
        CU_TENSOR_MAP_L2_PROMOTION_NONE, CU_TENSOR_MAP_FLOAT_OOB_FILL_NONE);
  }
  for (int w = 0; w < 2; w++) {
    const cuuint64_t M = w ? S_ : F_, K = w ? F_ : S_;
    cuuint64_t gd[3] = {64, K, M / 64};
    cuuint64_t st[2] = {M * 2, 128};
    cuuint32_t bx[3] = {64, 64, 2};
    cuuint32_t es[3] = {1, 1, 1};
    enc(w ? &tmW2 : &tmW1, CU_TENSOR_MAP_DATA_TYPE_BFLOAT16, 3, d_in[w ? 9 : 7], gd, st, bx, es, CU_TENSOR_MAP_INTERLEAVE_NONE,
        CU_TENSOR_MAP_SWIZZLE_128B, CU_TENSOR_MAP_L2_PROMOTION_L2_256B, CU_TENSOR_MAP_FLOAT_OOB_FILL_NONE);
  }
  {
    cuuint64_t gd[2] = {S_, D_};
    cuuint64_t st[1] = {S_ * 2};
    cuuint32_t bx[2] = {64, 72};
    cuuint32_t es[2] = {1, 1};
    enc(&tmZ, CU_TENSOR_MAP_DATA_TYPE_BFLOAT16, 2, zp, gd, st, bx, es, CU_TENSOR_MAP_INTERLEAVE_NONE, CU_TENSOR_MAP_SWIZZLE_128B,
        CU_TENSOR_MAP_L2_PROMOTION_L2_256B, CU_TENSOR_MAP_FLOAT_OOB_FILL_NONE);
  }
  RoleMap roles;
  int dev = 0, sms = 0;
  cudaGetDevice(&dev);
  cudaDeviceGetAttribute(&sms, cudaDevAttrMultiProcessorCount, dev);
  roles.by_sm = sms == NCTA;
  for (int k = 0; k < NCTA / 2; k++) roles.role[k] = role_of_pair(k);
  cudaFuncSetAttribute(fused_kernel, cudaFuncAttributeMaxDynamicSharedMemorySize, SMEM_BYTES);
  fused_kernel<<<NCTA, 384, SMEM_BYTES>>>((const __nv_bfloat16*)d_in[0], gs, (const __nv_bfloat16*)d_in[8], (const __nv_bfloat16*)d_in[3],
                                          (const __nv_bfloat16*)d_in[4], (const __nv_bfloat16*)d_in[5], tmW1, tmW2, tmZ, tmH, tmK, tmV, tmKV, tmKL,
                                          roles, (const __nv_bfloat16*)d_in[10], (__nv_bfloat16*)d_out);
}
```

```cpp
#include <cuda_runtime.h>
#include <cuda_bf16.h>
#include <cuda.h>
#include <stdint.h>

namespace {

constexpr int S_ = 2048, D_ = 576, F_ = 4608;
constexpr int NCTA = 132, NG2 = 128, NCONV = 6;
constexpr int ST = 5, ASZ = 16384, PITCH_S = ASZ + 144 * 128, PITCH_B = ASZ + 192 * 128;
constexpr int KVIN = (36 + 33) * 128, KVW = 2 * KVIN + 64 * 176;
constexpr int BAR_OFF = ST * PITCH_S + 2 * KVW;
constexpr int SMEM_BYTES = BAR_OFF + 512;
constexpr int LNROT = 120;
constexpr int SKEW = 1;
constexpr int LEAD_S = 4, LEAD_B = 2;
constexpr int CTURN = 14, CPER = 4;
constexpr int TURN = 4, KPRE = 2;
constexpr int XAT = 12, GLAG = 4, PRE0 = 1;
constexpr int LAG = 4;
constexpr int CBUF = 14464, CH_OFF = 128, CT_OFF = 4224, KVT = 128 + 8192;
constexpr int CSTG_OFF = ST * PITCH_S + 3 * CBUF;
constexpr uint32_t SPIN_LIMIT = 1u << 22;

constexpr int FL_H = 0, FL_U = 3, FL_KV = 9, FL_Z = 12, FL_GATE = 13, FL_DONE = 14, FL_N = 15;
struct Scratch {
  uint32_t flags[64 * 32];
  uint4 stats[S_];
  uint8_t h[32 * 72 * 1024];
  uint8_t u[72 * D_ * 128];
  uint8_t kv[D_ * KVT];
  __nv_bfloat16 z[D_ * S_];
};
__device__ __align__(1024) Scratch g_scratch;
extern __shared__ __align__(1024) uint8_t smem_raw[];
#define TUNABLES(X) X(W9, 1200) X(QLATE, 40) X(QDELAY, 400) X(QRAMP, 5) X(A0, 1200) X(AD, 300) X(AN, 2) X(AL, 1500) X(H0, 3100) X(HD, 400) X(HS2, 8) X(HW, 4200) X(LK1, 7) X(LK2, 14) X(KVGO, 6) X(KVGO1, 10) X(CVGO, 31) X(GDELAY, 608) X(GDELAY1, 256) X(ZDELAY, 3000) X(ZRAMP, 40)
#define X(k, v) constexpr int T_##k = v;
TUNABLES(X)
#undef X
#define TN(k) T_##k
struct RoleMap { uint32_t role[NCTA / 2]; uint32_t by_sm; };
#define PROF(i) do {} while (0)
#define PROFG(i) do {} while (0)
#define PROFC(i) do {} while (0)

template<int TB> __device__ __forceinline__ void wgmma_ss(float (&d)[96], uint32_t da, uint32_t db, int sd) {
  asm volatile("{\n.reg .pred p;\n.reg .b64 a, b;\nsetp.ne.b32 p, %98, 0;\nmov.b64 a, {%96, %100};\nmov.b64 b, {%97, %101};\n"
    "wgmma.mma_async.sync.aligned.m64n192k16.f32.bf16.bf16 {%0, %1, %2, %3, %4, %5, %6, %7, %8, %9, %10, %11, %12, %13, %14, %15, %16, %17, %18, %19, %20, %21, %22, %23, %24, %25, %26, %27, %28, %29, %30, %31, %32, %33, %34, %35, %36, %37, %38, %39, %40, %41, %42, %43, %44, %45, %46, %47, %48, %49, %50, %51, %52, %53, %54, %55, %56, %57, %58, %59, %60, %61, %62, %63, %64, %65, %66, %67, %68, %69, %70, %71, %72, %73, %74, %75, %76, %77, %78, %79, %80, %81, %82, %83, %84, %85, %86, %87, %88, %89, %90, %91, %92, %93, %94, %95}, a, b, p, 1, 1, 1, %99;\n}\n"
    : "+f"(d[0]), "+f"(d[1]), "+f"(d[2]), "+f"(d[3]), "+f"(d[4]), "+f"(d[5]), "+f"(d[6]), "+f"(d[7]), "+f"(d[8]), "+f"(d[9]), "+f"(d[10]), "+f"(d[11]), "+f"(d[12]), "+f"(d[13]), "+f"(d[14]), "+f"(d[15]), "+f"(d[16]), "+f"(d[17]), "+f"(d[18]), "+f"(d[19]), "+f"(d[20]), "+f"(d[21]), "+f"(d[22]), "+f"(d[23]), "+f"(d[24]), "+f"(d[25]), "+f"(d[26]), "+f"(d[27]), "+f"(d[28]), "+f"(d[29]), "+f"(d[30]), "+f"(d[31]), "+f"(d[32]), "+f"(d[33]), "+f"(d[34]), "+f"(d[35]), "+f"(d[36]), "+f"(d[37]), "+f"(d[38]), "+f"(d[39]), "+f"(d[40]), "+f"(d[41]), "+f"(d[42]), "+f"(d[43]), "+f"(d[44]), "+f"(d[45]), "+f"(d[46]), "+f"(d[47]), "+f"(d[48]), "+f"(d[49]), "+f"(d[50]), "+f"(d[51]), "+f"(d[52]), "+f"(d[53]), "+f"(d[54]), "+f"(d[55]), "+f"(d[56]), "+f"(d[57]), "+f"(d[58]), "+f"(d[59]), "+f"(d[60]), "+f"(d[61]), "+f"(d[62]), "+f"(d[63]), "+f"(d[64]), "+f"(d[65]), "+f"(d[66]), "+f"(d[67]), "+f"(d[68]), "+f"(d[69]), "+f"(d[70]), "+f"(d[71]), "+f"(d[72]), "+f"(d[73]), "+f"(d[74]), "+f"(d[75]), "+f"(d[76]), "+f"(d[77]), "+f"(d[78]), "+f"(d[79]), "+f"(d[80]), "+f"(d[81]), "+f"(d[82]), "+f"(d[83]), "+f"(d[84]), "+f"(d[85]), "+f"(d[86]), "+f"(d[87]), "+f"(d[88]), "+f"(d[89]), "+f"(d[90]), "+f"(d[91]), "+f"(d[92]), "+f"(d[93]), "+f"(d[94]), "+f"(d[95])
    : "r"(da), "r"(db), "r"(sd), "n"(TB), "r"(0x40000040u), "r"(TB ? 0x40u : 0x40000040u));
}
template<int TB> __device__ __forceinline__ void wgmma_ss(float (&d)[72], uint32_t da, uint32_t db, int sd) {
  asm volatile("{\n.reg .pred p;\n.reg .b64 a, b;\nsetp.ne.b32 p, %74, 0;\nmov.b64 a, {%72, %76};\nmov.b64 b, {%73, %77};\n"
    "wgmma.mma_async.sync.aligned.m64n144k16.f32.bf16.bf16 {%0, %1, %2, %3, %4, %5, %6, %7, %8, %9, %10, %11, %12, %13, %14, %15, %16, %17, %18, %19, %20, %21, %22, %23, %24, %25, %26, %27, %28, %29, %30, %31, %32, %33, %34, %35, %36, %37, %38, %39, %40, %41, %42, %43, %44, %45, %46, %47, %48, %49, %50, %51, %52, %53, %54, %55, %56, %57, %58, %59, %60, %61, %62, %63, %64, %65, %66, %67, %68, %69, %70, %71}, a, b, p, 1, 1, 1, %75;\n}\n"
    : "+f"(d[0]), "+f"(d[1]), "+f"(d[2]), "+f"(d[3]), "+f"(d[4]), "+f"(d[5]), "+f"(d[6]), "+f"(d[7]), "+f"(d[8]), "+f"(d[9]), "+f"(d[10]), "+f"(d[11]), "+f"(d[12]), "+f"(d[13]), "+f"(d[14]), "+f"(d[15]), "+f"(d[16]), "+f"(d[17]), "+f"(d[18]), "+f"(d[19]), "+f"(d[20]), "+f"(d[21]), "+f"(d[22]), "+f"(d[23]), "+f"(d[24]), "+f"(d[25]), "+f"(d[26]), "+f"(d[27]), "+f"(d[28]), "+f"(d[29]), "+f"(d[30]), "+f"(d[31]), "+f"(d[32]), "+f"(d[33]), "+f"(d[34]), "+f"(d[35]), "+f"(d[36]), "+f"(d[37]), "+f"(d[38]), "+f"(d[39]), "+f"(d[40]), "+f"(d[41]), "+f"(d[42]), "+f"(d[43]), "+f"(d[44]), "+f"(d[45]), "+f"(d[46]), "+f"(d[47]), "+f"(d[48]), "+f"(d[49]), "+f"(d[50]), "+f"(d[51]), "+f"(d[52]), "+f"(d[53]), "+f"(d[54]), "+f"(d[55]), "+f"(d[56]), "+f"(d[57]), "+f"(d[58]), "+f"(d[59]), "+f"(d[60]), "+f"(d[61]), "+f"(d[62]), "+f"(d[63]), "+f"(d[64]), "+f"(d[65]), "+f"(d[66]), "+f"(d[67]), "+f"(d[68]), "+f"(d[69]), "+f"(d[70]), "+f"(d[71])
    : "r"(da), "r"(db), "r"(sd), "n"(TB), "r"(0x40000040u), "r"(TB ? 0x40u : 0x40000040u));
}
template<int TB> __device__ __forceinline__ void wgmma_ss(float (&d)[36], uint32_t da, uint32_t db, int sd) {
  asm volatile("{\n.reg .pred p;\n.reg .b64 a, b;\nsetp.ne.b32 p, %38, 0;\nmov.b64 a, {%36, %40};\nmov.b64 b, {%37, %41};\n"
    "wgmma.mma_async.sync.aligned.m64n72k16.f32.bf16.bf16 {%0, %1, %2, %3, %4, %5, %6, %7, %8, %9, %10, %11, %12, %13, %14, %15, %16, %17, %18, %19, %20, %21, %22, %23, %24, %25, %26, %27, %28, %29, %30, %31, %32, %33, %34, %35}, a, b, p, 1, 1, 1, %39;\n}\n"
    : "+f"(d[0]), "+f"(d[1]), "+f"(d[2]), "+f"(d[3]), "+f"(d[4]), "+f"(d[5]), "+f"(d[6]), "+f"(d[7]), "+f"(d[8]), "+f"(d[9]), "+f"(d[10]), "+f"(d[11]), "+f"(d[12]), "+f"(d[13]), "+f"(d[14]), "+f"(d[15]), "+f"(d[16]), "+f"(d[17]), "+f"(d[18]), "+f"(d[19]), "+f"(d[20]), "+f"(d[21]), "+f"(d[22]), "+f"(d[23]), "+f"(d[24]), "+f"(d[25]), "+f"(d[26]), "+f"(d[27]), "+f"(d[28]), "+f"(d[29]), "+f"(d[30]), "+f"(d[31]), "+f"(d[32]), "+f"(d[33]), "+f"(d[34]), "+f"(d[35])
    : "r"(da), "r"(db), "r"(sd), "n"(TB), "r"(0x40000040u), "r"(TB ? 0x40u : 0x40000040u));
}
__device__ __forceinline__ void wgmma_rs_n32(float (&d)[16], uint32_t a0, uint32_t a1, uint32_t a2, uint32_t a3, uint64_t db, int sd) {
  asm volatile("{\n.reg .pred p;\nsetp.ne.b32 p, %21, 0;\n"
    "wgmma.mma_async.sync.aligned.m64n32k16.f32.bf16.bf16 {%0, %1, %2, %3, %4, %5, %6, %7, %8, %9, %10, %11, %12, %13, %14, %15}, {%16, %17, %18, %19}, %20, p, 1, 1, 0;\n}\n"
    : "+f"(d[0]), "+f"(d[1]), "+f"(d[2]), "+f"(d[3]), "+f"(d[4]), "+f"(d[5]), "+f"(d[6]), "+f"(d[7]), "+f"(d[8]), "+f"(d[9]), "+f"(d[10]), "+f"(d[11]), "+f"(d[12]), "+f"(d[13]), "+f"(d[14]), "+f"(d[15])
    : "r"(a0), "r"(a1), "r"(a2), "r"(a3), "l"(db), "r"(sd));
}

__device__ __forceinline__ void wg_fence() { asm volatile("wgmma.fence.sync.aligned;" ::: "memory"); }
__device__ __forceinline__ void wg_commit() { asm volatile("wgmma.commit_group.sync.aligned;" ::: "memory"); }
template <int n> __device__ __forceinline__ void wg_wait() { asm volatile("wgmma.wait_group.sync.aligned %0;" ::"n"(n) : "memory"); }
__device__ __forceinline__ uint64_t mkdesc(uint32_t addr, uint32_t lbo, uint32_t sbo, uint32_t sw) {
  return (uint64_t)((addr & 0x3FFFF) >> 4) | ((uint64_t)(lbo >> 4) << 16) | ((uint64_t)(sbo >> 4) << 32) | ((uint64_t)sw << 62);
}
__device__ __forceinline__ void mbar_init(uint32_t a, int c) { asm volatile("mbarrier.init.shared::cta.b64 [%0], %1;" ::"r"(a), "r"(c)); }
__device__ __forceinline__ void mbar_expect(uint32_t a, uint32_t b) { asm volatile("mbarrier.arrive.expect_tx.shared::cta.b64 _, [%0], %1;" ::"r"(a), "r"(b) : "memory"); }
__device__ __forceinline__ void mbar_arrive(uint32_t a) { asm volatile("mbarrier.arrive.shared::cta.b64 _, [%0];" ::"r"(a) : "memory"); }
__device__ __forceinline__ void mbar_arrive_cluster(uint32_t raddr) { asm volatile("mbarrier.arrive.shared::cluster.b64 _, [%0];" ::"r"(raddr) : "memory"); }
__device__ __forceinline__ uint32_t mapa(uint32_t a, uint32_t cta) { uint32_t r; asm("mapa.shared::cluster.u32 %0, %1, %2;" : "=r"(r) : "r"(a), "r"(cta)); return r; }
__device__ __forceinline__ void mbar_wait(uint32_t a, uint32_t ph) {
  asm volatile(
      "{\n.reg .pred p;\n.reg .u32 c;\nmov.u32 c, 0;\n"
      "WAIT_LOOP:\nmbarrier.try_wait.parity.shared::cta.b64 p, [%0], %1;\n@p bra WAIT_DONE;\n"
      "add.u32 c, c, 1;\nsetp.lt.u32 p, c, %2;\n@p bra WAIT_LOOP;\ntrap;\nWAIT_DONE:\n}" ::"r"(a), "r"(ph), "n"(SPIN_LIMIT) : "memory");
}
__device__ __forceinline__ void mbar_wait_u(uint32_t a, uint32_t ph) {
  asm volatile("{\n.reg .pred p;\nWAIT_LOOP:\nmbarrier.try_wait.parity.shared::cta.b64 p, [%0], %1;\n@!p bra WAIT_LOOP;\n}" ::"r"(a), "r"(ph) : "memory");
}
__device__ __forceinline__ uint32_t desc_lo(uint32_t addr, uint32_t lbo) { return ((addr & 0x3FFFF) >> 4) | ((lbo >> 4) << 16); }
__device__ __forceinline__ void tma2d(uint32_t dst, const CUtensorMap* m, int c0, int c1, uint32_t bar) {
  asm volatile("cp.async.bulk.tensor.2d.shared::cluster.global.mbarrier::complete_tx::bytes [%0], [%1, {%3, %4}], [%2];" ::"r"(dst), "l"(m), "r"(bar), "r"(c0), "r"(c1) : "memory");
}
__device__ __forceinline__ void bulk_g2s(uint32_t dst, const void* src, uint32_t sz, uint32_t bar) {
  asm volatile("cp.async.bulk.shared::cluster.global.mbarrier::complete_tx::bytes [%0], [%1], %2, [%3];" ::"r"(dst), "l"(src), "r"(sz), "r"(bar) : "memory");
}
__device__ __forceinline__ void bulk_s2g(void* dst, uint32_t src, uint32_t sz) {
  asm volatile("cp.async.bulk.global.shared::cta.bulk_group [%0], [%1], %2;" ::"l"(dst), "r"(src), "r"(sz) : "memory");
}
__device__ __forceinline__ uint64_t stream_policy() {
  uint64_t p;
  asm volatile("createpolicy.fractional.L2::evict_first.b64 %0, 1.0;" : "=l"(p));
  return p;
}
__device__ __forceinline__ void tma_weights(uint32_t dst, const CUtensorMap* m, int k0, int mchunk, uint32_t bar, uint64_t pol) {
  asm volatile("cp.async.bulk.tensor.3d.shared::cluster.global.mbarrier::complete_tx::bytes.L2::cache_hint [%0], [%1, {%6, %3, %4}], [%2], %5;"
               ::"r"(dst), "l"(m), "r"(bar), "r"(k0), "r"(mchunk), "l"(pol), "r"(0) : "memory");
}
__device__ __forceinline__ bool elect_one() {
  uint32_t p;
  asm volatile("{\n.reg .pred P;\nelect.sync _|P, 0xffffffff;\nselp.u32 %0, 1, 0, P;\n}" : "=r"(p));
  return p;
}
__device__ __forceinline__ void bulk_g2s_stream(uint32_t dst, const void* src, uint32_t sz, uint32_t bar, uint64_t pol) {
  asm volatile("cp.async.bulk.shared::cluster.global.mbarrier::complete_tx::bytes.L2::cache_hint [%0], [%1], %2, [%3], %4;"
               ::"r"(dst), "l"(src), "r"(sz), "r"(bar), "l"(pol) : "memory");
}
__device__ __forceinline__ void tma3d_store(const CUtensorMap* m, int c1, int c2, uint32_t src) {
  asm volatile("cp.async.bulk.tensor.3d.global.shared::cta.bulk_group [%0, {%4, %2, %3}], [%1];" ::"l"(m), "r"(src), "r"(c1), "r"(c2), "r"(0) : "memory");
}
__device__ __forceinline__ void tma2d_stream(uint32_t dst, const CUtensorMap* m, int c0, int c1, uint32_t bar, uint64_t pol) {
  asm volatile("cp.async.bulk.tensor.2d.shared::cluster.global.mbarrier::complete_tx::bytes.L2::cache_hint [%0], [%1, {%3, %4}], [%2], %5;"
               ::"r"(dst), "l"(m), "r"(bar), "r"(c0), "r"(c1), "l"(pol) : "memory");
}
__device__ __forceinline__ void tma4d_store(const CUtensorMap* m, int c1, int c2, int c3, uint32_t src) {
  asm volatile("cp.async.bulk.tensor.4d.global.shared::cta.bulk_group [%0, {%5, %2, %3, %4}], [%1];" ::"l"(m), "r"(src), "r"(c1), "r"(c2), "r"(c3), "r"(0) : "memory");
}
__device__ __forceinline__ void bulk_commit() { asm volatile("cp.async.bulk.commit_group;" ::: "memory"); }
__device__ __forceinline__ void bulk_wait_all() { asm volatile("cp.async.bulk.wait_group 0;" ::: "memory"); }
__device__ __forceinline__ void fence_async_smem() { asm volatile("fence.proxy.async.shared::cta;" ::: "memory"); }
__device__ __forceinline__ void fence_async_global() { asm volatile("fence.proxy.async.global;" ::: "memory"); }
__device__ __forceinline__ void named_bar(int id, int n) { asm volatile("bar.sync %0, %1;" ::"r"(id), "r"(n) : "memory"); }
__device__ __forceinline__ void named_arrive(int id, int n) { asm volatile("bar.arrive %0, %1;" ::"r"(id), "r"(n) : "memory"); }
__device__ __forceinline__ void flag_add(uint32_t* f, int i, uint32_t v) { asm volatile("red.relaxed.gpu.global.add.u32 [%0], %1;" ::"l"(f + i * 32), "r"(v) : "memory"); }
__device__ __forceinline__ uint32_t flag_ld(uint32_t* f, int i) { uint32_t v; asm volatile("ld.relaxed.gpu.global.u32 %0, [%1];" : "=r"(v) : "l"(f + i * 32) : "memory"); return v; }
__device__ __forceinline__ void prefetch_map(const CUtensorMap* m) { asm volatile("prefetch.tensormap [%0];" ::"l"(m) : "memory"); }
__device__ __forceinline__ void stsm4_t(uint32_t a, uint32_t r0, uint32_t r1, uint32_t r2, uint32_t r3) {
  asm volatile("stmatrix.sync.aligned.m8n8.x4.trans.shared.b16 [%0], {%1, %2, %3, %4};" ::"r"(a), "r"(r0), "r"(r1), "r"(r2), "r"(r3) : "memory");
}
__device__ __forceinline__ uint32_t lds32(uint32_t a) { uint32_t v; asm volatile("ld.shared.u32 %0, [%1];" : "=r"(v) : "r"(a) : "memory"); return v; }
__device__ __forceinline__ void sts32(uint32_t a, uint32_t v) { asm volatile("st.shared.u32 [%0], %1;" ::"r"(a), "r"(v) : "memory"); }
__device__ __forceinline__ uint4 ld_l2(const uint4* p) { uint4 v; asm volatile("ld.relaxed.gpu.global.v4.u32 {%0, %1, %2, %3}, [%4];" : "=r"(v.x), "=r"(v.y), "=r"(v.z), "=r"(v.w) : "l"(p) : "memory"); return v; }
__device__ __forceinline__ void sts128(uint32_t a, uint32_t x, uint32_t y, uint32_t z, uint32_t w) { asm volatile("st.shared.v4.u32 [%0], {%1, %2, %3, %4};" ::"r"(a), "r"(x), "r"(y), "r"(z), "r"(w) : "memory"); }
__device__ __forceinline__ uint4 lds128(uint32_t a) { uint4 v; asm volatile("ld.shared.v4.u32 {%0, %1, %2, %3}, [%4];" : "=r"(v.x), "=r"(v.y), "=r"(v.z), "=r"(v.w) : "r"(a) : "memory"); return v; }
__device__ __forceinline__ void st_async4(uint32_t raddr, uint32_t a, uint32_t b, uint32_t c, uint32_t d, uint32_t rbar) {
  asm volatile("st.async.weak.shared::cluster.mbarrier::complete_tx::bytes.v4.b32 [%0], {%1, %2, %3, %4}, [%5];" ::"r"(raddr), "r"(a), "r"(b), "r"(c), "r"(d), "r"(rbar) : "memory");
}
__device__ __forceinline__ uint32_t pack_bf16(float lo, float hi) { uint32_t r; asm("cvt.rn.bf16x2.f32 %0, %1, %2;" : "=r"(r) : "f"(hi), "f"(lo)); return r; }
__device__ __forceinline__ float bf_lo(uint32_t v) { return __uint_as_float(v << 16); }
__device__ __forceinline__ float bf_hi(uint32_t v) { return __uint_as_float(v & 0xffff0000u); }
__device__ __forceinline__ float bf_round(float x) { return bf_lo(pack_bf16(x, 0.f)); }
__device__ __forceinline__ uint32_t hmul2(uint32_t a, uint32_t b) { uint32_t r; asm("mul.rn.bf16x2 %0, %1, %2;" : "=r"(r) : "r"(a), "r"(b)); return r; }
__device__ __forceinline__ uint32_t hsub2(uint32_t a, uint32_t b) { uint32_t r; asm("sub.rn.bf16x2 %0, %1, %2;" : "=r"(r) : "r"(a), "r"(b)); return r; }
__device__ __forceinline__ uint32_t hfma2(uint32_t a, uint32_t b, uint32_t c) { uint32_t r; asm("fma.rn.bf16x2 %0, %1, %2, %3;" : "=r"(r) : "r"(a), "r"(b), "r"(c)); return r; }
__device__ __forceinline__ uint4 ldg128(const void* p) { uint4 v; asm volatile("ld.global.nc.v4.u32 {%0, %1, %2, %3}, [%4];" : "=r"(v.x), "=r"(v.y), "=r"(v.z), "=r"(v.w) : "l"(p)); return v; }
__device__ __forceinline__ uint32_t ldg16(const void* p) { uint32_t v; asm volatile("ld.global.nc.u16 %0, [%1];" : "=r"(v) : "l"(p)); return v; }
__device__ __forceinline__ float tanh_ordered(float x) { float y; asm volatile("tanh.approx.f32 %0, %1;" : "=f"(y) : "f"(x)); return y; }
__device__ __forceinline__ uint32_t tanh2_ordered(uint32_t x) { uint32_t y; asm volatile("tanh.approx.bf16x2 %0, %1;" : "=r"(y) : "r"(x)); return y; }
__device__ __forceinline__ void mma16816(float (&d)[4], uint32_t a0, uint32_t a1, uint32_t a2, uint32_t a3, uint32_t b0, uint32_t b1) {
  asm("mma.sync.aligned.m16n8k16.row.col.f32.bf16.bf16.f32 {%0, %1, %2, %3}, {%4, %5, %6, %7}, {%8, %9}, {%0, %1, %2, %3};"
      : "+f"(d[0]), "+f"(d[1]), "+f"(d[2]), "+f"(d[3]) : "r"(a0), "r"(a1), "r"(a2), "r"(a3), "r"(b0), "r"(b1));
}
__device__ __forceinline__ uint32_t hadd2(uint32_t a, uint32_t b) { uint32_t r; asm("add.rn.bf16x2 %0, %1, %2;" : "=r"(r) : "r"(a), "r"(b)); return r; }
__device__ __forceinline__ uint32_t ldg32(const void* p) { uint32_t v; asm volatile("ld.global.nc.L1::no_allocate.u32 %0, [%1];" : "=r"(v) : "l"(p)); return v; }
__device__ __forceinline__ uint2 lds64(uint32_t a) { uint2 v; asm volatile("ld.shared.v2.u32 {%0, %1}, [%2];" : "=r"(v.x), "=r"(v.y) : "r"(a) : "memory"); return v; }
__device__ __forceinline__ uint32_t lds32_if(uint32_t a, uint32_t on) {
  uint32_t v;
  asm volatile("{\n.reg .pred p;\nsetp.ne.u32 p, %2, 0;\n@p ld.shared.u32 %0, [%1];\n}" : "=r"(v) : "r"(a), "r"(on) : "memory");
  return v;
}
__device__ __forceinline__ uint32_t clock_now() { uint32_t t; asm volatile("mov.u32 %0, %%clock;" : "=r"(t)); return t; }
__device__ __forceinline__ uint32_t time_now() { uint32_t t; asm volatile("mov.u32 %0, %%globaltimer_lo;" : "=r"(t)); return t; }
__device__ __forceinline__ void spin_until(uint32_t t0, uint32_t n) { while (clock_now() - t0 < n) {} }
__device__ __forceinline__ uint2 ldg64_if(const void* p, uint32_t on) {
  uint2 v;
  asm volatile("{\n.reg .pred p;\nsetp.ne.u32 p, %3, 0;\n@p ld.global.nc.v2.u32 {%0, %1}, [%2];\n}" : "=r"(v.x), "=r"(v.y) : "l"(p), "r"(on));
  return v;
}
template <class T> __device__ __forceinline__ T pin(T v) { asm volatile("" : "+r"(v)); return v; }
__device__ __forceinline__ void st_async2(uint32_t raddr, uint32_t a, uint32_t b, uint32_t rbar) {
  asm volatile("st.async.weak.shared::cluster.mbarrier::complete_tx::bytes.v2.b32 [%0], {%1, %2}, [%3];" ::"r"(raddr), "r"(a), "r"(b), "r"(rbar) : "memory");
}
__device__ __forceinline__ void bulk_prefetch(const void* src, uint32_t sz, uint64_t pol) {
  asm volatile("cp.async.bulk.prefetch.L2.global.L2::cache_hint [%0], %1, %2;" ::"l"(src), "r"(sz), "l"(pol) : "memory");
}
__device__ __forceinline__ void bulk_wait_read() { asm volatile("cp.async.bulk.wait_group.read 0;" ::: "memory"); }
__device__ __forceinline__ uint32_t shfl_ordered(uint32_t v, int src) { uint32_t r; asm volatile("shfl.sync.idx.b32 %0, %1, %2, 0x1f, 0xffffffff;" : "=r"(r) : "r"(v), "r"(src)); return r; }
__device__ __forceinline__ int chan_pos(int d) {
  return d < 512 ? 72 * (d >> 6) + ((d & 33) | ((d & 6) << 2) | ((d >> 2) & 6)) : 72 * ((d - 512) >> 3) + 64 + (d & 7);
}

struct Ring {
  uint32_t s, ph;
  __device__ __forceinline__ void next() { if (++s == ST) { s = 0; ph ^= 1; } }
};
constexpr int B_FULL = 0, B_GO = 40, B_CFULL = 48, B_SEMPTY = 80, B_ZFULL = 96, B_RFULL = 104, B_UDONE = 120, B_KFULL = 136, B_RAW = 168, B_CVGO = 248, B_PEER = 256, B_G2GO = 264, B_KVGO = 280,
              B_EMPTY = 296, B_G1DONE = 336,
              B_CEMPTY = 344, B_SFULL = 376, B_USTG = 392, B_END = 408;

__device__ __forceinline__ void wait_counter(uint32_t* f, int idx, uint32_t want, uint32_t first, uint32_t nap) {
#pragma unroll 1
  for (uint32_t spins = 0; first != want; spins++) {
    if (nap && spins) __nanosleep(nap);
    first = flag_ld(f, idx);
    if (spins > SPIN_LIMIT) asm volatile("trap;");
  }
  fence_async_global();
}

__device__ __forceinline__ void gate_arrive(uint32_t* f, uint32_t back) {
  asm volatile("red.relaxed.gpu.global.max.u32 [%0], %1;" ::"l"(f + FL_GATE * 32 + 1), "r"(time_now() - back) : "memory");
  flag_add(f, FL_GATE, 1);
}

__device__ __forceinline__ float ln_rinv(float var) {
  float rt, rinv;
  asm("sqrt.approx.ftz.f32 %0, %1;" : "=f"(rt) : "f"(bf_round(bf_round(var) + 1e-5f)));
  asm("rcp.approx.ftz.f32 %0, %1;" : "=f"(rinv) : "f"(bf_round(rt)));
  return rinv;
}
__device__ __forceinline__ uint32_t ln_apply(uint32_t x, const uint4& st) {
  const uint32_t d = hsub2(x, st.x);
  return hfma2(d, st.y, hmul2(d, st.z));
}

__device__ __forceinline__ void polling_done(uint32_t* f, int lane) {
  unsigned old = 0;
  if (lane == 0) asm volatile("atom.relaxed.gpu.global.add.u32 %0, [%1], 1;" : "=r"(old) : "l"(f + FL_DONE * 32) : "memory");
  old = __shfl_sync(0xffffffffu, old, 0);
  if (old == NCTA + NG2 - 1) {
    if (lane < FL_N) *(uint2*)(f + lane * 32) = make_uint2(0u, 0u);
  }
}

struct Pipe { Ring r; uint32_t prev; bool pending; int cnt; };
__device__ __forceinline__ void pipe_drain(Pipe& p, uint32_t bars, bool leader) {
  wg_wait<0>();
  if (leader) mbar_arrive(bars + B_EMPTY + p.prev * 8);
  p.pending = false;
}
template <int TB, int LEAD, int R>
__device__ __forceinline__ void gemm_run(float (&acc)[R], int n, int accumulate, Pipe& p, uint32_t sb, uint32_t pitch, int wg, bool leader) {
  const uint32_t bars = sb + BAR_OFF;
  const uint32_t dA0 = desc_lo(sb + wg * 8192, 8192), dB0 = desc_lo(sb + ASZ, TB ? 128 : 16);
  constexpr int KB_STEP = TB ? 16 : 2;
#pragma unroll 1
  for (int kb = 0; kb < n; kb++) {
    if (LEAD && kb == n - LEAD && wg == 1) { if (TB) pipe_drain(p, bars, leader); named_bar(8, 256); }
    mbar_wait(bars + B_FULL + p.r.s * 8, p.r.ph);
    if (kb == 0 && !accumulate && threadIdx.x == 0) { PROF(21 + TB); PROFC(49 - 2 * TB); }
    const uint32_t dA = dA0 + p.r.s * (pitch >> 4), dB = dB0 + p.r.s * (pitch >> 4);
    wg_fence();
    wgmma_ss<TB>(acc, dA, dB, accumulate | kb);
#pragma unroll
    for (int k = 1; k < 4; k++) wgmma_ss<TB>(acc, dA + k * 128, dB + k * KB_STEP, 1);
    wg_commit();
    wg_wait<1>();
    if (p.pending && leader) mbar_arrive(bars + B_EMPTY + p.prev * 8);
    p.pending = true;
    p.prev = p.r.s;
    p.r.next();
  }
  if (LEAD && wg == 0) named_arrive(8, 256);
}

template <int BROW0, int I0, int I1>
__device__ __forceinline__ void gemm2_part(float (&c)[36], uint32_t sb, uint32_t pitch, int wg) {
  const uint32_t dA0 = desc_lo(sb + wg * 8192, 8192), dB0 = desc_lo(sb + ASZ + BROW0 * 128, 16);
  wg_fence();
#pragma unroll
  for (int i = I0; i < I1; i++) {
    const int step = 68 - LAG + (i >> 2);
    if ((i & 3) == 0 && BROW0 == 0) mbar_wait_u(sb + BAR_OFF + B_FULL + (step % ST) * 8, (step / ST) & 1);
    if (i == 4 * LAG - TURN && BROW0 && wg == 0) named_arrive(7, 256);
    wgmma_ss<0>(c, dA0 + (step % ST) * (pitch >> 4) + (i & 3) * 128, dB0 + (step % ST) * (pitch >> 4) + (i & 3) * 2, 1);
  }
  wg_commit();
}
__device__ __forceinline__ void split_acc(const float (&acc)[72], float (&a)[36], float (&b)[36]) {
#pragma unroll
  for (int i = 0; i < 36; i++) { asm volatile("mov.b32 %0, %1;" : "=f"(a[i]) : "f"(acc[i])); asm volatile("mov.b32 %0, %1;" : "=f"(b[i]) : "f"(acc[36 + i])); }
}
template <int NV, int R, class Slice>
__device__ __forceinline__ void gelu_store(const float (&acc)[R], uint32_t bias0, uint32_t bias1, uint32_t sa, uint32_t zero, Slice slice) {
  const uint32_t bb[2] = {pin(bias0) * 0x10001u, pin(bias1) * 0x10001u};
  uint32_t x[2][4], t[2][4], dep[NV / 8], c3 = 0x3d123d12u;
#pragma unroll
  for (int j = 0; j <= NV / 8; j++) {
    if (j < NV / 8) {
      if (j >= GLAG) c3 = (dep[j - GLAG] & zero) | 0x3d123d12u;
#pragma unroll
      for (int u = 0; u < 4; u++) {
        x[j & 1][u] = hadd2(pack_bf16(acc[8 * j + 2 * u], acc[8 * j + 2 * u + 1]), bb[u & 1]);
        t[j & 1][u] = tanh2_ordered(hmul2(x[j & 1][u], hfma2(hmul2(x[j & 1][u], c3), x[j & 1][u], 0x3f4c3f4cu)));
      }
    }
    if (j > 0) {
      const uint32_t *xx = x[(j - 1) & 1], *tt = t[(j - 1) & 1];
      stsm4_t(sa + (j - 1) * 2048, hfma2(xx[0], tt[0], xx[0]), hfma2(xx[1], tt[1], xx[1]), hfma2(xx[2], tt[2], xx[2]), hfma2(xx[3], tt[3], xx[3]));
      dep[j - 1] = slice(j - 1);
    }
  }
}
struct Role { int half, kind, g2_m, dt, g1_mt, g1_nt, cs; uint32_t pitch; };
__device__ __forceinline__ Role get_role(const RoleMap& roles) {
  uint32_t b, sm;
  asm volatile("mov.u32 %0, %%ctaid.x;" : "=r"(b));
  asm volatile("mov.u32 %0, %%smid;" : "=r"(sm));
  const uint32_t w = roles.role[(roles.by_sm ? sm : b) >> 1];
  const int half = b & 1, kind = w & 3, m = (w >> 4) & 15, dt = (w >> 2) & 3;
  return Role{half, kind, m * 128, dt, half * 18 + (int)((w >> 8) & 31), (int)(w >> 16), (m * 4 + dt) * 2 + half, kind ? (uint32_t)PITCH_B : (uint32_t)PITCH_S};
}
__device__ __forceinline__ int g2_block(int half, int j) { return half * 36 + (j < 12 ? 2 * j : j < 24 ? 2 * j - 23 : j); }
__device__ __forceinline__ int conv_chan(int cs, int i) { return (3 * (cs >> 5) + (i >> 1)) * 64 + ((2 * cs) & 63) + (i & 1); }
__device__ __forceinline__ uint32_t conv_buf(uint32_t sb, int b) { return sb + (b == 3 ? (36 % ST) * PITCH_S : ST * PITCH_S + b * CBUF); }

__global__ void __cluster_dims__(2, 1, 1) __launch_bounds__(384, 1)
fused_kernel(const __nv_bfloat16* __restrict__ q, Scratch* __restrict__ gs, const __nv_bfloat16* __restrict__ b1,
             const __nv_bfloat16* __restrict__ shiftk, const __nv_bfloat16* __restrict__ ssmk, const __nv_bfloat16* __restrict__ ssmD,
             const __grid_constant__ CUtensorMap tmW1, const __grid_constant__ CUtensorMap tmW2, const __grid_constant__ CUtensorMap tmZ,
             const __grid_constant__ CUtensorMap tmH, const __grid_constant__ CUtensorMap tmK, const __grid_constant__ CUtensorMap tmV,
             const __grid_constant__ CUtensorMap tmKV, const __grid_constant__ CUtensorMap tmKL, const __grid_constant__ RoleMap roles, const __nv_bfloat16* __restrict__ b2,
             __nv_bfloat16* __restrict__ out) {
  const int cta = blockIdx.x;
  const int tid = threadIdx.x;
  if (tid == 288) PROFG(0);

  const uint32_t t_start = clock_now();
  if (tid == 256) { prefetch_map(&tmW1); prefetch_map(&tmH); }
  const int lc = (cta + LNROT) & 127;
  const uint32_t do_ln = cta < 128 && tid < 256;
  const int oct = lc + (tid & 128), ln_row = oct * 8 + ((tid >> 4) & 7), l16 = tid & 15;
  uint2 xr[9];
  if (do_ln && oct >= TN(QLATE)) spin_until(t_start, TN(QDELAY) + TN(QRAMP) * oct / 2);
#pragma unroll
  for (int i = 0; i < 9; i++) xr[i] = ldg64_if(q + (size_t)ln_row * D_ + i * 64 + l16 * 4, do_ln);
  if (tid == 0) PROF(32);
  const int warp = __shfl_sync(0xffffffffu, tid >> 5, 0);
  const uint32_t sb = __shfl_sync(0xffffffffu, (uint32_t)__cvta_generic_to_shared(smem_raw), 0);
  const uint32_t bars = sb + BAR_OFF;
  const int lane = tid & 31;
  const int wg = warp >> 2;
  constexpr int LN_OFF = ST * PITCH_B;

  if (warp < 8 || warp == 11) {
    asm volatile("barrier.cluster.arrive.relaxed.aligned;" ::: "memory");
    const int hq = (lane & 16) >> 3, hb = (lane & 16) + hq;
    float da[3][4] = {};
#pragma unroll
    for (int i = 0; i < 9; i++) mma16816(da[i % 3], xr[i].x, 0x3f803f80u, xr[i].y, 0x3f803f80u, xr[i].x, xr[i].y);
    const float r1 = ((da[0][2] + da[0][3]) + (da[1][2] + da[1][3])) + (da[2][2] + da[2][3]);
    const float r2 = (lane & 4) ? (da[0][1] + da[1][1]) + da[2][1] : (da[0][0] + da[1][0]) + da[2][0];
    const float s1 = __shfl_sync(0xffffffffu, r1, hq) + __shfl_sync(0xffffffffu, r1, hq + 1);
    const float s2 = (__shfl_sync(0xffffffffu, r2, hb) + __shfl_sync(0xffffffffu, r2, hb + 4)) + (__shfl_sync(0xffffffffu, r2, hb + 9) + __shfl_sync(0xffffffffu, r2, hb + 13));
    if (tid == 0) { asm volatile("" ::"f"(s2) : "memory"); PROF(27); }
    const float mean = s1 * (1.f / D_), var = fmaxf(fmaf(-mean, mean, s2 * (1.f / D_)), 0.f);
    const float rinv = ln_rinv(var), rinv2 = ln_rinv(var * rinv * rinv), scale = rinv * rinv2, shift = -bf_round((mean - bf_round(mean)) * rinv) * rinv2;
    const uint32_t m2 = pack_bf16(mean, mean), hi2 = pack_bf16(scale, scale), lo2 = pack_bf16(scale - bf_lo(hi2), scale - bf_lo(hi2)), sh2 = pack_bf16(shift, shift);
    const uint32_t hi1 = pack_bf16(rinv, rinv);
    asm volatile("{\n.reg .pred p;\nsetp.eq.u32 p, %5, 0;\n@p st.shared.v4.u32 [%0], {%1, %2, %3, %4};\n}" ::"r"(sb + LN_OFF + 18432 + tid), "r"(m2), "r"(hi1),
                 "r"(pack_bf16(rinv - bf_lo(hi1), rinv - bf_lo(hi1))), "r"(0u), "r"(tid & 0x10f) : "memory");
    const uint32_t g0 = 4 * (l16 >> 3) + 2 * (l16 & 1), hrow = sb + LN_OFF + ((tid >> 7) & 1) * 9216 + (tid & 0x70);
    const uint32_t hs0 = hrow + g0 * 128 + ((l16 >> 1) & 3) * 4, hs8 = ((hrow + (l16 >> 1) * 1152) ^ ((l16 >> 1) << 4)) + 1024 + (l16 & 1) * 8;
    uint32_t w[18];
#pragma unroll
    for (int i = 0; i < 18; i++) {
      const uint32_t d = hsub2((i & 1) ? xr[i >> 1].y : xr[i >> 1].x, m2);
      asm("max.u32 %0, %1, 1;" : "=r"(w[i]) : "r"(hfma2(d, hi2, hfma2(d, lo2, sh2))));
    }
#pragma unroll
    for (int i = 0; i < 16; i++) {
      const int gi = 9 * (i >> 1) + (i & 1);
      asm volatile("{\n.reg .pred p;\nsetp.ne.u32 p, %2, 0;\n@p st.shared.u32 [%0], %1;\n}" ::"r"((hs0 ^ ((g0 * 16 + (gi & 7) * 16) & 0x70)) + gi * 128), "r"(w[i]), "r"(do_ln) : "memory");
    }
    asm volatile("{\n.reg .pred p;\nsetp.ne.u32 p, %3, 0;\n@p st.shared.v2.u32 [%0], {%1, %2};\n}" ::"r"(hs8), "r"(w[16]), "r"(w[17]), "r"(do_ln) : "memory");
    if (tid == 224) PROF(13);
    fence_async_smem();
    if (warp < 8) named_arrive(wg, 160);
  } else if (warp != 8) {
    spin_until(t_start, TN(W9));
  }

  if (wg == 2) {
    asm volatile("setmaxnreg.dec.sync.aligned.u32 56;");
    auto store_h = [&](int w) {
      named_bar(w, 160);
      if (cta < 128 && elect_one()) {
        tma3d_store(&tmH, ((lc >> 3) + 16 * w) * 72, lc & 7, sb + LN_OFF + w * 9216);
        bulk_s2g(gs->stats + (lc + 128 * w) * 8, sb + LN_OFF + 18432 + w * 128, 128);
        bulk_commit();
      }
    };
    auto publish_h = [&](int w) {
      if (cta < 128 && elect_one()) { bulk_wait_all(); flag_add(gs->flags, FL_H + (w ? 2 : lc >> 6), 1); }
      __syncwarp();
    };
    uint32_t look = 0;
    if (warp == 11) {
      if (lc >= 64) spin_until(t_start, TN(HW));
      store_h(0);
      look = flag_ld(gs->flags, FL_H);
      if (lc < 64) publish_h(0);
      if (lane == 0) PROF(1);
    } else {
      if (elect_one()) {
        if (warp == 8) {
#pragma unroll
          for (int o = 0; o < B_GO; o += 8) mbar_init(bars + o, 1);
        } else if (warp == 9) {
#pragma unroll
          for (int o = B_GO; o < B_RAW + 40; o += 8) mbar_init(bars + o, 1);
        } else {
#pragma unroll
          for (int o = B_RAW + 40; o < B_END; o += 8) mbar_init(bars + o, o < B_EMPTY ? 1 : o < B_CEMPTY ? 2 : 4);
        }
        asm volatile("fence.mbarrier_init.release.cluster;" ::: "memory");
      }
      __syncwarp();
      asm volatile("barrier.cluster.arrive.relaxed.aligned;" ::: "memory");
      if (warp == 9) { prefetch_map(&tmK); prefetch_map(&tmV); prefetch_map(&tmKV); prefetch_map(&tmKL); prefetch_map(&tmW2); prefetch_map(&tmZ); }
      if (tid == 256) PROF(35);
    }
    const Role ro = get_role(roles);
    if (warp != 8) asm volatile("barrier.cluster.wait.aligned;" ::: "memory");
    if (warp == 11) {
      Ring r{0, 1};
      const uint32_t bsz = ro.pitch - ASZ;
      const uint8_t* src = gs->h + ro.g1_nt * bsz + ST * 73728;
      named_bar(10, 64);
#pragma unroll 1
      for (int i = ST; i < 32; i++) {
        if (i == ST || i == 8 || i == 16) wait_counter(gs->flags, FL_H + (i >> 3), i == 16 ? 128u : 64u, look, 0);
        if (i == TN(LK1) || i == TN(LK2)) look = flag_ld(gs->flags, FL_H + (i >> 3) + 1);
        mbar_wait(bars + B_EMPTY + r.s * 8, r.ph ^ 1);
        if (elect_one()) bulk_g2s(sb + r.s * ro.pitch + ASZ, src, bsz, bars + B_FULL + r.s * 8);
        if (i == ST && lane == 0) PROF(25);
        if (i == TN(HS2)) store_h(1);
        if (i == TN(HS2) + 2 || (i == ST && lc >= 64)) publish_h(i != ST);
        if (i == TN(KVGO1) && lane == 0) mbar_arrive(bars + B_KVGO + 8);
        if (i == TN(KVGO) && lane == 0) mbar_arrive(bars + B_KVGO);
        if (i == TN(CVGO) && lane == 0) mbar_arrive(bars + B_CVGO);
        src += 73728;
        r.next();
      }
      if (ro.kind != 2) {
        look = 0;
#pragma unroll 1
        for (int j = 0; j < 36; j++) {
          const uint8_t* su = gs->u + ((size_t)g2_block(ro.half, j) * D_ + ro.dt * 144) * 128;
          if (j == 0 || j == 12 || j == 24) wait_counter(gs->flags, FL_U + ro.half * 3 + j / 12, j == 24 ? 36u : 48u, look, 100);
          if (ro.kind ? j == 4 : j < 2) mbar_wait_u(bars + B_UDONE + (j ? 8 : 0), 0);
          mbar_wait(bars + B_EMPTY + r.s * 8, r.ph ^ 1);
          if (elect_one()) {
            bulk_g2s(sb + r.s * ro.pitch + ASZ, su + (ro.half ^ 1) * 9216, 9216, bars + B_FULL + r.s * 8);
            bulk_g2s(sb + r.s * ro.pitch + ASZ + 9216, su + ro.half * 9216, 9216, bars + B_FULL + r.s * 8);
          }
          if (j == 9 || j == 21) look = flag_ld(gs->flags, FL_U + ro.half * 3 + j / 12 + 1);
          if (j == 0 && lane == 0) PROF(8);
          r.next();
        }
#pragma unroll 1
        for (int o = lane; o < ST * 73728 / 16 / NG2; o += 32) ((uint4*)gs->h)[ro.cs * (ST * 73728 / 16 / NG2) + o] = make_uint4(0u, 0u, 0u, 0u);
      }
      polling_done(gs->flags, lane);
    } else if (warp == 8) {
      const uint64_t pol = stream_policy();
      Ring r{0, 0};
#pragma unroll 1
      for (int i = 0; i < 32; i++) {
        if (i < ST) spin_until(t_start, TN(A0) + i * TN(AD) + (i >= TN(AN) ? TN(AL) : 0));
        if (i == ST) {
          asm volatile("barrier.cluster.wait.aligned;" ::: "memory");
          if (roles.by_sm) {
            uint32_t sm;
            asm volatile("mov.u32 %0, %%smid;" : "=r"(sm));
            if (elect_one()) { mbar_expect(bars + B_PEER, 8); st_async2(mapa(bars + B_END, ro.half ^ 1), sm, sm, mapa(bars + B_PEER, ro.half ^ 1)); }
            mbar_wait_u(bars + B_PEER, 0);
            if ((lds32(bars + B_END) ^ sm) != 1 || sm >= NCTA) asm volatile("trap;");
          }
        }
        if (i >= ST) mbar_wait(bars + B_EMPTY + r.s * 8, r.ph ^ 1);
        if (elect_one()) {
          mbar_expect(bars + B_FULL + r.s * 8, ro.pitch);
          tma_weights(sb + r.s * ro.pitch, &tmW1, i * 64, ro.g1_mt * 2, bars + B_FULL + r.s * 8, pol);
        }
        r.next();
      }
      if (ro.kind != 2) {
#pragma unroll 1
        for (int j = 0; j < 36; j++) {
          if (j == 4 && ro.kind == 0) mbar_wait_u(bars + B_CEMPTY + 24, 0);
          mbar_wait(bars + B_EMPTY + r.s * 8, r.ph ^ 1);
          if (elect_one()) {
            mbar_expect(bars + B_FULL + r.s * 8, PITCH_S);
            tma_weights(sb + r.s * ro.pitch, &tmW2, g2_block(ro.half, j) * 64, ro.g2_m >> 6, bars + B_FULL + r.s * 8, pol);
          }
          r.next();
        }
        if (lane < 2) mbar_expect(bars + B_RFULL + lane * 8, 9216);
        __syncwarp();
        mbar_wait(bars + B_EMPTY + r.s * 8, r.ph ^ 1);
        if (lane == 0) mbar_arrive_cluster(mapa(bars + B_GO, ro.half ^ 1));
      }
      if (lane == 0) PROF(28);
    } else {
      const uint64_t pol = stream_policy();
      {
        const uint32_t hb = (ro.pitch - ASZ) >> 1, raw = bars + B_RAW + (warp - 9) * 40, dst = sb + ASZ + (warp - 9) * hb;
        const uint8_t* src = gs->h + (2 * ro.g1_nt + warp - 9) * hb;
        auto fetch_h = [&](int i) { if (elect_one()) { mbar_expect(raw + i * 8, hb); bulk_g2s(dst + i * ro.pitch, src + i * 73728, hb, raw + i * 8); } };
        int next = 0;
#pragma unroll 1
        for (int i = -1; i < ST; i++) {
          if (i >= 0) {
#pragma unroll 1
            for (uint32_t tries = 0;; tries++) {
              mbar_wait_u(raw + i * 8, tries & 1);
              if (lane == 0 && i == 0) PROF(29 + warp);
              const uint32_t pa = dst + i * ro.pitch + lane * 32 + (lane >> 2) * 4;
              uint32_t m = 1;
#pragma unroll
              for (int j = 0; j < 12; j++) m = min(m, lds32(pa + (j < 9 || ro.kind ? j : 0) * 1024));
              if (__all_sync(0xffffffffu, m)) break;
              if (lane == 0) PROF(26);
              fetch_h(i);
            }
            if (elect_one()) asm volatile("mbarrier.complete_tx.relaxed.cta.shared::cta.b64 [%0], %1;" ::"r"(bars + B_FULL + i * 8), "r"(hb) : "memory");
          }
#pragma unroll 1
          for (const int end = min(next + 2, ST); next < end; next++) {
            if (i < 0) spin_until(t_start, TN(H0) + next * TN(HD));
            fetch_h(next);
            if (next == 0 && tid == 288) PROF(3);
          }
          if (i < 0 && warp == 10) named_arrive(10, 64);
        }
      }
      if (ro.kind == 0) {
        mbar_wait_u(bars + B_KVGO + (warp - 9) * 8, 0);
        const int cs = ro.cs, grp = (cs / 3) * 2 + warp - 9, cb0 = (cs % 3) * 3;
        const uint32_t kin_s = sb + ST * PITCH_S + (warp - 9) * KVW, kout = kin_s + 2 * KVIN, fb = bars + B_KFULL + (warp - 9) * 16;
        auto fetch = [&](int i) {
          if (elect_one()) {
            mbar_expect(fb + (i & 1) * 8, KVIN);
            tma2d_stream(kin_s + (i & 1) * KVIN, &tmK, (cb0 + i) * 64, grp * 32 - 4, fb + (i & 1) * 8, pol);
            tma2d_stream(kin_s + (i & 1) * KVIN + 4608, &tmV, (cb0 + i) * 64, grp * 32 - 1, fb + (i & 1) * 8, pol);
          }
        };
        fetch(0);
        uint4 shk = ldg128(shiftk + (cb0 * 64 + lane * 2) * 4);
        const uint32_t dskip = ldg16(ssmD + conv_chan(cs, lane < NCONV ? lane : 0));
#pragma unroll 1
        for (int i = 0; i < 3; i++) {
          const uint32_t w0 = __byte_perm(shk.x, shk.z, 0x5410), w1 = __byte_perm(shk.x, shk.z, 0x7632);
          const uint32_t w2 = __byte_perm(shk.y, shk.w, 0x5410), w3 = __byte_perm(shk.y, shk.w, 0x7632);
          const uint32_t ka = kin_s + (i & 1) * KVIN + lane * 4;
          mbar_wait_u(fb + (i & 1) * 8, i >> 1);
          if (tid == 288 && i < 2) PROF(30 + i);
          if (i < 2) fetch(i + 1);
          shk = ldg128(i < 2 ? shiftk + ((cb0 + i + 1) * 64 + lane * 2) * 4 : ssmk + (size_t)conv_chan(cs, lane < NCONV ? lane : 0) * S_);
          uint32_t kr[8], vr[8], t1, t2, t3, xp;
          {
            const uint32_t k0 = lds32(ka), k1 = lds32(ka + 128), k2 = lds32(ka + 256), k3 = lds32(ka + 384), v0 = lds32(ka + 4608);
#pragma unroll
            for (int j = 0; j < 8; j++) { kr[j] = lds32(ka + 512 + j * 128); vr[j] = lds32(ka + 4736 + j * 128); }
            xp = hmul2(hfma2(k3, w0, hfma2(k2, w1, hfma2(k1, w2, hmul2(k0, w3)))), v0);
            t1 = hfma2(k3, w1, hfma2(k2, w2, hmul2(k1, w3)));
            t2 = hfma2(k3, w2, hmul2(k2, w3));
            t3 = hmul2(k3, w3);
          }
#pragma unroll 1
          for (int o = 0; o < 4; o++) {
            const uint32_t from = ka + o * 1024, to = kout + (o >> 1) * 5120 + lane * 80 + (o & 1) * 32;
#pragma unroll
            for (int m = 0; m < 8; m += 4) {
              uint32_t x[4];
#pragma unroll
              for (int j = 0; j < 4; j++) {
                x[j] = hmul2(hfma2(kr[m + j], w0, t1), vr[m + j]);
                t1 = hfma2(kr[m + j], w1, t2);
                t2 = hfma2(kr[m + j], w2, t3);
                t3 = hmul2(kr[m + j], w3);
              }
#pragma unroll
              for (int c = 0; c < 2; c++) {
                const uint32_t sel = c ? 0x7632 : 0x5410;
                sts128(to + c * 2560 + m * 4, __byte_perm(x[0], xp, sel), __byte_perm(x[1], x[0], sel), __byte_perm(x[2], x[1], sel), __byte_perm(x[3], x[2], sel));
              }
#pragma unroll
              for (int j = m; j < m + 4; j++) { kr[j] = lds32_if(from + 1536 + j * 128, o < 3); vr[j] = lds32_if(from + 5760 + j * 128, o < 3); }
              xp = x[3];
            }
            if (o & 1) {
              fence_async_smem();
              __syncwarp();
              if (elect_one()) {
                bulk_wait_all();
                if (o == 1 && i) flag_add(gs->flags, FL_KV + i - 1, 1);
                tma4d_store(&tmKV, (cb0 + i) * 32, 0, 2 * grp + (o >> 1), kout + (o >> 1) * 5120);
                bulk_commit();
              }
              __syncwarp();
            }
          }
        }
        shk.x = __byte_perm(pack_bf16(bf_lo(shk.x) + bf_lo(dskip), 0.f), shk.x, 0x7610);
        look = flag_ld(gs->flags, FL_KV + warp - 9);
        if (elect_one()) {
          bulk_wait_all();
          flag_add(gs->flags, FL_KV + 2, 1);
          bulk_prefetch(ssmk + (size_t)conv_chan(cs, 2 * (warp - 9)) * S_, 2 * S_ * 2, pol);
          if (warp == 9) PROFG(2);
        }
        __syncwarp();
#pragma unroll 1
        for (int i = warp == 9 ? 0 : 2; i < (warp == 9 ? 2 : NCONV); i++) {
          const int b = i & 3, d = conv_chan(cs, i);
          const uint32_t base = conv_buf(sb, b), cf = bars + B_CFULL + b * 8;
          if (!(i & 1)) wait_counter(gs->flags, FL_KV + (i >> 1), 192u, i < 4 ? look : 0u, 200);
          if (i == 2) { mbar_wait_u(bars + B_CVGO, 0); spin_until(clock_now(), 600); }
          if (i == 0 && lane == 0) PROF(23);
          if (i == 3) {
            mbar_wait_u(bars + B_G1DONE, 0);
            if (elect_one()) bulk_prefetch(ssmk + (size_t)conv_chan(cs, 4) * S_, 2 * S_ * 2, pol);
          }
          if (i >= 4) mbar_wait_u(bars + B_CEMPTY + b * 8, 0);
          if (lane == i) sts128(base + CH_OFF, shk.x, shk.y, shk.z, shk.w);
          if (lane >= 29) sts128(base + CH_OFF + (lane - 32) * 16, 0u, 0u, 0u, 0u);
          fence_async_smem();
          __syncwarp();
          if (elect_one()) mbar_expect(cf, 4080 + 64 * 160);
#pragma unroll 1
          for (int k = 0; k < 5; k++) {
            if (elect_one()) {
              if (k < 4) asm volatile("cp.async.bulk.tensor.3d.shared::cluster.global.mbarrier::complete_tx::bytes [%0], [%1, {%3, %4, %5}], [%2];"
                                      ::"r"(base + CT_OFF + k * 2560), "l"(&tmKL), "r"(cf), "r"(0), "r"(k * 16), "r"(d) : "memory");
              else bulk_g2s_stream(base + CH_OFF + 16, ssmk + (size_t)d * S_ + 8, 4080, cf, pol);
            }
          }
        }
      }
      if (warp == 9) {
        if (elect_one()) {
          const uint32_t bsz = ro.pitch - ASZ;
#pragma unroll 1
          for (int w = 0; w < 2; w++) {
            const uint32_t src = sb + (ro.kind ? (w ? (36 % ST) * PITCH_B + ASZ : ST * PITCH_B) : ((32 % ST) + w) * PITCH_S + ASZ);
            mbar_wait_u(bars + B_USTG + w * 8, 0);
            bulk_s2g(gs->u + (size_t)(2 * ro.g1_mt + w) * D_ * 128 + ro.g1_nt * bsz, src, bsz);
            bulk_commit();
            if (ro.kind && w == 0) gate_arrive(gs->flags, TN(GDELAY) - 512);
            bulk_wait_read();
            mbar_arrive(bars + B_UDONE + w * 8);
            bulk_wait_all();
            flag_add(gs->flags, FL_U + ro.half * 3 + (ro.kind ? 2 : w), 1);
            PROFG(5 + 12 * w);
          }
          if (ro.kind == 0) {
#pragma unroll 1
            for (int i = 0; i < NCONV; i++) {
              mbar_wait_u(bars + B_SFULL + (i & 1) * 8, (i >> 1) & 1);
              bulk_s2g(gs->z + (size_t)chan_pos(conv_chan(ro.cs, i)) * S_, sb + CSTG_OFF + (i & 1) * 4096, 4096);
              bulk_commit();
              if (i == NCONV - 3) gate_arrive(gs->flags, 0);
              bulk_wait_read();
              mbar_arrive(bars + B_SEMPTY + (i & 1) * 8);
            }
            bulk_wait_all();
            flag_add(gs->flags, FL_Z, 1);
            PROFG(6);
          }
        }
      } else if (ro.kind != 2) {
        mbar_wait_u(bars + B_UDONE, 0);
        uint2 gate;
#pragma unroll 1
        for (uint32_t spins = 0;; spins++) {
          asm volatile("ld.relaxed.gpu.global.v2.u32 {%0, %1}, [%2];" : "=r"(gate.x), "=r"(gate.y) : "l"(gs->flags + FL_GATE * 32) : "memory");
          if (gate.x == NCTA) break;
          __nanosleep(100);
          if (spins > SPIN_LIMIT) asm volatile("trap;");
        }
        if (lane == 0) PROF(46);
#pragma unroll 1
        for (int w = 0; w < 2; w++) {
          while (time_now() - gate.y < TN(GDELAY) + w * TN(GDELAY1)) {}
          if (lane == 0) mbar_arrive(bars + B_G2GO + w * 8);
          if (lane == 0 && w == 0) PROF(24);
        }
        wait_counter(gs->flags, FL_Z, 96u, 0, 300);
        spin_until(clock_now(), TN(ZDELAY) + TN(ZRAMP) * cta);
        if (elect_one()) {
          mbar_expect(bars + B_ZFULL, 18432);
          tma2d(sb + ST * ro.pitch, &tmZ, ro.g2_m, ro.dt * 144 + ro.half * 72, bars + B_ZFULL);
          tma2d(sb + ST * ro.pitch + 9216, &tmZ, ro.g2_m + 64, ro.dt * 144 + ro.half * 72, bars + B_ZFULL);
          PROFG(7);
        }
        polling_done(gs->flags, lane);
      }
    }
  } else {
    asm volatile("setmaxnreg.inc.sync.aligned.u32 224;");
    const int wi = warp & 3, g = lane >> 2, qd = lane & 3, wt = tid & 127;
    const bool leader = wt == 0;
    Pipe p{{0, 0}, 0, false, 0};
    asm volatile("barrier.cluster.wait.aligned;" ::: "memory");
    int kind;
    {
      const Role ro = get_role(roles);
      kind = ro.kind;
      const int f0 = ro.g1_mt * 128 + wg * 64 + wi * 16 + g;
      uint32_t bias0 = ldg16(b1 + f0), bias1 = ldg16(b1 + f0 + 8);
      const uint32_t so = ((lane >> 4) * 8 + (lane & 7)) * 128 + (((2 * wi + ((lane >> 3) & 1)) ^ (lane & 7)) << 4);
      if (kind) {
        float acc[96];
        gemm_run<1, LEAD_B>(acc, 32, 0, p, sb, PITCH_B, wg, leader);
        pipe_drain(p, bars, leader);
        if (wg) mbar_wait_u(bars + B_EMPTY + (36 % ST) * 8, ((36 / ST) & 1) ^ 1);
        if (leader) PROF(4 + 10 * wg);
        uint32_t sa = sb + (wg ? (36 % ST) * PITCH_B + ASZ : ST * PITCH_B) + so;
#pragma unroll 1
        for (int c = 0; c < 4; c++, sa += 6144) {
          gelu_store<24>(acc, bias0, bias1, sa, 0u, [](int) { return 0u; });
#pragma unroll
          for (int i = 0; i < 72; i++) acc[i] = acc[i + 24];
        }
        fence_async_smem();
        __syncwarp();
        if (lane == 0) mbar_arrive(bars + B_USTG + wg * 8);
        if (leader) PROF(15 + wg);
      } else {
        const int cB = (g >> 1) & 1, cA = g >> 2, b = 2 * wi + (g & 1);
        const uint32_t toff = pin(CT_OFF + (40 * (2 * cA + cB) + 8 + b - 2 * qd) * 4);
        const int phi = 2 * cA + (qd >> 1) + cB, pp = cB ? (phi & 3) : ((phi + 3) & 3);
        const int srcB = shfl_ordered(((pp >> 1) << 4) | ((cB ^ 1) << 3) | ((g & 1) << 2) | ((pp & 1) << 1) | (qd & 1), lane);
        const bool pB1 = cB && phi < 4, pB2 = cB && phi == 4;
        const int word = (8 * cB + 2 * (phi & 3) + (qd & 1)) * 8 + b;
        const uint32_t sto = shfl_ordered(sb + CSTG_OFF + wg * 4096 + (word ^ (((word >> 5) & 3) << 1)) * 4, lane);
        uint32_t a[16][4];
        auto load_a = [&](uint32_t base, int t, uint32_t on) {
          const uint32_t pt = base + toff + (t >> 1) * 1280 + (t & 1) * 64;
          a[t][0] = lds32_if(pt + 32, on); a[t][1] = lds32_if(pt + 672, on); a[t][2] = lds32_if(pt, on); a[t][3] = lds32_if(pt + 640, on);
        };
        {
          float acc[72];
          gemm_run<1, 0>(acc, 32 - LEAD_S - (wg ? 0 : PRE0), 0, p, sb, PITCH_S, wg, leader);
          if (wg == 1) pipe_drain(p, bars, leader);
          mbar_wait_u(bars + B_CFULL + wg * 8, 0);
#pragma unroll
          for (int t = 0; t < 8; t++) load_a(conv_buf(sb, wg), t, 1);
          if (wg == 1) named_bar(8, 256);
          gemm_run<1, 0>(acc, LEAD_S + (wg ? 0 : PRE0), 1, p, sb, PITCH_S, wg, leader);
          named_arrive(8 - 2 * wg, 256);
          mbar_wait_u(bars + B_EMPTY + ((32 % ST) + wg) * 8, ((32 / ST) & 1) ^ 1);
          pipe_drain(p, bars, leader);
          if (leader) mbar_arrive(bars + B_G1DONE);
          if (leader) PROF(4 + 10 * wg);
          if (tid == 128) PROFC(48);
          gelu_store<72>(acc, bias0, bias1, sb + ((32 % ST) + wg) * PITCH_S + ASZ + so, roles.by_sm >> 1, [&](int t) {
            return t + GLAG < 9 ? lds32(bars) : 0u;
          });
          fence_async_smem();
          __syncwarp();
          if (lane == 0) mbar_arrive(bars + B_USTG + wg * 8);
          if (leader) PROF(15 + wg);
        }
#pragma unroll 1
        for (int i = wg; i < NCONV; i += 2) {
          const uint32_t base = conv_buf(sb, i & 3), next = conv_buf(sb, (i + 2) & 3);
          const uint64_t dH = mkdesc(base + CH_OFF, 16, 128, 0);
          float y[8][16];
          named_bar(6 + wg, 256);
          wg_fence();
#pragma unroll
          for (int t = 0; t < 16; t++) {
            if (t == 8) wg_fence();
            if (t == CTURN) named_arrive(7 - wg, 256);
#pragma unroll
            for (int cb = t >> 1; cb < 8; cb++) {
              wgmma_rs_n32(y[cb], a[t][0], a[t][1], a[t][2], a[t][3], dH + (32 * cb - 32 * (t >> 1) - 2 * (t & 1) - 1), t);
              const int n = 8 * t - (t >> 1) * ((t - 1) >> 1) - (t >> 1) + cb + 1;
              if (n % CPER == 0 && n / CPER <= 8) load_a(base, 7 + n / CPER, 1);
            }
          }
          wg_commit();
          const bool more = i + 2 < NCONV;
          if (more) mbar_wait_u(bars + B_CFULL + ((i + 2) & 3) * 8, (i + 2) >> 2);
          mbar_wait_u(bars + B_SEMPTY + wg * 8, ((i >> 1) & 1) ^ 1);
          wg_wait<0>();
          if (lane == 0) mbar_arrive(bars + B_CEMPTY + (i & 3) * 8);
          if (leader) PROF(40 + i);
          uint32_t P[16], Q[16], R[16], o[8];
#pragma unroll
          for (int j = 0; j < 32; j++) {
            if ((j & 3) == 0) load_a(next, j >> 2, more);
            float v0 = y[j >> 2][4 * (j & 3)], v1 = y[j >> 2][4 * (j & 3) + 1];
            if (j >= 2) { v0 += y[(j - 2) >> 2][4 * ((j - 2) & 3) + 2]; v1 += y[(j - 2) >> 2][4 * ((j - 2) & 3) + 3]; }
            if (j & 1) R[j >> 1] = shfl_ordered(pack_bf16(v0, v1), lane ^ 16);
            else P[j >> 1] = pack_bf16(v0, v1);
          }
#pragma unroll
          for (int m = 0; m < 16; m++) Q[m] = hadd2(P[m], cA ? R[m] : (m ? R[m - 1] : 0u));
#pragma unroll
          for (int m = 0; m < 8; m++) o[m] = shfl_ordered(pB1 ? Q[2 * m] : (pB2 ? (m ? Q[2 * m - 1] : 0u) : Q[2 * m + 1]), srcB);
#pragma unroll
          for (int m = 0; m < 8; m++) sts32(sto + m * 512, hadd2(pB1 ? Q[2 * m + 1] : Q[2 * m], o[m]));
          fence_async_smem();
          __syncwarp();
          if (lane == 0) mbar_arrive(bars + B_SFULL + wg * 8);
          if (leader && i == 5) PROF(53);
        }
        if (wg == 0) named_bar(6, 256);
      }
    }
    if (kind != 2) {
      const Role ro = get_role(roles);
      const uint32_t pitch = ro.pitch;
      const int s0 = ro.g2_m + wg * 64 + wi * 16 + g;
      const size_t go = (size_t)s0 * D_ + ro.dt * 128 + ro.half * 64 + qd * 8, go8 = (size_t)s0 * D_ + 512 + ro.dt * 16 + ro.half * 8 + qd * 2;
      uint32_t x[2][9], sg[2][9];
      float acc[72];
      mbar_wait_u(bars + B_G2GO + wg * 8, 0);
      gemm_run<0, 0>(acc, XAT + 2 * wg, 0, p, sb, pitch, wg, leader);
#pragma unroll
      for (int J = 0; J < 4; J++) {
        const uint4 v = ldg128(q + go + (J & 1) * 8 * D_ + (J >> 1) * 32);
        x[J & 1][4 * (J >> 1)] = v.x; x[J & 1][4 * (J >> 1) + 1] = v.y; x[J & 1][4 * (J >> 1) + 2] = v.z; x[J & 1][4 * (J >> 1) + 3] = v.w;
      }
      x[0][8] = ldg32(q + go8); x[1][8] = ldg32(q + go8 + 8 * D_);
      const uint4 st0 = ld_l2(gs->stats + s0), st1 = ld_l2(gs->stats + s0 + 8);
      const uint32_t braw0 = ldg16(b2 + s0), braw1 = ldg16(b2 + s0 + 8);
      gemm_run<0, 0>(acc, 20 - XAT, 1, p, sb, pitch, wg, leader);
      {
        const int zw = 8 * wi + (g ^ ((((ro.g2_m >> 6) + wg) & 3) << 1));
        const uint32_t za = sb + ST * pitch + wg * 9216 + qd * 256 + (zw & 3) * 4;
        mbar_wait_u(bars + B_ZFULL, 0);
#pragma unroll
        for (int j = 0; j < 9; j++) {
          sg[0][j] = lds32(za + j * 1024 + (((zw >> 2) ^ (2 * qd)) << 4));
          sg[1][j] = lds32(za + j * 1024 + 128 + (((zw >> 2) ^ (2 * qd + 1)) << 4));
        }
      }
      gemm_run<0, 0>(acc, 1, 1, p, sb, pitch, wg, leader);
#pragma unroll
      for (int j = 0; j < 9; j++) {
        const uint32_t z0 = __byte_perm(sg[0][j], sg[1][j], 0x5410), z1 = __byte_perm(sg[0][j], sg[1][j], 0x7632);
        sg[0][j] = hmul2(ln_apply(x[0][j], st0), z0);
        sg[1][j] = hmul2(ln_apply(x[1][j], st1), z1);
        asm volatile("" : "+r"(sg[0][j]), "+r"(sg[1][j]));
      }
      gemm_run<0, SKEW>(acc, 15 - LAG - 2 * wg, 1, p, sb, pitch, wg, leader);
      const uint32_t rbuf = sb + (68 % ST) * pitch + warp * 2304;
      const uint32_t rdst = mapa(rbuf, ro.half ^ 1), rbar = mapa(bars + B_RFULL + wg * 8, ro.half ^ 1);
      pipe_drain(p, bars, leader);
      if (leader) PROF(9 + 10 * wg);
      if (tid == 128) PROFC(50);
      float cs[36], ck[36];
      split_acc(acc, cs, ck);
      gemm2_part<0, 0, 4 * LAG>(cs, sb, pitch, wg);
      if (KPRE) gemm2_part<72, 0, KPRE>(ck, sb, pitch, wg);
      const float hb0 = fmaf(bf_lo(braw0), 0.5f, __uint_as_float(st0.w)), hb1 = fmaf(bf_lo(braw1), 0.5f, __uint_as_float(st1.w));
      mbar_wait(bars + B_GO, 0);
      wg_wait<KPRE ? 1 : 0>();
      if (leader) PROF(54 + wg);
#pragma unroll
      for (int i = 0; i < 5; i++) {
        const float* c = &cs[8 * i];
        const uint32_t v0 = pack_bf16(fmaf(c[0], 0.25f, hb0), fmaf(c[1], 0.25f, hb0)), v1 = pack_bf16(fmaf(c[2], 0.25f, hb1), fmaf(c[3], 0.25f, hb1));
        if (i < 4) st_async4(rdst + i * 512 + lane * 16, v0, v1, pack_bf16(fmaf(c[4], 0.25f, hb0), fmaf(c[5], 0.25f, hb0)), pack_bf16(fmaf(c[6], 0.25f, hb1), fmaf(c[7], 0.25f, hb1)), rbar);
        else st_async2(rdst + 2048 + lane * 8, v0, v1, rbar);
      }
      if (wg == 1) named_bar(7, 256);
      gemm2_part<72, KPRE, 4 * LAG>(ck, sb, pitch, wg);
      uint32_t rp[18];
      mbar_wait(bars + B_RFULL + wg * 8, 0);
#pragma unroll
      for (int m = 0; m < 4; m++) {
        const uint4 v = lds128(rbuf + m * 512 + lane * 16);
        rp[4 * m] = v.x; rp[4 * m + 1] = v.y; rp[4 * m + 2] = v.z; rp[4 * m + 3] = v.w;
      }
      { const uint2 v = lds64(rbuf + 2048 + lane * 8); rp[16] = v.x; rp[17] = v.y; }
      __nv_bfloat16* o = out + go;
      wg_wait<0>();
      if (leader) PROF(10 + 10 * wg);
      float h[2][4], t[2][4], half = 0.25f;
#pragma unroll
      for (int j = 0; j <= 9; j++) {
        if (j < 9) {
          const uint32_t ra = rp[2 * j], rb = rp[2 * j + 1];
          if (j >= 2) half = fmaf(t[j & 1][3], 0.f, 0.25f);
          h[j & 1][0] = fmaf(ck[4 * j], half, bf_lo(ra)); h[j & 1][1] = fmaf(ck[4 * j + 1], half, bf_hi(ra));
          h[j & 1][2] = fmaf(ck[4 * j + 2], half, bf_lo(rb)); h[j & 1][3] = fmaf(ck[4 * j + 3], half, bf_hi(rb));
#pragma unroll
          for (int u = 0; u < 4; u++) t[j & 1][u] = tanh_ordered(h[j & 1][u]);
        }
        if (j > 0) {
          const int k = j - 1;
          const float* hh = h[k & 1];
          const float* tt = t[k & 1];
          x[0][k] = hfma2(sg[0][k], pack_bf16(fmaf(hh[0], tt[0], hh[0]), fmaf(hh[1], tt[1], hh[1])), x[0][k]);
          x[1][k] = hfma2(sg[1][k], pack_bf16(fmaf(hh[2], tt[2], hh[2]), fmaf(hh[3], tt[3], hh[3])), x[1][k]);
          if ((k & 3) == 3) {
            *(uint4*)(o + (k >> 2) * 32) = make_uint4(x[0][k - 3], x[0][k - 2], x[0][k - 1], x[0][k]);
            *(uint4*)(o + 8 * D_ + (k >> 2) * 32) = make_uint4(x[1][k - 3], x[1][k - 2], x[1][k - 1], x[1][k]);
          }
        }
      }
      *(uint32_t*)(out + go8) = x[0][8];
      *(uint32_t*)(out + go8 + 8 * D_) = x[1][8];
      if (leader) PROF(11 + 7 * wg);
      if (tid == 128) PROFC(51);
    }
  }
}

typedef CUresult (*EncodeFn)(CUtensorMap*, CUtensorMapDataType, cuuint32_t, void*, const cuuint64_t*, const cuuint64_t*, const cuuint32_t*,
                             const cuuint32_t*, CUtensorMapInterleave, CUtensorMapSwizzle, CUtensorMapL2promotion, CUtensorMapFloatOOBfill);

uint32_t role_of_pair(int t) {
  int grp, i;
  if (t < 32) { const int j = t & 7; i = t >> 3; grp = j < 6 ? 1 + j : 12 + 2 * (j - 6); }
  else if (t < 60) { const int j = (t - 32) % 7; i = (t - 32) / 7; grp = j < 5 ? 7 + j : 13 + 2 * (j - 5); }
  else if (t < 62) return 2u | (uint32_t)(14 + 3 * (t - 60)) << 8 | 2u << 16;
  else { grp = 0; i = t - 62; }
  if (grp < 12) return (uint32_t)(i << 2 | grp << 4 | grp << 8 | i << 16);
  const int u = (grp & 1) * 4 + i;
  return (uint32_t)(1 | i << 2 | grp << 4 | (12 + 3 * ((grp - 12) >> 1) + u / 3) << 8 | (u % 3) << 16);
}

}

extern "C" void kernel_launch(void* const* d_in, const int* in_sizes, int n_in, void* d_out, int out_size) {
  (void)in_sizes; (void)n_in; (void)out_size;
  EncodeFn enc = nullptr;
  cudaDriverEntryPointQueryResult qr;
  cudaGetDriverEntryPoint("cuTensorMapEncodeTiled", (void**)&enc, cudaEnableDefault, &qr);
  Scratch* gs = nullptr;
  cudaGetSymbolAddress((void**)&gs, g_scratch);
  void *zp = gs->z, *hp = gs->h, *kvp = gs->kv + 128;
  CUtensorMap tmW1, tmW2, tmZ, tmH, tmK, tmV, tmKV, tmKL;
  for (int w = 0; w < 2; w++) {
    cuuint64_t gd[2] = {D_, S_};
    cuuint64_t st[1] = {D_ * 2};
    cuuint32_t bx[2] = {64, w ? 33u : 36u};
    cuuint32_t es[2] = {1, 1};
    enc(w ? &tmV : &tmK, CU_TENSOR_MAP_DATA_TYPE_BFLOAT16, 2, d_in[1 + w], gd, st, bx, es, CU_TENSOR_MAP_INTERLEAVE_NONE, CU_TENSOR_MAP_SWIZZLE_NONE,
        CU_TENSOR_MAP_L2_PROMOTION_L2_128B, CU_TENSOR_MAP_FLOAT_OOB_FILL_NONE);
  }
  {
    cuuint64_t gd[4] = {16, D_ / 2, 2, 128};
    cuuint64_t st[3] = {2 * KVT, KVT, 64};
    cuuint32_t bx[4] = {20, 32, 2, 1};
    cuuint32_t es[4] = {1, 1, 1, 1};
    enc(&tmKV, CU_TENSOR_MAP_DATA_TYPE_UINT32, 4, kvp, gd, st, bx, es, CU_TENSOR_MAP_INTERLEAVE_NONE, CU_TENSOR_MAP_SWIZZLE_NONE,
        CU_TENSOR_MAP_L2_PROMOTION_NONE, CU_TENSOR_MAP_FLOAT_OOB_FILL_NONE);
  }
  {
    cuuint64_t gd[3] = {40, 64, D_};
    cuuint64_t st[2] = {128, KVT};
    cuuint32_t bx[3] = {40, 16, 1};
    cuuint32_t es[3] = {1, 1, 1};
    enc(&tmKL, CU_TENSOR_MAP_DATA_TYPE_UINT32, 3, gs->kv + 96, gd, st, bx, es, CU_TENSOR_MAP_INTERLEAVE_NONE, CU_TENSOR_MAP_SWIZZLE_NONE,
        CU_TENSOR_MAP_L2_PROMOTION_NONE, CU_TENSOR_MAP_FLOAT_OOB_FILL_NONE);
  }
  {
    cuuint64_t gd[3] = {64, 32 * 72, 8};
    cuuint64_t st[2] = {1024, 128};
    cuuint32_t bx[3] = {64, 72, 1};
    cuuint32_t es[3] = {1, 1, 1};
    enc(&tmH, CU_TENSOR_MAP_DATA_TYPE_BFLOAT16, 3, hp, gd, st, bx, es, CU_TENSOR_MAP_INTERLEAVE_NONE, CU_TENSOR_MAP_SWIZZLE_128B,
        CU_TENSOR_MAP_L2_PROMOTION_NONE, CU_TENSOR_MAP_FLOAT_OOB_FILL_NONE);
  }
  for (int w = 0; w < 2; w++) {
    const cuuint64_t M = w ? S_ : F_, K = w ? F_ : S_;
    cuuint64_t gd[3] = {64, K, M / 64};
    cuuint64_t st[2] = {M * 2, 128};
    cuuint32_t bx[3] = {64, 64, 2};
    cuuint32_t es[3] = {1, 1, 1};
    enc(w ? &tmW2 : &tmW1, CU_TENSOR_MAP_DATA_TYPE_BFLOAT16, 3, d_in[w ? 9 : 7], gd, st, bx, es, CU_TENSOR_MAP_INTERLEAVE_NONE,
        CU_TENSOR_MAP_SWIZZLE_128B, CU_TENSOR_MAP_L2_PROMOTION_L2_256B, CU_TENSOR_MAP_FLOAT_OOB_FILL_NONE);
  }
  {
    cuuint64_t gd[2] = {S_, D_};
    cuuint64_t st[1] = {S_ * 2};
    cuuint32_t bx[2] = {64, 72};
    cuuint32_t es[2] = {1, 1};
    enc(&tmZ, CU_TENSOR_MAP_DATA_TYPE_BFLOAT16, 2, zp, gd, st, bx, es, CU_TENSOR_MAP_INTERLEAVE_NONE, CU_TENSOR_MAP_SWIZZLE_128B,
        CU_TENSOR_MAP_L2_PROMOTION_L2_256B, CU_TENSOR_MAP_FLOAT_OOB_FILL_NONE);
  }
  RoleMap roles;
  int dev = 0, sms = 0;
  cudaGetDevice(&dev);
  cudaDeviceGetAttribute(&sms, cudaDevAttrMultiProcessorCount, dev);
  roles.by_sm = sms == NCTA;
  for (int k = 0; k < NCTA / 2; k++) roles.role[k] = role_of_pair(k);
  cudaFuncSetAttribute(fused_kernel, cudaFuncAttributeMaxDynamicSharedMemorySize, SMEM_BYTES);
  fused_kernel<<<NCTA, 384, SMEM_BYTES>>>((const __nv_bfloat16*)d_in[0], gs, (const __nv_bfloat16*)d_in[8], (const __nv_bfloat16*)d_in[3],
                                          (const __nv_bfloat16*)d_in[4], (const __nv_bfloat16*)d_in[5], tmW1, tmW2, tmZ, tmH, tmK, tmV, tmKV, tmKL,
                                          roles, (const __nv_bfloat16*)d_in[10], (__nv_bfloat16*)d_out);
}
```

```cpp
#include <cuda_runtime.h>
#include <cuda_bf16.h>
#include <cuda.h>
#include <stdint.h>

namespace {

constexpr int S_ = 2048, D_ = 576, F_ = 4608;
constexpr int NCTA = 132, NG2 = 128;
constexpr int ST = 5, ASZ = 16384, PITCH_S = ASZ + 144 * 128, PITCH_B = ASZ + 192 * 128;
constexpr int KVIN = (36 + 33) * 128, KVW = 2 * KVIN + 64 * 176;
constexpr int BAR_OFF = ST * PITCH_S + 2 * KVW;
constexpr int SMEM_BYTES = BAR_OFF + 512;
constexpr int LNROT = 120;
constexpr int SKEW = 1;
constexpr int LEAD_S = 4, LEAD_B = 3;
constexpr int CTURN = 14, CPER = 4;
constexpr int TURN = 4, KPRE = 2;
constexpr int XAT = 12, ZAT = 25, GLAG = 4, PRE0 = 1;
constexpr int LAG = 4;
constexpr int CBUF = 14464, CH_OFF = 128, CT_OFF = 4224, KVT = 128 + 8192;
constexpr int BLK_NS = 336;
constexpr uint32_t SPIN_LIMIT = 1u << 22;

constexpr int FL_H = 0, FL_U = 3, FL_KV = 9, FL_Z = 12, FL_GATE = 13, FL_DONE = 14, FL_N = 15;
struct Scratch {
  uint32_t flags[64 * 32];
  uint4 stats[S_];
  uint8_t h[32 * 72 * 1024];
  uint8_t u[72 * D_ * 128];
  uint8_t kv[D_ * KVT];
  __nv_bfloat16 z[D_ * S_];
};
__device__ __align__(1024) Scratch g_scratch;
extern __shared__ __align__(1024) uint8_t smem_raw[];
#define TUNABLES(X) X(W9, 1200) X(QLATE, 40) X(QDELAY, 400) X(QRAMP, 5) X(A0, 1200) X(AD, 300) X(AN, 2) X(AL, 1500) X(H0, 3100) X(HD, 400) X(HS2, 8) X(HW, 4200) X(LK1, 7) X(LK2, 14) X(KVGO, 6) X(KVGO1, 10) X(CVGO, 31) X(GDELAY, 1280) X(GDELAY1, 128) X(GBIG, 960) X(ZDELAY, 0) X(ZRAMP, 30)
#define X(k, v) constexpr int T_##k = v;
TUNABLES(X)
#undef X
#define TN(k) T_##k
struct RoleMap { uint32_t role[NCTA / 2]; uint32_t by_sm; };
#define PROF(i) do {} while (0)
#define PROFG(i) do {} while (0)
#define PROFC(i) do {} while (0)

template<int TB> __device__ __forceinline__ void wgmma_ss(float (&d)[96], uint32_t da, uint32_t db, int sd) {
  asm volatile("{\n.reg .pred p;\n.reg .b64 a, b;\nsetp.ne.b32 p, %98, 0;\nmov.b64 a, {%96, %100};\nmov.b64 b, {%97, %101};\n"
    "wgmma.mma_async.sync.aligned.m64n192k16.f32.bf16.bf16 {%0, %1, %2, %3, %4, %5, %6, %7, %8, %9, %10, %11, %12, %13, %14, %15, %16, %17, %18, %19, %20, %21, %22, %23, %24, %25, %26, %27, %28, %29, %30, %31, %32, %33, %34, %35, %36, %37, %38, %39, %40, %41, %42, %43, %44, %45, %46, %47, %48, %49, %50, %51, %52, %53, %54, %55, %56, %57, %58, %59, %60, %61, %62, %63, %64, %65, %66, %67, %68, %69, %70, %71, %72, %73, %74, %75, %76, %77, %78, %79, %80, %81, %82, %83, %84, %85, %86, %87, %88, %89, %90, %91, %92, %93, %94, %95}, a, b, p, 1, 1, 1, %99;\n}\n"
    : "+f"(d[0]), "+f"(d[1]), "+f"(d[2]), "+f"(d[3]), "+f"(d[4]), "+f"(d[5]), "+f"(d[6]), "+f"(d[7]), "+f"(d[8]), "+f"(d[9]), "+f"(d[10]), "+f"(d[11]), "+f"(d[12]), "+f"(d[13]), "+f"(d[14]), "+f"(d[15]), "+f"(d[16]), "+f"(d[17]), "+f"(d[18]), "+f"(d[19]), "+f"(d[20]), "+f"(d[21]), "+f"(d[22]), "+f"(d[23]), "+f"(d[24]), "+f"(d[25]), "+f"(d[26]), "+f"(d[27]), "+f"(d[28]), "+f"(d[29]), "+f"(d[30]), "+f"(d[31]), "+f"(d[32]), "+f"(d[33]), "+f"(d[34]), "+f"(d[35]), "+f"(d[36]), "+f"(d[37]), "+f"(d[38]), "+f"(d[39]), "+f"(d[40]), "+f"(d[41]), "+f"(d[42]), "+f"(d[43]), "+f"(d[44]), "+f"(d[45]), "+f"(d[46]), "+f"(d[47]), "+f"(d[48]), "+f"(d[49]), "+f"(d[50]), "+f"(d[51]), "+f"(d[52]), "+f"(d[53]), "+f"(d[54]), "+f"(d[55]), "+f"(d[56]), "+f"(d[57]), "+f"(d[58]), "+f"(d[59]), "+f"(d[60]), "+f"(d[61]), "+f"(d[62]), "+f"(d[63]), "+f"(d[64]), "+f"(d[65]), "+f"(d[66]), "+f"(d[67]), "+f"(d[68]), "+f"(d[69]), "+f"(d[70]), "+f"(d[71]), "+f"(d[72]), "+f"(d[73]), "+f"(d[74]), "+f"(d[75]), "+f"(d[76]), "+f"(d[77]), "+f"(d[78]), "+f"(d[79]), "+f"(d[80]), "+f"(d[81]), "+f"(d[82]), "+f"(d[83]), "+f"(d[84]), "+f"(d[85]), "+f"(d[86]), "+f"(d[87]), "+f"(d[88]), "+f"(d[89]), "+f"(d[90]), "+f"(d[91]), "+f"(d[92]), "+f"(d[93]), "+f"(d[94]), "+f"(d[95])
    : "r"(da), "r"(db), "r"(sd), "n"(TB), "r"(0x40000040u), "r"(TB ? 0x40u : 0x40000040u));
}
template<int TB> __device__ __forceinline__ void wgmma_ss(float (&d)[72], uint32_t da, uint32_t db, int sd) {
  asm volatile("{\n.reg .pred p;\n.reg .b64 a, b;\nsetp.ne.b32 p, %74, 0;\nmov.b64 a, {%72, %76};\nmov.b64 b, {%73, %77};\n"
    "wgmma.mma_async.sync.aligned.m64n144k16.f32.bf16.bf16 {%0, %1, %2, %3, %4, %5, %6, %7, %8, %9, %10, %11, %12, %13, %14, %15, %16, %17, %18, %19, %20, %21, %22, %23, %24, %25, %26, %27, %28, %29, %30, %31, %32, %33, %34, %35, %36, %37, %38, %39, %40, %41, %42, %43, %44, %45, %46, %47, %48, %49, %50, %51, %52, %53, %54, %55, %56, %57, %58, %59, %60, %61, %62, %63, %64, %65, %66, %67, %68, %69, %70, %71}, a, b, p, 1, 1, 1, %75;\n}\n"
    : "+f"(d[0]), "+f"(d[1]), "+f"(d[2]), "+f"(d[3]), "+f"(d[4]), "+f"(d[5]), "+f"(d[6]), "+f"(d[7]), "+f"(d[8]), "+f"(d[9]), "+f"(d[10]), "+f"(d[11]), "+f"(d[12]), "+f"(d[13]), "+f"(d[14]), "+f"(d[15]), "+f"(d[16]), "+f"(d[17]), "+f"(d[18]), "+f"(d[19]), "+f"(d[20]), "+f"(d[21]), "+f"(d[22]), "+f"(d[23]), "+f"(d[24]), "+f"(d[25]), "+f"(d[26]), "+f"(d[27]), "+f"(d[28]), "+f"(d[29]), "+f"(d[30]), "+f"(d[31]), "+f"(d[32]), "+f"(d[33]), "+f"(d[34]), "+f"(d[35]), "+f"(d[36]), "+f"(d[37]), "+f"(d[38]), "+f"(d[39]), "+f"(d[40]), "+f"(d[41]), "+f"(d[42]), "+f"(d[43]), "+f"(d[44]), "+f"(d[45]), "+f"(d[46]), "+f"(d[47]), "+f"(d[48]), "+f"(d[49]), "+f"(d[50]), "+f"(d[51]), "+f"(d[52]), "+f"(d[53]), "+f"(d[54]), "+f"(d[55]), "+f"(d[56]), "+f"(d[57]), "+f"(d[58]), "+f"(d[59]), "+f"(d[60]), "+f"(d[61]), "+f"(d[62]), "+f"(d[63]), "+f"(d[64]), "+f"(d[65]), "+f"(d[66]), "+f"(d[67]), "+f"(d[68]), "+f"(d[69]), "+f"(d[70]), "+f"(d[71])
    : "r"(da), "r"(db), "r"(sd), "n"(TB), "r"(0x40000040u), "r"(TB ? 0x40u : 0x40000040u));
}
template<int TB> __device__ __forceinline__ void wgmma_ss(float (&d)[36], uint32_t da, uint32_t db, int sd) {
  asm volatile("{\n.reg .pred p;\n.reg .b64 a, b;\nsetp.ne.b32 p, %38, 0;\nmov.b64 a, {%36, %40};\nmov.b64 b, {%37, %41};\n"
    "wgmma.mma_async.sync.aligned.m64n72k16.f32.bf16.bf16 {%0, %1, %2, %3, %4, %5, %6, %7, %8, %9, %10, %11, %12, %13, %14, %15, %16, %17, %18, %19, %20, %21, %22, %23, %24, %25, %26, %27, %28, %29, %30, %31, %32, %33, %34, %35}, a, b, p, 1, 1, 1, %39;\n}\n"
    : "+f"(d[0]), "+f"(d[1]), "+f"(d[2]), "+f"(d[3]), "+f"(d[4]), "+f"(d[5]), "+f"(d[6]), "+f"(d[7]), "+f"(d[8]), "+f"(d[9]), "+f"(d[10]), "+f"(d[11]), "+f"(d[12]), "+f"(d[13]), "+f"(d[14]), "+f"(d[15]), "+f"(d[16]), "+f"(d[17]), "+f"(d[18]), "+f"(d[19]), "+f"(d[20]), "+f"(d[21]), "+f"(d[22]), "+f"(d[23]), "+f"(d[24]), "+f"(d[25]), "+f"(d[26]), "+f"(d[27]), "+f"(d[28]), "+f"(d[29]), "+f"(d[30]), "+f"(d[31]), "+f"(d[32]), "+f"(d[33]), "+f"(d[34]), "+f"(d[35])
    : "r"(da), "r"(db), "r"(sd), "n"(TB), "r"(0x40000040u), "r"(TB ? 0x40u : 0x40000040u));
}
__device__ __forceinline__ void wgmma_rs_n32(float (&d)[16], uint32_t a0, uint32_t a1, uint32_t a2, uint32_t a3, uint64_t db, int sd) {
  asm volatile("{\n.reg .pred p;\nsetp.ne.b32 p, %21, 0;\n"
    "wgmma.mma_async.sync.aligned.m64n32k16.f32.bf16.bf16 {%0, %1, %2, %3, %4, %5, %6, %7, %8, %9, %10, %11, %12, %13, %14, %15}, {%16, %17, %18, %19}, %20, p, 1, 1, 0;\n}\n"
    : "+f"(d[0]), "+f"(d[1]), "+f"(d[2]), "+f"(d[3]), "+f"(d[4]), "+f"(d[5]), "+f"(d[6]), "+f"(d[7]), "+f"(d[8]), "+f"(d[9]), "+f"(d[10]), "+f"(d[11]), "+f"(d[12]), "+f"(d[13]), "+f"(d[14]), "+f"(d[15])
    : "r"(a0), "r"(a1), "r"(a2), "r"(a3), "l"(db), "r"(sd));
}

__device__ __forceinline__ void wg_fence() { asm volatile("wgmma.fence.sync.aligned;" ::: "memory"); }
__device__ __forceinline__ void wg_commit() { asm volatile("wgmma.commit_group.sync.aligned;" ::: "memory"); }
template <int n> __device__ __forceinline__ void wg_wait() { asm volatile("wgmma.wait_group.sync.aligned %0;" ::"n"(n) : "memory"); }
__device__ __forceinline__ uint64_t mkdesc(uint32_t addr, uint32_t lbo, uint32_t sbo, uint32_t sw) {
  return (uint64_t)((addr & 0x3FFFF) >> 4) | ((uint64_t)(lbo >> 4) << 16) | ((uint64_t)(sbo >> 4) << 32) | ((uint64_t)sw << 62);
}
__device__ __forceinline__ void mbar_init(uint32_t a, int c) { asm volatile("mbarrier.init.shared::cta.b64 [%0], %1;" ::"r"(a), "r"(c)); }
__device__ __forceinline__ void mbar_expect(uint32_t a, uint32_t b) { asm volatile("mbarrier.arrive.expect_tx.shared::cta.b64 _, [%0], %1;" ::"r"(a), "r"(b) : "memory"); }
__device__ __forceinline__ void mbar_arrive(uint32_t a) { asm volatile("mbarrier.arrive.shared::cta.b64 _, [%0];" ::"r"(a) : "memory"); }
__device__ __forceinline__ void mbar_arrive_cluster(uint32_t raddr) { asm volatile("mbarrier.arrive.shared::cluster.b64 _, [%0];" ::"r"(raddr) : "memory"); }
__device__ __forceinline__ uint32_t mapa(uint32_t a, uint32_t cta) { uint32_t r; asm("mapa.shared::cluster.u32 %0, %1, %2;" : "=r"(r) : "r"(a), "r"(cta)); return r; }
__device__ __forceinline__ void mbar_wait(uint32_t a, uint32_t ph) {
  asm volatile(
      "{\n.reg .pred p;\n.reg .u32 c;\nmov.u32 c, 0;\n"
      "WAIT_LOOP:\nmbarrier.try_wait.parity.shared::cta.b64 p, [%0], %1;\n@p bra WAIT_DONE;\n"
      "add.u32 c, c, 1;\nsetp.lt.u32 p, c, %2;\n@p bra WAIT_LOOP;\ntrap;\nWAIT_DONE:\n}" ::"r"(a), "r"(ph), "n"(SPIN_LIMIT) : "memory");
}
__device__ __forceinline__ void mbar_wait_u(uint32_t a, uint32_t ph) {
  asm volatile("{\n.reg .pred p;\nWAIT_LOOP:\nmbarrier.try_wait.parity.shared::cta.b64 p, [%0], %1;\n@!p bra WAIT_LOOP;\n}" ::"r"(a), "r"(ph) : "memory");
}
__device__ __forceinline__ uint32_t desc_lo(uint32_t addr, uint32_t lbo) { return ((addr & 0x3FFFF) >> 4) | ((lbo >> 4) << 16); }
__device__ __forceinline__ void tma2d(uint32_t dst, const CUtensorMap* m, int c0, int c1, uint32_t bar) {
  asm volatile("cp.async.bulk.tensor.2d.shared::cluster.global.mbarrier::complete_tx::bytes [%0], [%1, {%3, %4}], [%2];" ::"r"(dst), "l"(m), "r"(bar), "r"(c0), "r"(c1) : "memory");
}
__device__ __forceinline__ void bulk_g2s(uint32_t dst, const void* src, uint32_t sz, uint32_t bar) {
  asm volatile("cp.async.bulk.shared::cluster.global.mbarrier::complete_tx::bytes [%0], [%1], %2, [%3];" ::"r"(dst), "l"(src), "r"(sz), "r"(bar) : "memory");
}
__device__ __forceinline__ void bulk_s2g(void* dst, uint32_t src, uint32_t sz) {
  asm volatile("cp.async.bulk.global.shared::cta.bulk_group [%0], [%1], %2;" ::"l"(dst), "r"(src), "r"(sz) : "memory");
}
__device__ __forceinline__ uint64_t stream_policy() {
  uint64_t p;
  asm volatile("createpolicy.fractional.L2::evict_first.b64 %0, 1.0;" : "=l"(p));
  return p;
}
__device__ __forceinline__ void tma_weights(uint32_t dst, const CUtensorMap* m, int k0, int mchunk, uint32_t bar, uint64_t pol) {
  asm volatile("cp.async.bulk.tensor.3d.shared::cluster.global.mbarrier::complete_tx::bytes.L2::cache_hint [%0], [%1, {%6, %3, %4}], [%2], %5;"
               ::"r"(dst), "l"(m), "r"(bar), "r"(k0), "r"(mchunk), "l"(pol), "r"(0) : "memory");
}
__device__ __forceinline__ bool elect_one() {
  uint32_t p;
  asm volatile("{\n.reg .pred P;\nelect.sync _|P, 0xffffffff;\nselp.u32 %0, 1, 0, P;\n}" : "=r"(p));
  return p;
}
__device__ __forceinline__ void bulk_g2s_stream(uint32_t dst, const void* src, uint32_t sz, uint32_t bar, uint64_t pol) {
  asm volatile("cp.async.bulk.shared::cluster.global.mbarrier::complete_tx::bytes.L2::cache_hint [%0], [%1], %2, [%3], %4;"
               ::"r"(dst), "l"(src), "r"(sz), "r"(bar), "l"(pol) : "memory");
}
__device__ __forceinline__ void tma3d_store(const CUtensorMap* m, int c1, int c2, uint32_t src) {
  asm volatile("cp.async.bulk.tensor.3d.global.shared::cta.bulk_group [%0, {%4, %2, %3}], [%1];" ::"l"(m), "r"(src), "r"(c1), "r"(c2), "r"(0) : "memory");
}
__device__ __forceinline__ void tma2d_stream(uint32_t dst, const CUtensorMap* m, int c0, int c1, uint32_t bar, uint64_t pol) {
  asm volatile("cp.async.bulk.tensor.2d.shared::cluster.global.mbarrier::complete_tx::bytes.L2::cache_hint [%0], [%1, {%3, %4}], [%2], %5;"
               ::"r"(dst), "l"(m), "r"(bar), "r"(c0), "r"(c1), "l"(pol) : "memory");
}
__device__ __forceinline__ void tma4d_store(const CUtensorMap* m, int c1, int c2, int c3, uint32_t src) {
  asm volatile("cp.async.bulk.tensor.4d.global.shared::cta.bulk_group [%0, {%5, %2, %3, %4}], [%1];" ::"l"(m), "r"(src), "r"(c1), "r"(c2), "r"(c3), "r"(0) : "memory");
}
__device__ __forceinline__ void bulk_commit() { asm volatile("cp.async.bulk.commit_group;" ::: "memory"); }
__device__ __forceinline__ void bulk_wait_all() { asm volatile("cp.async.bulk.wait_group 0;" ::: "memory"); }
__device__ __forceinline__ void fence_async_smem() { asm volatile("fence.proxy.async.shared::cta;" ::: "memory"); }
__device__ __forceinline__ void fence_async_global() { asm volatile("fence.proxy.async.global;" ::: "memory"); }
__device__ __forceinline__ void named_bar(int id, int n) { asm volatile("bar.sync %0, %1;" ::"r"(id), "r"(n) : "memory"); }
__device__ __forceinline__ void named_arrive(int id, int n) { asm volatile("bar.arrive %0, %1;" ::"r"(id), "r"(n) : "memory"); }
__device__ __forceinline__ void flag_add(uint32_t* f, int i, uint32_t v) { asm volatile("red.relaxed.gpu.global.add.u32 [%0], %1;" ::"l"(f + i * 32), "r"(v) : "memory"); }
__device__ __forceinline__ uint32_t flag_ld(uint32_t* f, int i) { uint32_t v; asm volatile("ld.relaxed.gpu.global.u32 %0, [%1];" : "=r"(v) : "l"(f + i * 32) : "memory"); return v; }
__device__ __forceinline__ void prefetch_map(const CUtensorMap* m) { asm volatile("prefetch.tensormap [%0];" ::"l"(m) : "memory"); }
__device__ __forceinline__ void stsm4_t(uint32_t a, uint32_t r0, uint32_t r1, uint32_t r2, uint32_t r3) {
  asm volatile("stmatrix.sync.aligned.m8n8.x4.trans.shared.b16 [%0], {%1, %2, %3, %4};" ::"r"(a), "r"(r0), "r"(r1), "r"(r2), "r"(r3) : "memory");
}
__device__ __forceinline__ uint32_t lds32(uint32_t a) { uint32_t v; asm volatile("ld.shared.u32 %0, [%1];" : "=r"(v) : "r"(a) : "memory"); return v; }
__device__ __forceinline__ void sts32(uint32_t a, uint32_t v) { asm volatile("st.shared.u32 [%0], %1;" ::"r"(a), "r"(v) : "memory"); }
__device__ __forceinline__ uint4 ld_l2(const uint4* p) { uint4 v; asm volatile("ld.relaxed.gpu.global.v4.u32 {%0, %1, %2, %3}, [%4];" : "=r"(v.x), "=r"(v.y), "=r"(v.z), "=r"(v.w) : "l"(p) : "memory"); return v; }
__device__ __forceinline__ void sts128(uint32_t a, uint32_t x, uint32_t y, uint32_t z, uint32_t w) { asm volatile("st.shared.v4.u32 [%0], {%1, %2, %3, %4};" ::"r"(a), "r"(x), "r"(y), "r"(z), "r"(w) : "memory"); }
__device__ __forceinline__ uint4 lds128(uint32_t a) { uint4 v; asm volatile("ld.shared.v4.u32 {%0, %1, %2, %3}, [%4];" : "=r"(v.x), "=r"(v.y), "=r"(v.z), "=r"(v.w) : "r"(a) : "memory"); return v; }
__device__ __forceinline__ void st_async4(uint32_t raddr, uint32_t a, uint32_t b, uint32_t c, uint32_t d, uint32_t rbar) {
  asm volatile("st.async.weak.shared::cluster.mbarrier::complete_tx::bytes.v4.b32 [%0], {%1, %2, %3, %4}, [%5];" ::"r"(raddr), "r"(a), "r"(b), "r"(c), "r"(d), "r"(rbar) : "memory");
}
__device__ __forceinline__ uint32_t pack_bf16(float lo, float hi) { uint32_t r; asm("cvt.rn.bf16x2.f32 %0, %1, %2;" : "=r"(r) : "f"(hi), "f"(lo)); return r; }
__device__ __forceinline__ float bf_lo(uint32_t v) { return __uint_as_float(v << 16); }
__device__ __forceinline__ float bf_hi(uint32_t v) { return __uint_as_float(v & 0xffff0000u); }
__device__ __forceinline__ float bf_round(float x) { return bf_lo(pack_bf16(x, 0.f)); }
__device__ __forceinline__ uint32_t hmul2(uint32_t a, uint32_t b) { uint32_t r; asm("mul.rn.bf16x2 %0, %1, %2;" : "=r"(r) : "r"(a), "r"(b)); return r; }
__device__ __forceinline__ uint32_t hsub2(uint32_t a, uint32_t b) { uint32_t r; asm("sub.rn.bf16x2 %0, %1, %2;" : "=r"(r) : "r"(a), "r"(b)); return r; }
__device__ __forceinline__ uint32_t hfma2(uint32_t a, uint32_t b, uint32_t c) { uint32_t r; asm("fma.rn.bf16x2 %0, %1, %2, %3;" : "=r"(r) : "r"(a), "r"(b), "r"(c)); return r; }
__device__ __forceinline__ uint4 ldg128(const void* p) { uint4 v; asm volatile("ld.global.nc.v4.u32 {%0, %1, %2, %3}, [%4];" : "=r"(v.x), "=r"(v.y), "=r"(v.z), "=r"(v.w) : "l"(p)); return v; }
__device__ __forceinline__ uint32_t ldg16(const void* p) { uint32_t v; asm volatile("ld.global.nc.u16 %0, [%1];" : "=r"(v) : "l"(p)); return v; }
__device__ __forceinline__ float tanh_ordered(float x) { float y; asm volatile("tanh.approx.f32 %0, %1;" : "=f"(y) : "f"(x)); return y; }
__device__ __forceinline__ uint32_t tanh2_ordered(uint32_t x) { uint32_t y; asm volatile("tanh.approx.bf16x2 %0, %1;" : "=r"(y) : "r"(x)); return y; }
__device__ __forceinline__ void mma16816(float (&d)[4], uint32_t a0, uint32_t a1, uint32_t a2, uint32_t a3, uint32_t b0, uint32_t b1) {
  asm("mma.sync.aligned.m16n8k16.row.col.f32.bf16.bf16.f32 {%0, %1, %2, %3}, {%4, %5, %6, %7}, {%8, %9}, {%0, %1, %2, %3};"
      : "+f"(d[0]), "+f"(d[1]), "+f"(d[2]), "+f"(d[3]) : "r"(a0), "r"(a1), "r"(a2), "r"(a3), "r"(b0), "r"(b1));
}
__device__ __forceinline__ uint32_t hadd2(uint32_t a, uint32_t b) { uint32_t r; asm("add.rn.bf16x2 %0, %1, %2;" : "=r"(r) : "r"(a), "r"(b)); return r; }
__device__ __forceinline__ uint32_t ldg32(const void* p) { uint32_t v; asm volatile("ld.global.nc.L1::no_allocate.u32 %0, [%1];" : "=r"(v) : "l"(p)); return v; }
__device__ __forceinline__ uint2 lds64(uint32_t a) { uint2 v; asm volatile("ld.shared.v2.u32 {%0, %1}, [%2];" : "=r"(v.x), "=r"(v.y) : "r"(a) : "memory"); return v; }
__device__ __forceinline__ uint32_t lds32_if(uint32_t a, uint32_t on) {
  uint32_t v;
  asm volatile("{\n.reg .pred p;\nsetp.ne.u32 p, %2, 0;\n@p ld.shared.u32 %0, [%1];\n}" : "=r"(v) : "r"(a), "r"(on) : "memory");
  return v;
}
__device__ __forceinline__ uint32_t clock_now() { uint32_t t; asm volatile("mov.u32 %0, %%clock;" : "=r"(t)); return t; }
__device__ __forceinline__ uint32_t time_now() { uint32_t t; asm volatile("mov.u32 %0, %%globaltimer_lo;" : "=r"(t)); return t; }
__device__ __forceinline__ void spin_until(uint32_t t0, uint32_t n) { while (clock_now() - t0 < n) {} }
__device__ __forceinline__ uint2 ldg64_if(const void* p, uint32_t on) {
  uint2 v;
  asm volatile("{\n.reg .pred p;\nsetp.ne.u32 p, %3, 0;\n@p ld.global.nc.v2.u32 {%0, %1}, [%2];\n}" : "=r"(v.x), "=r"(v.y) : "l"(p), "r"(on));
  return v;
}
template <class T> __device__ __forceinline__ T pin(T v) { asm volatile("" : "+r"(v)); return v; }
__device__ __forceinline__ void st_async2(uint32_t raddr, uint32_t a, uint32_t b, uint32_t rbar) {
  asm volatile("st.async.weak.shared::cluster.mbarrier::complete_tx::bytes.v2.b32 [%0], {%1, %2}, [%3];" ::"r"(raddr), "r"(a), "r"(b), "r"(rbar) : "memory");
}
__device__ __forceinline__ void bulk_prefetch(const void* src, uint32_t sz, uint64_t pol) {
  asm volatile("cp.async.bulk.prefetch.L2.global.L2::cache_hint [%0], %1, %2;" ::"l"(src), "r"(sz), "l"(pol) : "memory");
}
__device__ __forceinline__ void bulk_wait_read() { asm volatile("cp.async.bulk.wait_group.read 0;" ::: "memory"); }
__device__ __forceinline__ uint32_t shfl_ordered(uint32_t v, int src) { uint32_t r; asm volatile("shfl.sync.idx.b32 %0, %1, %2, 0x1f, 0xffffffff;" : "=r"(r) : "r"(v), "r"(src)); return r; }
__device__ __forceinline__ int chan_pos(int d) {
  return d < 512 ? 72 * (d >> 6) + ((d & 33) | ((d & 6) << 2) | ((d >> 2) & 6)) : 72 * ((d - 512) >> 3) + 64 + (d & 7);
}

struct Ring {
  uint32_t s, ph;
  __device__ __forceinline__ void next() { if (++s == ST) { s = 0; ph ^= 1; } }
};
constexpr int B_FULL = 0, B_GO = 40, B_CFULL = 48, B_SEMPTY = 80, B_ZFULL = 96, B_RFULL = 104, B_UDONE = 120, B_KFULL = 136, B_RAW = 168, B_CVGO = 248, B_PEER = 256, B_G2GO = 264, B_KVGO = 280,
              B_EMPTY = 296, B_G1DONE = 336,
              B_CEMPTY = 344, B_SFULL = 376, B_USTG = 392, B_END = 408;

static_assert((B_EMPTY - B_GO) % 16 == 0 && (B_CEMPTY - B_EMPTY) % 16 == 0 && (B_END - B_CEMPTY) % 16 == 0, "barrier groups");

__device__ __forceinline__ void wait_counter(uint32_t* f, int idx, uint32_t want, uint32_t first, uint32_t nap) {
#pragma unroll 1
  for (uint32_t spins = 0; first != want; spins++) {
    if (nap && spins) __nanosleep(nap);
    first = flag_ld(f, idx);
    if (spins > SPIN_LIMIT) asm volatile("trap;");
  }
  fence_async_global();
}

__device__ __forceinline__ void gate_arrive(uint32_t* f, uint32_t back) {
  asm volatile("red.relaxed.gpu.global.max.u32 [%0], %1;" ::"l"(f + FL_GATE * 32 + 1), "r"(time_now() - back) : "memory");
  flag_add(f, FL_GATE, 1);
}

__device__ __forceinline__ float ln_rinv(float var) {
  float rt, rinv;
  asm("sqrt.approx.ftz.f32 %0, %1;" : "=f"(rt) : "f"(bf_round(bf_round(var) + 1e-5f)));
  asm("rcp.approx.ftz.f32 %0, %1;" : "=f"(rinv) : "f"(bf_round(rt)));
  return rinv;
}
__device__ __forceinline__ uint32_t ln_apply(uint32_t x, const uint4& st) {
  const uint32_t d = hsub2(x, st.x);
  return hfma2(d, st.y, hmul2(d, st.z));
}

__device__ __forceinline__ void polling_done(uint32_t* f, int lane) {
  unsigned old = 0;
  if (lane == 0) asm volatile("atom.relaxed.gpu.global.add.u32 %0, [%1], 1;" : "=r"(old) : "l"(f + FL_DONE * 32) : "memory");
  old = __shfl_sync(0xffffffffu, old, 0);
  if (old == 2 * NCTA - 1) {
    if (lane < FL_N) *(uint2*)(f + lane * 32) = make_uint2(0u, 0u);
  }
}

struct Pipe { Ring r; uint32_t prev; bool pending; int cnt; };
__device__ __forceinline__ void pipe_drain(Pipe& p, uint32_t bars, bool leader) {
  wg_wait<0>();
  if (leader) mbar_arrive(bars + B_EMPTY + p.prev * 8);
  p.pending = false;
}
template <int TB, int LEAD, int R>
__device__ __forceinline__ void gemm_run(float (&acc)[R], int n, int accumulate, Pipe& p, uint32_t sb, uint32_t pitch, int wg, bool leader) {
  const uint32_t bars = sb + BAR_OFF;
  const uint32_t dA0 = desc_lo(sb + wg * 8192, 8192), dB0 = desc_lo(sb + ASZ, TB ? 128 : 16);
  constexpr int KB_STEP = TB ? 16 : 2;
#pragma unroll 1
  for (int kb = 0; kb < n; kb++) {
    if (LEAD && kb == n - LEAD && wg == 1) { if (TB) pipe_drain(p, bars, leader); named_bar(8, 256); }
    mbar_wait(bars + B_FULL + p.r.s * 8, p.r.ph);
    if (kb == 0 && !accumulate && threadIdx.x == 0) { PROF(21 + TB); PROFC(49 - 2 * TB); }
    const uint32_t dA = dA0 + p.r.s * (pitch >> 4), dB = dB0 + p.r.s * (pitch >> 4);
    wg_fence();
    wgmma_ss<TB>(acc, dA, dB, accumulate | kb);
#pragma unroll
    for (int k = 1; k < 4; k++) wgmma_ss<TB>(acc, dA + k * 128, dB + k * KB_STEP, 1);
    wg_commit();
    wg_wait<1>();
    if (p.pending && leader) mbar_arrive(bars + B_EMPTY + p.prev * 8);
    p.pending = true;
    p.prev = p.r.s;
    p.r.next();
  }
  if (LEAD && wg == 0) named_arrive(8, 256);
}

template <int BROW0, int I0, int I1>
__device__ __forceinline__ void gemm2_part(float (&c)[36], uint32_t sb, uint32_t pitch, int wg) {
  const uint32_t dA0 = desc_lo(sb + wg * 8192, 8192), dB0 = desc_lo(sb + ASZ + BROW0 * 128, 16);
  wg_fence();
#pragma unroll
  for (int i = I0; i < I1; i++) {
    const int step = 69 - LAG + (i >> 2);
    if ((i & 3) == 0 && BROW0 == 0) mbar_wait_u(sb + BAR_OFF + B_FULL + (step % ST) * 8, (step / ST) & 1);
    if (i == 4 * LAG - TURN && BROW0 && wg == 0) named_arrive(7, 256);
    wgmma_ss<0>(c, dA0 + (step % ST) * (pitch >> 4) + (i & 3) * 128, dB0 + (step % ST) * (pitch >> 4) + (i & 3) * 2, 1);
  }
  wg_commit();
}
__device__ __forceinline__ void split_acc(const float (&acc)[72], float (&a)[36], float (&b)[36]) {
#pragma unroll
  for (int i = 0; i < 36; i++) { asm volatile("mov.b32 %0, %1;" : "=f"(a[i]) : "f"(acc[i])); asm volatile("mov.b32 %0, %1;" : "=f"(b[i]) : "f"(acc[36 + i])); }
}
template <int V0, int V1, int R, class Slice>
__device__ __forceinline__ void gelu_store(const float (&acc)[R], uint32_t bias0, uint32_t bias1, uint32_t sa, uint32_t zero, Slice slice) {
  const uint32_t bb[2] = {pin(bias0) * 0x10001u, pin(bias1) * 0x10001u};
  uint32_t x[2][4], t[2][4], dep[V1 / 8], c3 = 0x3d123d12u;
#pragma unroll
  for (int j = V0 / 8; j <= V1 / 8; j++) {
    if (j < V1 / 8) {
      if (j >= V0 / 8 + GLAG) c3 = (dep[j - GLAG] & zero) | 0x3d123d12u;
#pragma unroll
      for (int u = 0; u < 4; u++) {
        x[j & 1][u] = hadd2(pack_bf16(acc[8 * j + 2 * u], acc[8 * j + 2 * u + 1]), bb[u & 1]);
        t[j & 1][u] = tanh2_ordered(hmul2(x[j & 1][u], hfma2(hmul2(x[j & 1][u], c3), x[j & 1][u], 0x3f4c3f4cu)));
      }
    }
    if (j > V0 / 8) {
      const uint32_t *xx = x[(j - 1) & 1], *tt = t[(j - 1) & 1];
      stsm4_t(sa + (j - 1) * 2048, hfma2(xx[0], tt[0], xx[0]), hfma2(xx[1], tt[1], xx[1]), hfma2(xx[2], tt[2], xx[2]), hfma2(xx[3], tt[3], xx[3]));
      dep[j - 1] = slice(j - 1);
    }
  }
}
struct Role { int half, kind, g2_m, dt, g1_mt, g1_nt, cs, nconv, skip; uint32_t pitch; };
__device__ __forceinline__ Role get_role(const RoleMap& roles) {
  uint32_t b, sm;
  asm volatile("mov.u32 %0, %%ctaid.x;" : "=r"(b));
  asm volatile("mov.u32 %0, %%smid;" : "=r"(sm));
  const uint32_t w = roles.role[(roles.by_sm ? sm : b) >> 1];
  const int half = b & 1, kind = w & 3, m = (w >> 4) & 15, dt = (w >> 2) & 3;
  return Role{half, kind, m * 128, dt, half * 18 + (int)((w >> 8) & 31), (int)(w >> 16), (m * 4 + dt) * 2 + half,
              kind ? kind * kind : 6 - half, kind ? 1 : 2 - 2 * half, kind ? (uint32_t)PITCH_B : (uint32_t)PITCH_S};
}
__device__ __forceinline__ int g2_block(int half, int j) { return j < 0 ? 0 : half * 36 + (j < 12 ? 2 * j : j < 24 ? 2 * j - 23 : j); }
__device__ __forceinline__ int conv_chan(const Role& ro, int i) {
  const bool early = ro.kind == 0 && i < 4;
  const int k = early ? 2 * ro.cs + (i & 1) : ro.kind == 2 ? 176 + 4 * ro.cs + i : ro.kind ? 48 + ro.cs : i == 4 ? ro.cs : 96 + (ro.cs >> 1);
  return (3 * (k >> 6) + (early ? i >> 1 : 2)) * 64 + (k & 63);
}
__device__ __forceinline__ uint32_t conv_buf(uint32_t sb, int kind, int b) {
  return sb + (kind ? (b ? b + 1 : ST) * PITCH_B : b == 3 ? (36 % ST) * PITCH_S : ST * PITCH_S + b * CBUF);
}
__device__ __forceinline__ uint32_t conv_stage(uint32_t sb, int kind) { return sb + (kind ? ST * PITCH_B + CBUF : ST * PITCH_S + 3 * CBUF); }
__device__ __forceinline__ uint32_t u_stage(uint32_t sb, uint32_t pitch, int w) { return sb + (2 - w) * pitch + ASZ; }

__global__ void __cluster_dims__(2, 1, 1) __launch_bounds__(384, 1)
fused_kernel(const __nv_bfloat16* __restrict__ q, Scratch* __restrict__ gs, const __nv_bfloat16* __restrict__ b1,
             const __nv_bfloat16* __restrict__ shiftk, const __nv_bfloat16* __restrict__ ssmk, const __nv_bfloat16* __restrict__ ssmD,
             const __grid_constant__ CUtensorMap tmW1, const __grid_constant__ CUtensorMap tmW2, const __grid_constant__ CUtensorMap tmZ,
             const __grid_constant__ CUtensorMap tmH, const __grid_constant__ CUtensorMap tmK, const __grid_constant__ CUtensorMap tmV,
             const __grid_constant__ CUtensorMap tmKV, const __grid_constant__ CUtensorMap tmKL, const __grid_constant__ RoleMap roles, const __nv_bfloat16* __restrict__ b2,
             __nv_bfloat16* __restrict__ out) {
  const int cta = blockIdx.x;
  const int tid = threadIdx.x;
  if (tid == 288) PROFG(0);

  const uint32_t t_start = clock_now();
  if (tid == 256) { prefetch_map(&tmW1); prefetch_map(&tmH); }
  const int lc = (cta + LNROT) & 127;
  const uint32_t do_ln = cta < 128 && tid < 256;
  const int oct = lc + (tid & 128), ln_row = oct * 8 + ((tid >> 4) & 7), l16 = tid & 15;
  uint2 xr[9];
  if (do_ln && oct >= TN(QLATE)) spin_until(t_start, TN(QDELAY) + TN(QRAMP) * oct / 2);
#pragma unroll
  for (int i = 0; i < 9; i++) xr[i] = ldg64_if(q + (size_t)ln_row * D_ + i * 64 + l16 * 4, do_ln);
  if (tid == 0) PROF(32);
  const int warp = __shfl_sync(0xffffffffu, tid >> 5, 0);
  const uint32_t sb = __shfl_sync(0xffffffffu, (uint32_t)__cvta_generic_to_shared(smem_raw), 0);
  const uint32_t bars = sb + BAR_OFF;
  const int lane = tid & 31;
  const int wg = warp >> 2;
  constexpr int LN_OFF = ST * PITCH_B;

  if (warp < 8 || warp == 11) {
    asm volatile("barrier.cluster.arrive.relaxed.aligned;" ::: "memory");
    const int hq = (lane & 16) >> 3, hb = (lane & 16) + hq;
    float da[3][4] = {};
#pragma unroll
    for (int i = 0; i < 9; i++) mma16816(da[i % 3], xr[i].x, 0x3f803f80u, xr[i].y, 0x3f803f80u, xr[i].x, xr[i].y);
    const float r1 = ((da[0][2] + da[0][3]) + (da[1][2] + da[1][3])) + (da[2][2] + da[2][3]);
    const float r2 = (lane & 4) ? (da[0][1] + da[1][1]) + da[2][1] : (da[0][0] + da[1][0]) + da[2][0];
    const float s1 = __shfl_sync(0xffffffffu, r1, hq) + __shfl_sync(0xffffffffu, r1, hq + 1);
    const float s2 = (__shfl_sync(0xffffffffu, r2, hb) + __shfl_sync(0xffffffffu, r2, hb + 4)) + (__shfl_sync(0xffffffffu, r2, hb + 9) + __shfl_sync(0xffffffffu, r2, hb + 13));
    if (tid == 0) { asm volatile("" ::"f"(s2) : "memory"); PROF(27); }
    const float mean = s1 * (1.f / D_), var = fmaxf(fmaf(-mean, mean, s2 * (1.f / D_)), 0.f);
    const float rinv = ln_rinv(var), rinv2 = ln_rinv(var * rinv * rinv), scale = rinv * rinv2, shift = -bf_round((mean - bf_round(mean)) * rinv) * rinv2;
    const uint32_t m2 = pack_bf16(mean, mean), hi2 = pack_bf16(scale, scale), lo2 = pack_bf16(scale - bf_lo(hi2), scale - bf_lo(hi2)), sh2 = pack_bf16(shift, shift);
    const uint32_t hi1 = pack_bf16(rinv, rinv);
    asm volatile("{\n.reg .pred p;\nsetp.eq.u32 p, %5, 0;\n@p st.shared.v4.u32 [%0], {%1, %2, %3, %4};\n}" ::"r"(sb + LN_OFF + 18432 + tid), "r"(m2), "r"(hi1),
                 "r"(pack_bf16(rinv - bf_lo(hi1), rinv - bf_lo(hi1))), "r"(0u), "r"(tid & 0x10f) : "memory");
    const uint32_t g0 = 4 * (l16 >> 3) + 2 * (l16 & 1), hrow = sb + LN_OFF + ((tid >> 7) & 1) * 9216 + (tid & 0x70);
    const uint32_t hs0 = hrow + g0 * 128 + ((l16 >> 1) & 3) * 4, hs8 = ((hrow + (l16 >> 1) * 1152) ^ ((l16 >> 1) << 4)) + 1024 + (l16 & 1) * 8;
    uint32_t w[18];
#pragma unroll
    for (int i = 0; i < 18; i++) {
      const uint32_t d = hsub2((i & 1) ? xr[i >> 1].y : xr[i >> 1].x, m2);
      asm("max.u32 %0, %1, 1;" : "=r"(w[i]) : "r"(hfma2(d, hi2, hfma2(d, lo2, sh2))));
    }
#pragma unroll
    for (int i = 0; i < 16; i++) {
      const int gi = 9 * (i >> 1) + (i & 1);
      asm volatile("{\n.reg .pred p;\nsetp.ne.u32 p, %2, 0;\n@p st.shared.u32 [%0], %1;\n}" ::"r"((hs0 ^ ((g0 * 16 + (gi & 7) * 16) & 0x70)) + gi * 128), "r"(w[i]), "r"(do_ln) : "memory");
    }
    asm volatile("{\n.reg .pred p;\nsetp.ne.u32 p, %3, 0;\n@p st.shared.v2.u32 [%0], {%1, %2};\n}" ::"r"(hs8), "r"(w[16]), "r"(w[17]), "r"(do_ln) : "memory");
    if (tid == 224) PROF(13);
    fence_async_smem();
    if (warp < 8) named_arrive(wg, 160);
  } else if (warp != 8) {
    spin_until(t_start, TN(W9));
  }

  if (wg == 2) {
    asm volatile("setmaxnreg.dec.sync.aligned.u32 56;");
    auto store_h = [&](int w) {
      named_bar(w, 160);
      if (cta < 128 && elect_one()) {
        tma3d_store(&tmH, ((lc >> 3) + 16 * w) * 72, lc & 7, sb + LN_OFF + w * 9216);
        bulk_s2g(gs->stats + (lc + 128 * w) * 8, sb + LN_OFF + 18432 + w * 128, 128);
        bulk_commit();
      }
    };
    auto publish_h = [&](int w) {
      if (cta < 128 && elect_one()) { bulk_wait_all(); flag_add(gs->flags, FL_H + (w ? 2 : lc >> 6), 1); }
      __syncwarp();
    };
    uint32_t look = 0;
    if (warp == 11) {
      if (lc >= 64) spin_until(t_start, TN(HW));
      store_h(0);
      look = flag_ld(gs->flags, FL_H);
      if (lc < 64) publish_h(0);
      if (lane == 0) PROF(1);
    } else {
      if (elect_one()) {
        if (warp == 8) {
#pragma unroll
          for (int o = 0; o < B_GO; o += 8) mbar_init(bars + o, 1);
        } else {
#pragma unroll
          for (int o = 0; o < (B_EMPTY - B_GO) / 2; o += 8) mbar_init(bars + B_GO + (warp - 9) * ((B_EMPTY - B_GO) / 2) + o, 1);
#pragma unroll
          for (int o = 0; o < (B_CEMPTY - B_EMPTY) / 2; o += 8) mbar_init(bars + B_EMPTY + (warp - 9) * ((B_CEMPTY - B_EMPTY) / 2) + o, 2);
#pragma unroll
          for (int o = 0; o < (B_END - B_CEMPTY) / 2; o += 8) mbar_init(bars + B_CEMPTY + (warp - 9) * ((B_END - B_CEMPTY) / 2) + o, 4);
        }
        asm volatile("fence.mbarrier_init.release.cluster;" ::: "memory");
      }
      __syncwarp();
      asm volatile("barrier.cluster.arrive.relaxed.aligned;" ::: "memory");
      if (warp == 9) { prefetch_map(&tmK); prefetch_map(&tmV); prefetch_map(&tmKV); prefetch_map(&tmKL); prefetch_map(&tmW2); prefetch_map(&tmZ); }
      if (tid == 256) PROF(35);
    }
    const Role ro = get_role(roles);
    if (warp != 8) asm volatile("barrier.cluster.wait.aligned;" ::: "memory");
    if (warp == 11) {
      Ring r{0, 1};
      const uint32_t bsz = ro.pitch - ASZ;
      const uint8_t* src = gs->h + ro.g1_nt * bsz + ST * 73728;
      named_bar(10, 64);
#pragma unroll 1
      for (int i = ST; i < 32; i++) {
        if (i == ST || i == 8 || i == 16) wait_counter(gs->flags, FL_H + (i >> 3), i == 16 ? 128u : 64u, look, 0);
        if (i == TN(LK1) || i == TN(LK2)) look = flag_ld(gs->flags, FL_H + (i >> 3) + 1);
        mbar_wait(bars + B_EMPTY + r.s * 8, r.ph ^ 1);
        if (elect_one()) bulk_g2s(sb + r.s * ro.pitch + ASZ, src, bsz, bars + B_FULL + r.s * 8);
        if (i == ST && lane == 0) PROF(25);
        if (i == TN(HS2)) store_h(1);
        if (i == TN(HS2) + 2 || (i == ST && lc >= 64)) publish_h(i != ST);
        if (i == TN(KVGO1) && lane == 0) mbar_arrive(bars + B_KVGO + 8);
        if (i == TN(KVGO) && lane == 0) mbar_arrive(bars + B_KVGO);
        if (i == TN(CVGO) && lane == 0) mbar_arrive(bars + B_CVGO);
        src += 73728;
        r.next();
      }
      if (ro.kind != 2) {
        look = 0;
#pragma unroll 1
        for (int j = -1; j < 36; j++) {
          const uint8_t* su = gs->u + ((size_t)g2_block(ro.half, j) * D_ + ro.dt * 144) * 128;
          if (j == -1 || j == 12 || j == 24) wait_counter(gs->flags, FL_U + (j < 0 ? 0 : ro.half * 3 + j / 12), j < 0 ? 96u : j == 24 ? 36u : 48u, look, 100);
          if (j == (ro.skip ? 4 : -1) || j == 3) mbar_wait_u(bars + B_UDONE + (j == 3 ? 8 : 0), 0);
          if (j >= ro.skip - 1) mbar_wait(bars + B_EMPTY + r.s * 8, r.ph ^ 1);
          if (j >= ro.skip - 1 && elect_one()) {
            bulk_g2s(sb + r.s * ro.pitch + ASZ, su + (ro.half ^ 1) * 9216, 9216, bars + B_FULL + r.s * 8);
            bulk_g2s(sb + r.s * ro.pitch + ASZ + 9216, su + ro.half * 9216, 9216, bars + B_FULL + r.s * 8);
          }
          if (j == 9 || j == 21) look = flag_ld(gs->flags, FL_U + ro.half * 3 + j / 12 + 1);
          if (j == 1 && lane == 0) PROF(8);
          r.next();
        }
#pragma unroll 1
        for (int o = lane; o < ST * 73728 / 16 / NG2; o += 32) ((uint4*)gs->h)[ro.cs * (ST * 73728 / 16 / NG2) + o] = make_uint4(0u, 0u, 0u, 0u);
      }
    } else if (warp == 8) {
      const uint64_t pol = stream_policy();
      Ring r{0, 0};
#pragma unroll 1
      for (int i = 0; i < 32; i++) {
        if (i < ST) spin_until(t_start, TN(A0) + i * TN(AD) + (i >= TN(AN) ? TN(AL) : 0));
        if (i == ST) {
          asm volatile("barrier.cluster.wait.aligned;" ::: "memory");
          if (roles.by_sm) {
            uint32_t sm;
            asm volatile("mov.u32 %0, %%smid;" : "=r"(sm));
            if (elect_one()) { mbar_expect(bars + B_PEER, 8); st_async2(mapa(bars + B_END, ro.half ^ 1), sm, sm, mapa(bars + B_PEER, ro.half ^ 1)); }
            mbar_wait_u(bars + B_PEER, 0);
            if ((lds32(bars + B_END) ^ sm) != 1 || sm >= NCTA) asm volatile("trap;");
          }
        }
        if (i >= ST) mbar_wait(bars + B_EMPTY + r.s * 8, r.ph ^ 1);
        if (elect_one()) {
          mbar_expect(bars + B_FULL + r.s * 8, ro.pitch);
          tma_weights(sb + r.s * ro.pitch, &tmW1, i * 64, ro.g1_mt * 2, bars + B_FULL + r.s * 8, pol);
        }
        r.next();
      }
      if (ro.kind != 2) {
#pragma unroll 1
        for (int j = -1; j < 36; j++) {
          if (j == 3 && ro.kind == 0) mbar_wait_u(bars + B_CEMPTY + 24, 0);
          if (j >= ro.skip - 1) mbar_wait(bars + B_EMPTY + r.s * 8, r.ph ^ 1);
          if (j >= ro.skip - 1 && elect_one()) {
            mbar_expect(bars + B_FULL + r.s * 8, PITCH_S);
            tma_weights(sb + r.s * ro.pitch, &tmW2, g2_block(ro.half, j) * 64, ro.g2_m >> 6, bars + B_FULL + r.s * 8, pol);
          }
          r.next();
        }
        if (lane < 2) mbar_expect(bars + B_RFULL + lane * 8, 9216);
        __syncwarp();
        mbar_wait(bars + B_EMPTY + r.s * 8, r.ph ^ 1);
        if (lane == 0) mbar_arrive_cluster(mapa(bars + B_GO, ro.half ^ 1));
      }
      if (lane == 0) PROF(28);
    } else {
      const uint64_t pol = stream_policy();
      {
        const uint32_t hb = (ro.pitch - ASZ) >> 1, raw = bars + B_RAW + (warp - 9) * 40, dst = sb + ASZ + (warp - 9) * hb;
        const uint8_t* src = gs->h + (2 * ro.g1_nt + warp - 9) * hb;
        auto fetch_h = [&](int i) { if (elect_one()) { mbar_expect(raw + i * 8, hb); bulk_g2s(dst + i * ro.pitch, src + i * 73728, hb, raw + i * 8); } };
        int next = 0;
#pragma unroll 1
        for (int i = -1; i < ST; i++) {
          if (i >= 0) {
#pragma unroll 1
            for (uint32_t tries = 0;; tries++) {
              mbar_wait_u(raw + i * 8, tries & 1);
              if (lane == 0 && i == 0) PROF(29 + warp);
              const uint32_t pa = dst + i * ro.pitch + lane * 32 + (lane >> 2) * 4;
              uint32_t m = 1;
#pragma unroll
              for (int j = 0; j < 12; j++) m = min(m, lds32(pa + (j < 9 || ro.kind ? j : 0) * 1024));
              if (__all_sync(0xffffffffu, m)) break;
              if (lane == 0) PROF(26);
              fetch_h(i);
            }
            if (elect_one()) asm volatile("mbarrier.complete_tx.relaxed.cta.shared::cta.b64 [%0], %1;" ::"r"(bars + B_FULL + i * 8), "r"(hb) : "memory");
          }
#pragma unroll 1
          for (const int end = min(next + 2, ST); next < end; next++) {
            if (i < 0) spin_until(t_start, TN(H0) + next * TN(HD));
            fetch_h(next);
            if (next == 0 && tid == 288) PROF(3);
          }
          if (i < 0 && warp == 10) named_arrive(10, 64);
        }
      }
      const int chan = conv_chan(ro, lane < ro.nconv ? lane : 0);
      const uint32_t dskip = ldg16(ssmD + chan);
      uint4 shk;
      mbar_wait_u(bars + B_KVGO + (ro.kind ? 8 : (warp - 9) * 8), 0);
      if (ro.kind) shk = ldg128(ssmk + (size_t)chan * S_);
      else {
        const int cs = ro.cs, grp = (cs / 3) * 2 + warp - 9, cb0 = (cs % 3) * 3;
        const uint32_t kin_s = sb + ST * PITCH_S + (warp - 9) * KVW, kout = kin_s + 2 * KVIN, fb = bars + B_KFULL + (warp - 9) * 16;
        auto fetch = [&](int i) {
          if (elect_one()) {
            mbar_expect(fb + (i & 1) * 8, KVIN);
            tma2d_stream(kin_s + (i & 1) * KVIN, &tmK, (cb0 + i) * 64, grp * 32 - 4, fb + (i & 1) * 8, pol);
            tma2d_stream(kin_s + (i & 1) * KVIN + 4608, &tmV, (cb0 + i) * 64, grp * 32 - 1, fb + (i & 1) * 8, pol);
          }
        };
        fetch(0);
        shk = ldg128(shiftk + (cb0 * 64 + lane * 2) * 4);
#pragma unroll 1
        for (int i = 0; i < 3; i++) {
          const uint32_t w0 = __byte_perm(shk.x, shk.z, 0x5410), w1 = __byte_perm(shk.x, shk.z, 0x7632);
          const uint32_t w2 = __byte_perm(shk.y, shk.w, 0x5410), w3 = __byte_perm(shk.y, shk.w, 0x7632);
          const uint32_t ka = kin_s + (i & 1) * KVIN + lane * 4;
          mbar_wait_u(fb + (i & 1) * 8, i >> 1);
          if (tid == 288 && i < 2) PROF(30 + i);
          if (i < 2) fetch(i + 1);
          shk = ldg128(i < 2 ? shiftk + ((cb0 + i + 1) * 64 + lane * 2) * 4 : ssmk + (size_t)chan * S_);
          uint32_t kr[8], vr[8], t1, t2, t3, xp;
          {
            const uint32_t k0 = lds32(ka), k1 = lds32(ka + 128), k2 = lds32(ka + 256), k3 = lds32(ka + 384), v0 = lds32(ka + 4608);
#pragma unroll
            for (int j = 0; j < 8; j++) { kr[j] = lds32(ka + 512 + j * 128); vr[j] = lds32(ka + 4736 + j * 128); }
            xp = hmul2(hfma2(k3, w0, hfma2(k2, w1, hfma2(k1, w2, hmul2(k0, w3)))), v0);
            t1 = hfma2(k3, w1, hfma2(k2, w2, hmul2(k1, w3)));
            t2 = hfma2(k3, w2, hmul2(k2, w3));
            t3 = hmul2(k3, w3);
          }
#pragma unroll 1
          for (int o = 0; o < 4; o++) {
            const uint32_t from = ka + o * 1024, to = kout + (o >> 1) * 5120 + lane * 80 + (o & 1) * 32;
#pragma unroll
            for (int m = 0; m < 8; m += 4) {
              uint32_t x[4];
#pragma unroll
              for (int j = 0; j < 4; j++) {
                x[j] = hmul2(hfma2(kr[m + j], w0, t1), vr[m + j]);
                t1 = hfma2(kr[m + j], w1, t2);
                t2 = hfma2(kr[m + j], w2, t3);
                t3 = hmul2(kr[m + j], w3);
              }
#pragma unroll
              for (int c = 0; c < 2; c++) {
                const uint32_t sel = c ? 0x7632 : 0x5410;
                sts128(to + c * 2560 + m * 4, __byte_perm(x[0], xp, sel), __byte_perm(x[1], x[0], sel), __byte_perm(x[2], x[1], sel), __byte_perm(x[3], x[2], sel));
              }
#pragma unroll
              for (int j = m; j < m + 4; j++) { kr[j] = lds32_if(from + 1536 + j * 128, o < 3); vr[j] = lds32_if(from + 5760 + j * 128, o < 3); }
              xp = x[3];
            }
            if (o & 1) {
              fence_async_smem();
              __syncwarp();
              if (elect_one()) {
                bulk_wait_all();
                if (o == 1 && i) flag_add(gs->flags, FL_KV + i - 1, 1);
                tma4d_store(&tmKV, (cb0 + i) * 32, 0, 2 * grp + (o >> 1), kout + (o >> 1) * 5120);
                bulk_commit();
              }
              __syncwarp();
            }
          }
        }
        look = flag_ld(gs->flags, FL_KV + warp - 9);
        if (lane == 2 * (warp - 9)) bulk_prefetch(ssmk + (size_t)chan * S_, 2 * S_ * 2, pol);
        if (elect_one()) {
          bulk_wait_all();
          flag_add(gs->flags, FL_KV + 2, 1);
          if (warp == 9) PROFG(2);
        }
        __syncwarp();
      }
      {
        shk.x = __byte_perm(pack_bf16(bf_lo(shk.x) + bf_lo(dskip), 0.f), shk.x, 0x7610);
        const int mid = ro.kind ? 1 : 2;
#pragma unroll 1
        for (int i = warp == 9 ? 0 : mid; i < (warp == 9 ? mid : ro.nconv); i++) {
          const int b = i & 3, d = __shfl_sync(0xffffffffu, chan, i);
          const uint32_t base = conv_buf(sb, ro.kind, b), cf = bars + B_CFULL + b * 8;
          if (ro.kind ? i < 2 : !(i & 1)) wait_counter(gs->flags, FL_KV + (ro.kind ? 2 : i >> 1), 192u, i < 4 ? look : 0u, 200);
          if (i == 2) { mbar_wait_u(bars + B_CVGO, 0); spin_until(clock_now(), 600); }
          if (i == 0 && lane == 0) PROF(23);
          if (i == 2 * mid - 1) {
            mbar_wait_u(bars + B_G1DONE, 0);
            if (lane == 4 || lane == 5) bulk_prefetch(ssmk + (size_t)chan * S_, S_ * 2, pol);
          }
          if (i >= 4) mbar_wait_u(bars + B_CEMPTY + b * 8, 0);
          if (lane == i) sts128(base + CH_OFF, shk.x, shk.y, shk.z, shk.w);
          if (lane >= 29) sts128(base + CH_OFF + (lane - 32) * 16, 0u, 0u, 0u, 0u);
          fence_async_smem();
          __syncwarp();
          if (elect_one()) mbar_expect(cf, 4080 + 64 * 160);
#pragma unroll 1
          for (int k = 0; k < 5; k++) {
            if (elect_one()) {
              if (k < 4) asm volatile("cp.async.bulk.tensor.3d.shared::cluster.global.mbarrier::complete_tx::bytes [%0], [%1, {%3, %4, %5}], [%2];"
                                      ::"r"(base + CT_OFF + k * 2560), "l"(&tmKL), "r"(cf), "r"(0), "r"(k * 16), "r"(d) : "memory");
              else bulk_g2s_stream(base + CH_OFF + 16, ssmk + (size_t)d * S_ + 8, 4080, cf, pol);
            }
          }
        }
      }
      if (warp == 9) {
        if (lane < 6) sts32(bars + B_END + 8 + lane * 4, chan_pos(chan));
        __syncwarp();
        if (elect_one()) {
          const uint32_t bsz = ro.pitch - ASZ;
          if (ro.kind) { mbar_wait_u(bars + B_G1DONE, 0); gate_arrive(gs->flags, TN(GDELAY) + BLK_NS - (ro.kind == 1 ? TN(GBIG) : 0)); }
#pragma unroll 1
          for (int w = 0; w < 2; w++) {
            const uint32_t src = u_stage(sb, ro.pitch, w);
            mbar_wait_u(bars + B_USTG + w * 8, 0);
            bulk_s2g(gs->u + (size_t)(2 * ro.g1_mt + w) * D_ * 128 + ro.g1_nt * bsz, src, bsz);
            bulk_commit();
#pragma unroll 1
            for (int k = 0; k < ro.skip * w; k++) {
              mbar_arrive(bars + B_FULL + (2 + k) * 8);
              mbar_arrive(bars + B_EMPTY + (2 + k) * 8);
              mbar_arrive(bars + B_EMPTY + (2 + k) * 8);
            }
            bulk_wait_read();
            mbar_arrive(bars + B_UDONE + w * 8);
            bulk_wait_all();
            flag_add(gs->flags, FL_U + (ro.kind || w ? ro.half * 3 + (ro.kind ? 2 : 1) : 0), 1);
            PROFG(5 + 12 * w);
          }
#pragma unroll 1
          for (int i = 0; i < ro.nconv; i++) {
            mbar_wait_u(bars + B_SFULL + (i & 1) * 8, (i >> 1) & 1);
            bulk_s2g(gs->z + (size_t)lds32(bars + B_END + 8 + i * 4) * S_, conv_stage(sb, ro.kind) + (i & 1) * 4096, 4096);
            bulk_commit();
            if (ro.kind == 0 && i == ro.nconv - 4) gate_arrive(gs->flags, ro.skip * BLK_NS);
            bulk_wait_read();
            mbar_arrive(bars + B_SEMPTY + (i & 1) * 8);
          }
          bulk_wait_all();
          flag_add(gs->flags, FL_Z, 1);
          PROFG(6);
        }
      } else if (ro.kind != 2) {
        mbar_wait_u(bars + B_G1DONE, 0);
        uint2 gate;
#pragma unroll 1
        for (uint32_t spins = 0;; spins++) {
          asm volatile("ld.relaxed.gpu.global.v2.u32 {%0, %1}, [%2];" : "=r"(gate.x), "=r"(gate.y) : "l"(gs->flags + FL_GATE * 32) : "memory");
          if (gate.x == NCTA) break;
          __nanosleep(100);
          if (spins > SPIN_LIMIT) asm volatile("trap;");
        }
        if (lane == 0) PROF(46);
#pragma unroll 1
        for (int w = 0; w < 2; w++) {
          while (time_now() - gate.y < TN(GDELAY) + ro.skip * BLK_NS + w * TN(GDELAY1)) {}
          if (lane == 0) mbar_arrive(bars + B_G2GO + (w ^ (ro.nconv & 1)) * 8);
          if (lane == 0 && w == 0) PROF(24);
        }
        wait_counter(gs->flags, FL_Z, NCTA, 0, 300);
        spin_until(clock_now(), TN(ZDELAY) + TN(ZRAMP) * cta);
        if (elect_one()) {
          mbar_expect(bars + B_ZFULL, 18432);
          tma2d(sb + ST * ro.pitch, &tmZ, ro.g2_m, ro.dt * 144 + ro.half * 72, bars + B_ZFULL);
          tma2d(sb + ST * ro.pitch + 9216, &tmZ, ro.g2_m + 64, ro.dt * 144 + ro.half * 72, bars + B_ZFULL);
          PROFG(7);
        }
      }
    }
    if (warp >= 10) polling_done(gs->flags, lane);
  } else {
    asm volatile("setmaxnreg.inc.sync.aligned.u32 224;");
    const int wi = warp & 3, g = lane >> 2, qd = lane & 3, wt = tid & 127;
    const bool leader = wt == 0;
    Pipe p{{0, 0}, 0, false, 0};
    asm volatile("barrier.cluster.wait.aligned;" ::: "memory");
    int kind;
    {
      const Role ro = get_role(roles);
      kind = ro.kind;
      const int f0 = ro.g1_mt * 128 + wg * 64 + wi * 16 + g;
      uint32_t bias0 = ldg16(b1 + f0), bias1 = ldg16(b1 + f0 + 8);
      const uint32_t so = ((lane >> 4) * 8 + (lane & 7)) * 128 + (((2 * wi + ((lane >> 3) & 1)) ^ (lane & 7)) << 4);
      const int cB = (g >> 1) & 1, cA = g >> 2, b = 2 * wi + (g & 1), nconv = ro.nconv;
      const uint32_t toff = pin(CT_OFF + (40 * (2 * cA + cB) + 8 + b - 2 * qd) * 4);
      const int phi = 2 * cA + (qd >> 1) + cB, pp = cB ? (phi & 3) : ((phi + 3) & 3);
      const int srcB = shfl_ordered(((pp >> 1) << 4) | ((cB ^ 1) << 3) | ((g & 1) << 2) | ((pp & 1) << 1) | (qd & 1), lane);
      const bool pB1 = cB && phi < 4, pB2 = cB && phi == 4;
      const int word = (8 * cB + 2 * (phi & 3) + (qd & 1)) * 8 + b;
      const uint32_t sto = shfl_ordered(conv_stage(sb, kind) + wg * 4096 + (word ^ (((word >> 5) & 3) << 1)) * 4, lane);
      const uint32_t sa = shfl_ordered(u_stage(sb, ro.pitch, wg) + so, lane);
      uint32_t a[16][4];
      auto load_a = [&](uint32_t base, int t, uint32_t on) {
        const uint32_t pt = base + toff + (t >> 1) * 1280 + (t & 1) * 64;
        a[t][0] = lds32_if(pt + 32, on); a[t][1] = lds32_if(pt + 672, on); a[t][2] = lds32_if(pt, on); a[t][3] = lds32_if(pt + 640, on);
      };
      auto gemm1_done = [&]() {
        pipe_drain(p, bars, leader);
        if (leader) mbar_arrive(bars + B_G1DONE);
        mbar_wait_u(bars + B_EMPTY + (2 - wg) * 8, wg ^ 1);
        if (leader) PROF(4 + 10 * wg);
        if (tid == 128) PROFC(48);
      };
      {
        float acc[72];
        if (kind) {
          float big[96];
          gemm_run<1, LEAD_B>(big, 32, 0, p, sb, PITCH_B, wg, leader);
          if (wg == 1) named_arrive(6, 256);
          gemm1_done();
          if (wg < nconv) mbar_wait_u(bars + B_CFULL + wg * 8, 0);
#pragma unroll
          for (int t = 0; t < 8; t++) load_a(conv_buf(sb, 1, wg), t, 1);
          gelu_store<72, 96>(big, bias0, bias1, sa, 0u, [](int) { return 0u; });
#pragma unroll
          for (int i = 0; i < 72; i++) asm volatile("mov.b32 %0, %1;" : "=f"(acc[i]) : "f"(big[i]));
        } else {
          gemm_run<1, 0>(acc, 32 - LEAD_S - (wg ? 0 : PRE0), 0, p, sb, PITCH_S, wg, leader);
          if (wg == 1) pipe_drain(p, bars, leader);
          mbar_wait_u(bars + B_CFULL + wg * 8, 0);
#pragma unroll
          for (int t = 0; t < 8; t++) load_a(conv_buf(sb, 0, wg), t, 1);
          if (wg == 1) named_bar(8, 256);
          gemm_run<1, 0>(acc, LEAD_S + (wg ? 0 : PRE0), 1, p, sb, PITCH_S, wg, leader);
          named_arrive(8 - 2 * wg, 256);
          gemm1_done();
        }
        gelu_store<0, 72>(acc, bias0, bias1, sa, roles.by_sm >> 1, [&](int t) { return t + GLAG < 9 ? lds32(bars) : 0u; });
        fence_async_smem();
        __syncwarp();
        if (lane == 0) mbar_arrive(bars + B_USTG + wg * 8);
        if (leader) PROF(15 + wg);
      }
      {
#pragma unroll 1
        for (int i = wg; i < nconv; i += 2) {
          const uint32_t base = conv_buf(sb, kind, i & 3), next = conv_buf(sb, kind, (i + 2) & 3);
          const uint64_t dH = mkdesc(base + CH_OFF, 16, 128, 0);
          float y[8][16];
          named_bar(6 + wg, 256);
          wg_fence();
#pragma unroll
          for (int t = 0; t < 16; t++) {
            if (t == 8) wg_fence();
            if (t == CTURN) named_arrive(7 - wg, 256);
#pragma unroll
            for (int cb = t >> 1; cb < 8; cb++) {
              wgmma_rs_n32(y[cb], a[t][0], a[t][1], a[t][2], a[t][3], dH + (32 * cb - 32 * (t >> 1) - 2 * (t & 1) - 1), t);
              const int n = 8 * t - (t >> 1) * ((t - 1) >> 1) - (t >> 1) + cb + 1;
              if (n % CPER == 0 && n / CPER <= 8) load_a(base, 7 + n / CPER, 1);
            }
          }
          wg_commit();
          const bool more = i + 2 < nconv;
          if (more) mbar_wait_u(bars + B_CFULL + ((i + 2) & 3) * 8, (i + 2) >> 2);
          mbar_wait_u(bars + B_SEMPTY + wg * 8, ((i >> 1) & 1) ^ 1);
          wg_wait<0>();
          if (lane == 0) mbar_arrive(bars + B_CEMPTY + (i & 3) * 8);
          if (leader && i == nconv - 1) PROF(45);
          uint32_t P[16], Q[16], R[16], o[8];
#pragma unroll
          for (int j = 0; j < 32; j++) {
            if ((j & 3) == 0) load_a(next, j >> 2, more);
            float v0 = y[j >> 2][4 * (j & 3)], v1 = y[j >> 2][4 * (j & 3) + 1];
            if (j >= 2) { v0 += y[(j - 2) >> 2][4 * ((j - 2) & 3) + 2]; v1 += y[(j - 2) >> 2][4 * ((j - 2) & 3) + 3]; }
            if (j & 1) R[j >> 1] = shfl_ordered(pack_bf16(v0, v1), lane ^ 16);
            else P[j >> 1] = pack_bf16(v0, v1);
          }
#pragma unroll
          for (int m = 0; m < 16; m++) Q[m] = hadd2(P[m], cA ? R[m] : (m ? R[m - 1] : 0u));
#pragma unroll
          for (int m = 0; m < 8; m++) o[m] = shfl_ordered(pB1 ? Q[2 * m] : (pB2 ? (m ? Q[2 * m - 1] : 0u) : Q[2 * m + 1]), srcB);
#pragma unroll
          for (int m = 0; m < 8; m++) sts32(sto + m * 512, hadd2(pB1 ? Q[2 * m + 1] : Q[2 * m], o[m]));
          fence_async_smem();
          __syncwarp();
          if (lane == 0) mbar_arrive(bars + B_SFULL + wg * 8);
          if (leader && i == 5) PROF(53);
        }
        if (wg == (nconv & 1)) named_bar(6 + wg, 256);
      }
    }
    if (kind != 2) {
      const Role ro = get_role(roles);
      const uint32_t pitch = ro.pitch;
      const int s0 = ro.g2_m + wg * 64 + wi * 16 + g;
      const size_t go = (size_t)s0 * D_ + ro.dt * 128 + ro.half * 64 + qd * 8, go8 = (size_t)s0 * D_ + 512 + ro.dt * 16 + ro.half * 8 + qd * 2;
      uint32_t x[2][9], sg[2][9];
      float acc[72];
      p.r = Ring{(uint32_t)(2 + ro.skip), 0};
      mbar_wait_u(bars + B_G2GO + wg * 8, 0);
      gemm_run<0, 0>(acc, XAT + 2 * wg + 1 - ro.skip, 0, p, sb, pitch, wg, leader);
#pragma unroll
      for (int J = 0; J < 4; J++) {
        const uint4 v = ldg128(q + go + (J & 1) * 8 * D_ + (J >> 1) * 32);
        x[J & 1][4 * (J >> 1)] = v.x; x[J & 1][4 * (J >> 1) + 1] = v.y; x[J & 1][4 * (J >> 1) + 2] = v.z; x[J & 1][4 * (J >> 1) + 3] = v.w;
      }
      x[0][8] = ldg32(q + go8); x[1][8] = ldg32(q + go8 + 8 * D_);
      const uint4 st0 = ld_l2(gs->stats + s0), st1 = ld_l2(gs->stats + s0 + 8);
      const uint32_t braw0 = ldg16(b2 + s0), braw1 = ldg16(b2 + s0 + 8);
      gemm_run<0, 0>(acc, ZAT - XAT, 1, p, sb, pitch, wg, leader);
      {
        const int zw = 8 * wi + (g ^ ((((ro.g2_m >> 6) + wg) & 3) << 1));
        const uint32_t za = sb + ST * pitch + wg * 9216 + qd * 256 + (zw & 3) * 4;
        mbar_wait_u(bars + B_ZFULL, 0);
#pragma unroll
        for (int j = 0; j < 9; j++) {
          sg[0][j] = lds32(za + j * 1024 + (((zw >> 2) ^ (2 * qd)) << 4));
          sg[1][j] = lds32(za + j * 1024 + 128 + (((zw >> 2) ^ (2 * qd + 1)) << 4));
        }
      }
      gemm_run<0, 0>(acc, 1, 1, p, sb, pitch, wg, leader);
#pragma unroll
      for (int j = 0; j < 9; j++) {
        const uint32_t z0 = __byte_perm(sg[0][j], sg[1][j], 0x5410), z1 = __byte_perm(sg[0][j], sg[1][j], 0x7632);
        sg[0][j] = hmul2(ln_apply(x[0][j], st0), z0);
        sg[1][j] = hmul2(ln_apply(x[1][j], st1), z1);
        asm volatile("" : "+r"(sg[0][j]), "+r"(sg[1][j]));
      }
      gemm_run<0, SKEW>(acc, 35 - ZAT - LAG - 2 * wg, 1, p, sb, pitch, wg, leader);
      const uint32_t rbuf = sb + (69 % ST) * pitch + warp * 2304;
      const uint32_t rdst = mapa(rbuf, ro.half ^ 1), rbar = mapa(bars + B_RFULL + wg * 8, ro.half ^ 1);
      pipe_drain(p, bars, leader);
      if (leader) PROF(9 + 10 * wg);
      if (tid == 128) PROFC(50);
      float cs[36], ck[36];
      split_acc(acc, cs, ck);
      gemm2_part<0, 0, 4 * LAG>(cs, sb, pitch, wg);
      if (KPRE) gemm2_part<72, 0, KPRE>(ck, sb, pitch, wg);
      const float hb0 = fmaf(bf_lo(braw0), 0.5f, __uint_as_float(st0.w)), hb1 = fmaf(bf_lo(braw1), 0.5f, __uint_as_float(st1.w));
      mbar_wait(bars + B_GO, 0);
      wg_wait<KPRE ? 1 : 0>();
      if (leader) PROF(54 + wg);
#pragma unroll
      for (int i = 0; i < 5; i++) {
        const float* c = &cs[8 * i];
        const uint32_t v0 = pack_bf16(fmaf(c[0], 0.25f, hb0), fmaf(c[1], 0.25f, hb0)), v1 = pack_bf16(fmaf(c[2], 0.25f, hb1), fmaf(c[3], 0.25f, hb1));
        if (i < 4) st_async4(rdst + i * 512 + lane * 16, v0, v1, pack_bf16(fmaf(c[4], 0.25f, hb0), fmaf(c[5], 0.25f, hb0)), pack_bf16(fmaf(c[6], 0.25f, hb1), fmaf(c[7], 0.25f, hb1)), rbar);
        else st_async2(rdst + 2048 + lane * 8, v0, v1, rbar);
      }
      if (wg == 1) named_bar(7, 256);
      gemm2_part<72, KPRE, 4 * LAG>(ck, sb, pitch, wg);
      uint32_t rp[18];
      mbar_wait(bars + B_RFULL + wg * 8, 0);
#pragma unroll
      for (int m = 0; m < 4; m++) {
        const uint4 v = lds128(rbuf + m * 512 + lane * 16);
        rp[4 * m] = v.x; rp[4 * m + 1] = v.y; rp[4 * m + 2] = v.z; rp[4 * m + 3] = v.w;
      }
      { const uint2 v = lds64(rbuf + 2048 + lane * 8); rp[16] = v.x; rp[17] = v.y; }
      __nv_bfloat16* o = out + go;
      wg_wait<0>();
      if (leader) PROF(10 + 10 * wg);
      float h[2][4], t[2][4], half = 0.25f;
#pragma unroll
      for (int j = 0; j <= 9; j++) {
        if (j < 9) {
          const uint32_t ra = rp[2 * j], rb = rp[2 * j + 1];
          if (j >= 2) half = fmaf(t[j & 1][3], 0.f, 0.25f);
          h[j & 1][0] = fmaf(ck[4 * j], half, bf_lo(ra)); h[j & 1][1] = fmaf(ck[4 * j + 1], half, bf_hi(ra));
          h[j & 1][2] = fmaf(ck[4 * j + 2], half, bf_lo(rb)); h[j & 1][3] = fmaf(ck[4 * j + 3], half, bf_hi(rb));
#pragma unroll
          for (int u = 0; u < 4; u++) t[j & 1][u] = tanh_ordered(h[j & 1][u]);
        }
        if (j > 0) {
          const int k = j - 1;
          const float* hh = h[k & 1];
          const float* tt = t[k & 1];
          x[0][k] = hfma2(sg[0][k], pack_bf16(fmaf(hh[0], tt[0], hh[0]), fmaf(hh[1], tt[1], hh[1])), x[0][k]);
          x[1][k] = hfma2(sg[1][k], pack_bf16(fmaf(hh[2], tt[2], hh[2]), fmaf(hh[3], tt[3], hh[3])), x[1][k]);
          if ((k & 3) == 3) {
            *(uint4*)(o + (k >> 2) * 32) = make_uint4(x[0][k - 3], x[0][k - 2], x[0][k - 1], x[0][k]);
            *(uint4*)(o + 8 * D_ + (k >> 2) * 32) = make_uint4(x[1][k - 3], x[1][k - 2], x[1][k - 1], x[1][k]);
          }
        }
      }
      *(uint32_t*)(out + go8) = x[0][8];
      *(uint32_t*)(out + go8 + 8 * D_) = x[1][8];
      if (leader) PROF(11 + 7 * wg);
      if (tid == 128) PROFC(51);
    }
  }
}

typedef CUresult (*EncodeFn)(CUtensorMap*, CUtensorMapDataType, cuuint32_t, void*, const cuuint64_t*, const cuuint64_t*, const cuuint32_t*,
                             const cuuint32_t*, CUtensorMapInterleave, CUtensorMapSwizzle, CUtensorMapL2promotion, CUtensorMapFloatOOBfill);

uint32_t role_of_pair(int t) {
  int grp, i;
  if (t < 32) { const int j = t & 7; i = t >> 3; grp = j < 6 ? 1 + j : 12 + 2 * (j - 6); }
  else if (t < 60) { const int j = (t - 32) % 7; i = (t - 32) / 7; grp = j < 5 ? 7 + j : 13 + 2 * (j - 5); }
  else if (t < 62) return 2u | (uint32_t)(t - 60) << 2 | (uint32_t)(14 + 3 * (t - 60)) << 8 | 2u << 16;
  else { grp = 0; i = t - 62; }
  if (grp < 12) return (uint32_t)(i << 2 | grp << 4 | grp << 8 | i << 16);
  const int u = (grp & 1) * 4 + i;
  return (uint32_t)(1 | i << 2 | grp << 4 | (12 + 3 * ((grp - 12) >> 1) + u / 3) << 8 | (u % 3) << 16);
}

}

extern "C" void kernel_launch(void* const* d_in, const int* in_sizes, int n_in, void* d_out, int out_size) {
  (void)in_sizes; (void)n_in; (void)out_size;
  EncodeFn enc = nullptr;
  cudaDriverEntryPointQueryResult qr;
  cudaGetDriverEntryPoint("cuTensorMapEncodeTiled", (void**)&enc, cudaEnableDefault, &qr);
  Scratch* gs = nullptr;
  cudaGetSymbolAddress((void**)&gs, g_scratch);
  void *zp = gs->z, *hp = gs->h, *kvp = gs->kv + 128;
  CUtensorMap tmW1, tmW2, tmZ, tmH, tmK, tmV, tmKV, tmKL;
  for (int w = 0; w < 2; w++) {
    cuuint64_t gd[2] = {D_, S_};
    cuuint64_t st[1] = {D_ * 2};
    cuuint32_t bx[2] = {64, w ? 33u : 36u};
    cuuint32_t es[2] = {1, 1};
    enc(w ? &tmV : &tmK, CU_TENSOR_MAP_DATA_TYPE_BFLOAT16, 2, d_in[1 + w], gd, st, bx, es, CU_TENSOR_MAP_INTERLEAVE_NONE, CU_TENSOR_MAP_SWIZZLE_NONE,
        CU_TENSOR_MAP_L2_PROMOTION_L2_128B, CU_TENSOR_MAP_FLOAT_OOB_FILL_NONE);
  }
  {
    cuuint64_t gd[4] = {16, D_ / 2, 2, 128};
    cuuint64_t st[3] = {2 * KVT, KVT, 64};
    cuuint32_t bx[4] = {20, 32, 2, 1};
    cuuint32_t es[4] = {1, 1, 1, 1};
    enc(&tmKV, CU_TENSOR_MAP_DATA_TYPE_UINT32, 4, kvp, gd, st, bx, es, CU_TENSOR_MAP_INTERLEAVE_NONE, CU_TENSOR_MAP_SWIZZLE_NONE,
        CU_TENSOR_MAP_L2_PROMOTION_NONE, CU_TENSOR_MAP_FLOAT_OOB_FILL_NONE);
  }
  {
    cuuint64_t gd[3] = {40, 64, D_};
    cuuint64_t st[2] = {128, KVT};
    cuuint32_t bx[3] = {40, 16, 1};
    cuuint32_t es[3] = {1, 1, 1};
    enc(&tmKL, CU_TENSOR_MAP_DATA_TYPE_UINT32, 3, gs->kv + 96, gd, st, bx, es, CU_TENSOR_MAP_INTERLEAVE_NONE, CU_TENSOR_MAP_SWIZZLE_NONE,
        CU_TENSOR_MAP_L2_PROMOTION_NONE, CU_TENSOR_MAP_FLOAT_OOB_FILL_NONE);
  }
  {
    cuuint64_t gd[3] = {64, 32 * 72, 8};
    cuuint64_t st[2] = {1024, 128};
    cuuint32_t bx[3] = {64, 72, 1};
    cuuint32_t es[3] = {1, 1, 1};
    enc(&tmH, CU_TENSOR_MAP_DATA_TYPE_BFLOAT16, 3, hp, gd, st, bx, es, CU_TENSOR_MAP_INTERLEAVE_NONE, CU_TENSOR_MAP_SWIZZLE_128B,
        CU_TENSOR_MAP_L2_PROMOTION_NONE, CU_TENSOR_MAP_FLOAT_OOB_FILL_NONE);
  }
  for (int w = 0; w < 2; w++) {
    const cuuint64_t M = w ? S_ : F_, K = w ? F_ : S_;
    cuuint64_t gd[3] = {64, K, M / 64};
    cuuint64_t st[2] = {M * 2, 128};
    cuuint32_t bx[3] = {64, 64, 2};
    cuuint32_t es[3] = {1, 1, 1};
    enc(w ? &tmW2 : &tmW1, CU_TENSOR_MAP_DATA_TYPE_BFLOAT16, 3, d_in[w ? 9 : 7], gd, st, bx, es, CU_TENSOR_MAP_INTERLEAVE_NONE,
        CU_TENSOR_MAP_SWIZZLE_128B, CU_TENSOR_MAP_L2_PROMOTION_L2_256B, CU_TENSOR_MAP_FLOAT_OOB_FILL_NONE);
  }
  {
    cuuint64_t gd[2] = {S_, D_};
    cuuint64_t st[1] = {S_ * 2};
    cuuint32_t bx[2] = {64, 72};
    cuuint32_t es[2] = {1, 1};
    enc(&tmZ, CU_TENSOR_MAP_DATA_TYPE_BFLOAT16, 2, zp, gd, st, bx, es, CU_TENSOR_MAP_INTERLEAVE_NONE, CU_TENSOR_MAP_SWIZZLE_128B,
        CU_TENSOR_MAP_L2_PROMOTION_L2_256B, CU_TENSOR_MAP_FLOAT_OOB_FILL_NONE);
  }
  RoleMap roles;
  int dev = 0, sms = 0;
  cudaGetDevice(&dev);
  cudaDeviceGetAttribute(&sms, cudaDevAttrMultiProcessorCount, dev);
  roles.by_sm = sms == NCTA;
  for (int k = 0; k < NCTA / 2; k++) roles.role[k] = role_of_pair(k);
  cudaFuncSetAttribute(fused_kernel, cudaFuncAttributeMaxDynamicSharedMemorySize, SMEM_BYTES);
  fused_kernel<<<NCTA, 384, SMEM_BYTES>>>((const __nv_bfloat16*)d_in[0], gs, (const __nv_bfloat16*)d_in[8], (const __nv_bfloat16*)d_in[3],
                                          (const __nv_bfloat16*)d_in[4], (const __nv_bfloat16*)d_in[5], tmW1, tmW2, tmZ, tmH, tmK, tmV, tmKV, tmKL,
                                          roles, (const __nv_bfloat16*)d_in[10], (__nv_bfloat16*)d_out);
}
```

```cpp
#include <cuda_runtime.h>
#include <cuda_bf16.h>
#include <cuda.h>
#include <stdint.h>

namespace {

constexpr int S_ = 2048, D_ = 576, F_ = 4608;
constexpr int NCTA = 132, NG2 = 128;
constexpr int ST = 5, ASZ = 16384, PITCH_S = ASZ + 144 * 128, PITCH_B = ASZ + 192 * 128;
constexpr int KVIN = (36 + 33) * 128, KVW = 2 * KVIN + 64 * 176;
constexpr int BAR_OFF = ST * PITCH_S + 2 * KVW;
constexpr int SMEM_BYTES = BAR_OFF + 512;
constexpr int LNROT = 120;
constexpr int SKEW = 1;
constexpr int LEAD_S = 4, LEAD_B = 3;
constexpr int CTURN = 14, CPER = 4;
constexpr int TURN = 4, KPRE = 2;
constexpr int XAT = 12, ZAT = 25, GLAG = 4, PRE0 = 1;
constexpr int LAG = 4;
constexpr int CBUF = 14464, CH_OFF = 128, CT_OFF = 4224, KVT = 128 + 8192;
constexpr int BLK_NS = 336;
constexpr uint32_t SPIN_LIMIT = 1u << 22;

constexpr int FL_H = 0, FL_U = 3, FL_KV = 9, FL_Z = 12, FL_GATE = 13, FL_DONE = 14, FL_N = 15;
struct Scratch {
  uint32_t flags[64 * 32];
  uint4 stats[S_];
  uint8_t h[32 * 72 * 1024];
  uint8_t u[72 * D_ * 128];
  uint8_t kv[D_ * KVT];
  __nv_bfloat16 z[D_ * S_];
};
__device__ __align__(1024) Scratch g_scratch;
extern __shared__ __align__(1024) uint8_t smem_raw[];
#define TUNABLES(X) X(W9, 1200) X(QLATE, 40) X(QDELAY, 400) X(QRAMP, 5) X(A0, 1200) X(AD, 300) X(AN, 2) X(AL, 1500) X(H0, 3100) X(HD, 400) X(HS2, 8) X(HW, 4200) X(LK1, 7) X(LK2, 14) X(KVGO, 6) X(KVGO1, 10) X(CVGO, 31) X(GDELAY, 1280) X(GDELAY1, 128) X(GBIG, 960) X(ZDELAY, 0) X(ZRAMP, 30)
#define X(k, v) constexpr int T_##k = v;
TUNABLES(X)
#undef X
#define TN(k) T_##k
struct RoleMap { uint32_t role[NCTA / 2]; uint32_t by_sm; };
#define PROF(i) do {} while (0)
#define PROFG(i) do {} while (0)
#define PROFC(i) do {} while (0)

template<int TB> __device__ __forceinline__ void wgmma_ss(float (&d)[96], uint32_t da, uint32_t db, int sd) {
  asm volatile("{\n.reg .pred p;\n.reg .b64 a, b;\nsetp.ne.b32 p, %98, 0;\nmov.b64 a, {%96, %100};\nmov.b64 b, {%97, %101};\n"
    "wgmma.mma_async.sync.aligned.m64n192k16.f32.bf16.bf16 {%0, %1, %2, %3, %4, %5, %6, %7, %8, %9, %10, %11, %12, %13, %14, %15, %16, %17, %18, %19, %20, %21, %22, %23, %24, %25, %26, %27, %28, %29, %30, %31, %32, %33, %34, %35, %36, %37, %38, %39, %40, %41, %42, %43, %44, %45, %46, %47, %48, %49, %50, %51, %52, %53, %54, %55, %56, %57, %58, %59, %60, %61, %62, %63, %64, %65, %66, %67, %68, %69, %70, %71, %72, %73, %74, %75, %76, %77, %78, %79, %80, %81, %82, %83, %84, %85, %86, %87, %88, %89, %90, %91, %92, %93, %94, %95}, a, b, p, 1, 1, 1, %99;\n}\n"
    : "+f"(d[0]), "+f"(d[1]), "+f"(d[2]), "+f"(d[3]), "+f"(d[4]), "+f"(d[5]), "+f"(d[6]), "+f"(d[7]), "+f"(d[8]), "+f"(d[9]), "+f"(d[10]), "+f"(d[11]), "+f"(d[12]), "+f"(d[13]), "+f"(d[14]), "+f"(d[15]), "+f"(d[16]), "+f"(d[17]), "+f"(d[18]), "+f"(d[19]), "+f"(d[20]), "+f"(d[21]), "+f"(d[22]), "+f"(d[23]), "+f"(d[24]), "+f"(d[25]), "+f"(d[26]), "+f"(d[27]), "+f"(d[28]), "+f"(d[29]), "+f"(d[30]), "+f"(d[31]), "+f"(d[32]), "+f"(d[33]), "+f"(d[34]), "+f"(d[35]), "+f"(d[36]), "+f"(d[37]), "+f"(d[38]), "+f"(d[39]), "+f"(d[40]), "+f"(d[41]), "+f"(d[42]), "+f"(d[43]), "+f"(d[44]), "+f"(d[45]), "+f"(d[46]), "+f"(d[47]), "+f"(d[48]), "+f"(d[49]), "+f"(d[50]), "+f"(d[51]), "+f"(d[52]), "+f"(d[53]), "+f"(d[54]), "+f"(d[55]), "+f"(d[56]), "+f"(d[57]), "+f"(d[58]), "+f"(d[59]), "+f"(d[60]), "+f"(d[61]), "+f"(d[62]), "+f"(d[63]), "+f"(d[64]), "+f"(d[65]), "+f"(d[66]), "+f"(d[67]), "+f"(d[68]), "+f"(d[69]), "+f"(d[70]), "+f"(d[71]), "+f"(d[72]), "+f"(d[73]), "+f"(d[74]), "+f"(d[75]), "+f"(d[76]), "+f"(d[77]), "+f"(d[78]), "+f"(d[79]), "+f"(d[80]), "+f"(d[81]), "+f"(d[82]), "+f"(d[83]), "+f"(d[84]), "+f"(d[85]), "+f"(d[86]), "+f"(d[87]), "+f"(d[88]), "+f"(d[89]), "+f"(d[90]), "+f"(d[91]), "+f"(d[92]), "+f"(d[93]), "+f"(d[94]), "+f"(d[95])
    : "r"(da), "r"(db), "r"(sd), "n"(TB), "r"(0x40000040u), "r"(TB ? 0x40u : 0x40000040u));
}
template<int TB> __device__ __forceinline__ void wgmma_ss(float (&d)[72], uint32_t da, uint32_t db, int sd) {
  asm volatile("{\n.reg .pred p;\n.reg .b64 a, b;\nsetp.ne.b32 p, %74, 0;\nmov.b64 a, {%72, %76};\nmov.b64 b, {%73, %77};\n"
    "wgmma.mma_async.sync.aligned.m64n144k16.f32.bf16.bf16 {%0, %1, %2, %3, %4, %5, %6, %7, %8, %9, %10, %11, %12, %13, %14, %15, %16, %17, %18, %19, %20, %21, %22, %23, %24, %25, %26, %27, %28, %29, %30, %31, %32, %33, %34, %35, %36, %37, %38, %39, %40, %41, %42, %43, %44, %45, %46, %47, %48, %49, %50, %51, %52, %53, %54, %55, %56, %57, %58, %59, %60, %61, %62, %63, %64, %65, %66, %67, %68, %69, %70, %71}, a, b, p, 1, 1, 1, %75;\n}\n"
    : "+f"(d[0]), "+f"(d[1]), "+f"(d[2]), "+f"(d[3]), "+f"(d[4]), "+f"(d[5]), "+f"(d[6]), "+f"(d[7]), "+f"(d[8]), "+f"(d[9]), "+f"(d[10]), "+f"(d[11]), "+f"(d[12]), "+f"(d[13]), "+f"(d[14]), "+f"(d[15]), "+f"(d[16]), "+f"(d[17]), "+f"(d[18]), "+f"(d[19]), "+f"(d[20]), "+f"(d[21]), "+f"(d[22]), "+f"(d[23]), "+f"(d[24]), "+f"(d[25]), "+f"(d[26]), "+f"(d[27]), "+f"(d[28]), "+f"(d[29]), "+f"(d[30]), "+f"(d[31]), "+f"(d[32]), "+f"(d[33]), "+f"(d[34]), "+f"(d[35]), "+f"(d[36]), "+f"(d[37]), "+f"(d[38]), "+f"(d[39]), "+f"(d[40]), "+f"(d[41]), "+f"(d[42]), "+f"(d[43]), "+f"(d[44]), "+f"(d[45]), "+f"(d[46]), "+f"(d[47]), "+f"(d[48]), "+f"(d[49]), "+f"(d[50]), "+f"(d[51]), "+f"(d[52]), "+f"(d[53]), "+f"(d[54]), "+f"(d[55]), "+f"(d[56]), "+f"(d[57]), "+f"(d[58]), "+f"(d[59]), "+f"(d[60]), "+f"(d[61]), "+f"(d[62]), "+f"(d[63]), "+f"(d[64]), "+f"(d[65]), "+f"(d[66]), "+f"(d[67]), "+f"(d[68]), "+f"(d[69]), "+f"(d[70]), "+f"(d[71])
    : "r"(da), "r"(db), "r"(sd), "n"(TB), "r"(0x40000040u), "r"(TB ? 0x40u : 0x40000040u));
}
template<int TB> __device__ __forceinline__ void wgmma_ss(float (&d)[36], uint32_t da, uint32_t db, int sd) {
  asm volatile("{\n.reg .pred p;\n.reg .b64 a, b;\nsetp.ne.b32 p, %38, 0;\nmov.b64 a, {%36, %40};\nmov.b64 b, {%37, %41};\n"
    "wgmma.mma_async.sync.aligned.m64n72k16.f32.bf16.bf16 {%0, %1, %2, %3, %4, %5, %6, %7, %8, %9, %10, %11, %12, %13, %14, %15, %16, %17, %18, %19, %20, %21, %22, %23, %24, %25, %26, %27, %28, %29, %30, %31, %32, %33, %34, %35}, a, b, p, 1, 1, 1, %39;\n}\n"
    : "+f"(d[0]), "+f"(d[1]), "+f"(d[2]), "+f"(d[3]), "+f"(d[4]), "+f"(d[5]), "+f"(d[6]), "+f"(d[7]), "+f"(d[8]), "+f"(d[9]), "+f"(d[10]), "+f"(d[11]), "+f"(d[12]), "+f"(d[13]), "+f"(d[14]), "+f"(d[15]), "+f"(d[16]), "+f"(d[17]), "+f"(d[18]), "+f"(d[19]), "+f"(d[20]), "+f"(d[21]), "+f"(d[22]), "+f"(d[23]), "+f"(d[24]), "+f"(d[25]), "+f"(d[26]), "+f"(d[27]), "+f"(d[28]), "+f"(d[29]), "+f"(d[30]), "+f"(d[31]), "+f"(d[32]), "+f"(d[33]), "+f"(d[34]), "+f"(d[35])
    : "r"(da), "r"(db), "r"(sd), "n"(TB), "r"(0x40000040u), "r"(TB ? 0x40u : 0x40000040u));
}
__device__ __forceinline__ void wgmma_rs_n32(float (&d)[16], uint32_t a0, uint32_t a1, uint32_t a2, uint32_t a3, uint64_t db, int sd) {
  asm volatile("{\n.reg .pred p;\nsetp.ne.b32 p, %21, 0;\n"
    "wgmma.mma_async.sync.aligned.m64n32k16.f32.bf16.bf16 {%0, %1, %2, %3, %4, %5, %6, %7, %8, %9, %10, %11, %12, %13, %14, %15}, {%16, %17, %18, %19}, %20, p, 1, 1, 0;\n}\n"
    : "+f"(d[0]), "+f"(d[1]), "+f"(d[2]), "+f"(d[3]), "+f"(d[4]), "+f"(d[5]), "+f"(d[6]), "+f"(d[7]), "+f"(d[8]), "+f"(d[9]), "+f"(d[10]), "+f"(d[11]), "+f"(d[12]), "+f"(d[13]), "+f"(d[14]), "+f"(d[15])
    : "r"(a0), "r"(a1), "r"(a2), "r"(a3), "l"(db), "r"(sd));
}

__device__ __forceinline__ void wg_fence() { asm volatile("wgmma.fence.sync.aligned;" ::: "memory"); }
__device__ __forceinline__ void wg_commit() { asm volatile("wgmma.commit_group.sync.aligned;" ::: "memory"); }
template <int n> __device__ __forceinline__ void wg_wait() { asm volatile("wgmma.wait_group.sync.aligned %0;" ::"n"(n) : "memory"); }
__device__ __forceinline__ uint64_t mkdesc(uint32_t addr, uint32_t lbo, uint32_t sbo, uint32_t sw) {
  return (uint64_t)((addr & 0x3FFFF) >> 4) | ((uint64_t)(lbo >> 4) << 16) | ((uint64_t)(sbo >> 4) << 32) | ((uint64_t)sw << 62);
}
__device__ __forceinline__ void mbar_init(uint32_t a, int c) { asm volatile("mbarrier.init.shared::cta.b64 [%0], %1;" ::"r"(a), "r"(c)); }
__device__ __forceinline__ void mbar_expect(uint32_t a, uint32_t b) { asm volatile("mbarrier.arrive.expect_tx.shared::cta.b64 _, [%0], %1;" ::"r"(a), "r"(b) : "memory"); }
__device__ __forceinline__ void mbar_arrive(uint32_t a) { asm volatile("mbarrier.arrive.shared::cta.b64 _, [%0];" ::"r"(a) : "memory"); }
__device__ __forceinline__ void mbar_arrive_cluster(uint32_t raddr) { asm volatile("mbarrier.arrive.shared::cluster.b64 _, [%0];" ::"r"(raddr) : "memory"); }
__device__ __forceinline__ uint32_t mapa(uint32_t a, uint32_t cta) { uint32_t r; asm("mapa.shared::cluster.u32 %0, %1, %2;" : "=r"(r) : "r"(a), "r"(cta)); return r; }
__device__ __forceinline__ void mbar_wait(uint32_t a, uint32_t ph) {
  asm volatile(
      "{\n.reg .pred p;\n.reg .u32 c;\nmov.u32 c, 0;\n"
      "WAIT_LOOP:\nmbarrier.try_wait.parity.shared::cta.b64 p, [%0], %1;\n@p bra WAIT_DONE;\n"
      "add.u32 c, c, 1;\nsetp.lt.u32 p, c, %2;\n@p bra WAIT_LOOP;\ntrap;\nWAIT_DONE:\n}" ::"r"(a), "r"(ph), "n"(SPIN_LIMIT) : "memory");
}
__device__ __forceinline__ void mbar_wait_u(uint32_t a, uint32_t ph) {
  asm volatile("{\n.reg .pred p;\nWAIT_LOOP:\nmbarrier.try_wait.parity.shared::cta.b64 p, [%0], %1;\n@!p bra WAIT_LOOP;\n}" ::"r"(a), "r"(ph) : "memory");
}
__device__ __forceinline__ uint32_t desc_lo(uint32_t addr, uint32_t lbo) { return ((addr & 0x3FFFF) >> 4) | ((lbo >> 4) << 16); }
__device__ __forceinline__ void tma2d(uint32_t dst, const CUtensorMap* m, int c0, int c1, uint32_t bar) {
  asm volatile("cp.async.bulk.tensor.2d.shared::cluster.global.mbarrier::complete_tx::bytes [%0], [%1, {%3, %4}], [%2];" ::"r"(dst), "l"(m), "r"(bar), "r"(c0), "r"(c1) : "memory");
}
__device__ __forceinline__ void bulk_g2s(uint32_t dst, const void* src, uint32_t sz, uint32_t bar) {
  asm volatile("cp.async.bulk.shared::cluster.global.mbarrier::complete_tx::bytes [%0], [%1], %2, [%3];" ::"r"(dst), "l"(src), "r"(sz), "r"(bar) : "memory");
}
__device__ __forceinline__ void bulk_s2g(void* dst, uint32_t src, uint32_t sz) {
  asm volatile("cp.async.bulk.global.shared::cta.bulk_group [%0], [%1], %2;" ::"l"(dst), "r"(src), "r"(sz) : "memory");
}
__device__ __forceinline__ uint64_t stream_policy() {
  uint64_t p;
  asm volatile("createpolicy.fractional.L2::evict_first.b64 %0, 1.0;" : "=l"(p));
  return p;
}
__device__ __forceinline__ void tma_weights(uint32_t dst, const CUtensorMap* m, int k0, int mchunk, uint32_t bar, uint64_t pol) {
  asm volatile("cp.async.bulk.tensor.3d.shared::cluster.global.mbarrier::complete_tx::bytes.L2::cache_hint [%0], [%1, {%6, %3, %4}], [%2], %5;"
               ::"r"(dst), "l"(m), "r"(bar), "r"(k0), "r"(mchunk), "l"(pol), "r"(0) : "memory");
}
__device__ __forceinline__ bool elect_one() {
  uint32_t p;
  asm volatile("{\n.reg .pred P;\nelect.sync _|P, 0xffffffff;\nselp.u32 %0, 1, 0, P;\n}" : "=r"(p));
  return p;
}
__device__ __forceinline__ void bulk_g2s_stream(uint32_t dst, const void* src, uint32_t sz, uint32_t bar, uint64_t pol) {
  asm volatile("cp.async.bulk.shared::cluster.global.mbarrier::complete_tx::bytes.L2::cache_hint [%0], [%1], %2, [%3], %4;"
               ::"r"(dst), "l"(src), "r"(sz), "r"(bar), "l"(pol) : "memory");
}
__device__ __forceinline__ void tma3d_store(const CUtensorMap* m, int c1, int c2, uint32_t src) {
  asm volatile("cp.async.bulk.tensor.3d.global.shared::cta.bulk_group [%0, {%4, %2, %3}], [%1];" ::"l"(m), "r"(src), "r"(c1), "r"(c2), "r"(0) : "memory");
}
__device__ __forceinline__ void tma2d_stream(uint32_t dst, const CUtensorMap* m, int c0, int c1, uint32_t bar, uint64_t pol) {
  asm volatile("cp.async.bulk.tensor.2d.shared::cluster.global.mbarrier::complete_tx::bytes.L2::cache_hint [%0], [%1, {%3, %4}], [%2], %5;"
               ::"r"(dst), "l"(m), "r"(bar), "r"(c0), "r"(c1), "l"(pol) : "memory");
}
__device__ __forceinline__ void tma4d_store(const CUtensorMap* m, int c1, int c2, int c3, uint32_t src) {
  asm volatile("cp.async.bulk.tensor.4d.global.shared::cta.bulk_group [%0, {%5, %2, %3, %4}], [%1];" ::"l"(m), "r"(src), "r"(c1), "r"(c2), "r"(c3), "r"(0) : "memory");
}
__device__ __forceinline__ void bulk_commit() { asm volatile("cp.async.bulk.commit_group;" ::: "memory"); }
__device__ __forceinline__ void bulk_wait_all() { asm volatile("cp.async.bulk.wait_group 0;" ::: "memory"); }
__device__ __forceinline__ void fence_async_smem() { asm volatile("fence.proxy.async.shared::cta;" ::: "memory"); }
__device__ __forceinline__ void fence_async_global() { asm volatile("fence.proxy.async.global;" ::: "memory"); }
__device__ __forceinline__ void named_bar(int id, int n) { asm volatile("bar.sync %0, %1;" ::"r"(id), "r"(n) : "memory"); }
__device__ __forceinline__ void named_arrive(int id, int n) { asm volatile("bar.arrive %0, %1;" ::"r"(id), "r"(n) : "memory"); }
__device__ __forceinline__ void flag_add(uint32_t* f, int i, uint32_t v) { asm volatile("red.relaxed.gpu.global.add.u32 [%0], %1;" ::"l"(f + i * 32), "r"(v) : "memory"); }
__device__ __forceinline__ uint32_t flag_ld(uint32_t* f, int i) { uint32_t v; asm volatile("ld.relaxed.gpu.global.u32 %0, [%1];" : "=r"(v) : "l"(f + i * 32) : "memory"); return v; }
__device__ __forceinline__ void prefetch_map(const CUtensorMap* m) { asm volatile("prefetch.tensormap [%0];" ::"l"(m) : "memory"); }
__device__ __forceinline__ void stsm4_t(uint32_t a, uint32_t r0, uint32_t r1, uint32_t r2, uint32_t r3) {
  asm volatile("stmatrix.sync.aligned.m8n8.x4.trans.shared.b16 [%0], {%1, %2, %3, %4};" ::"r"(a), "r"(r0), "r"(r1), "r"(r2), "r"(r3) : "memory");
}
__device__ __forceinline__ uint32_t lds32(uint32_t a) { uint32_t v; asm volatile("ld.shared.u32 %0, [%1];" : "=r"(v) : "r"(a) : "memory"); return v; }
__device__ __forceinline__ void sts32(uint32_t a, uint32_t v) { asm volatile("st.shared.u32 [%0], %1;" ::"r"(a), "r"(v) : "memory"); }
__device__ __forceinline__ uint4 ld_l2(const uint4* p) { uint4 v; asm volatile("ld.relaxed.gpu.global.v4.u32 {%0, %1, %2, %3}, [%4];" : "=r"(v.x), "=r"(v.y), "=r"(v.z), "=r"(v.w) : "l"(p) : "memory"); return v; }
__device__ __forceinline__ void sts128(uint32_t a, uint32_t x, uint32_t y, uint32_t z, uint32_t w) { asm volatile("st.shared.v4.u32 [%0], {%1, %2, %3, %4};" ::"r"(a), "r"(x), "r"(y), "r"(z), "r"(w) : "memory"); }
__device__ __forceinline__ uint4 lds128(uint32_t a) { uint4 v; asm volatile("ld.shared.v4.u32 {%0, %1, %2, %3}, [%4];" : "=r"(v.x), "=r"(v.y), "=r"(v.z), "=r"(v.w) : "r"(a) : "memory"); return v; }
__device__ __forceinline__ void st_async4(uint32_t raddr, uint32_t a, uint32_t b, uint32_t c, uint32_t d, uint32_t rbar) {
  asm volatile("st.async.weak.shared::cluster.mbarrier::complete_tx::bytes.v4.b32 [%0], {%1, %2, %3, %4}, [%5];" ::"r"(raddr), "r"(a), "r"(b), "r"(c), "r"(d), "r"(rbar) : "memory");
}
__device__ __forceinline__ uint32_t pack_bf16(float lo, float hi) { uint32_t r; asm("cvt.rn.bf16x2.f32 %0, %1, %2;" : "=r"(r) : "f"(hi), "f"(lo)); return r; }
__device__ __forceinline__ float bf_lo(uint32_t v) { return __uint_as_float(v << 16); }
__device__ __forceinline__ float bf_hi(uint32_t v) { return __uint_as_float(v & 0xffff0000u); }
__device__ __forceinline__ float bf_round(float x) { return bf_lo(pack_bf16(x, 0.f)); }
__device__ __forceinline__ uint32_t hmul2(uint32_t a, uint32_t b) { uint32_t r; asm("mul.rn.bf16x2 %0, %1, %2;" : "=r"(r) : "r"(a), "r"(b)); return r; }
__device__ __forceinline__ uint32_t hsub2(uint32_t a, uint32_t b) { uint32_t r; asm("sub.rn.bf16x2 %0, %1, %2;" : "=r"(r) : "r"(a), "r"(b)); return r; }
__device__ __forceinline__ uint32_t hfma2(uint32_t a, uint32_t b, uint32_t c) { uint32_t r; asm("fma.rn.bf16x2 %0, %1, %2, %3;" : "=r"(r) : "r"(a), "r"(b), "r"(c)); return r; }
__device__ __forceinline__ uint4 ldg128(const void* p) { uint4 v; asm volatile("ld.global.nc.v4.u32 {%0, %1, %2, %3}, [%4];" : "=r"(v.x), "=r"(v.y), "=r"(v.z), "=r"(v.w) : "l"(p)); return v; }
__device__ __forceinline__ uint32_t ldg16(const void* p) { uint32_t v; asm volatile("ld.global.nc.u16 %0, [%1];" : "=r"(v) : "l"(p)); return v; }
__device__ __forceinline__ float tanh_ordered(float x) { float y; asm volatile("tanh.approx.f32 %0, %1;" : "=f"(y) : "f"(x)); return y; }
__device__ __forceinline__ uint32_t tanh2_ordered(uint32_t x) { uint32_t y; asm volatile("tanh.approx.bf16x2 %0, %1;" : "=r"(y) : "r"(x)); return y; }
__device__ __forceinline__ void mma16816(float (&d)[4], uint32_t a0, uint32_t a1, uint32_t a2, uint32_t a3, uint32_t b0, uint32_t b1) {
  asm("mma.sync.aligned.m16n8k16.row.col.f32.bf16.bf16.f32 {%0, %1, %2, %3}, {%4, %5, %6, %7}, {%8, %9}, {%0, %1, %2, %3};"
      : "+f"(d[0]), "+f"(d[1]), "+f"(d[2]), "+f"(d[3]) : "r"(a0), "r"(a1), "r"(a2), "r"(a3), "r"(b0), "r"(b1));
}
__device__ __forceinline__ uint32_t hadd2(uint32_t a, uint32_t b) { uint32_t r; asm("add.rn.bf16x2 %0, %1, %2;" : "=r"(r) : "r"(a), "r"(b)); return r; }
__device__ __forceinline__ uint32_t ldg32(const void* p) { uint32_t v; asm volatile("ld.global.nc.L1::no_allocate.u32 %0, [%1];" : "=r"(v) : "l"(p)); return v; }
__device__ __forceinline__ uint2 lds64(uint32_t a) { uint2 v; asm volatile("ld.shared.v2.u32 {%0, %1}, [%2];" : "=r"(v.x), "=r"(v.y) : "r"(a) : "memory"); return v; }
__device__ __forceinline__ uint32_t lds32_if(uint32_t a, uint32_t on) {
  uint32_t v;
  asm volatile("{\n.reg .pred p;\nsetp.ne.u32 p, %2, 0;\n@p ld.shared.u32 %0, [%1];\n}" : "=r"(v) : "r"(a), "r"(on) : "memory");
  return v;
}
__device__ __forceinline__ uint32_t clock_now() { uint32_t t; asm volatile("mov.u32 %0, %%clock;" : "=r"(t)); return t; }
__device__ __forceinline__ uint32_t time_now() { uint32_t t; asm volatile("mov.u32 %0, %%globaltimer_lo;" : "=r"(t)); return t; }
__device__ __forceinline__ void spin_until(uint32_t t0, uint32_t n) { while (clock_now() - t0 < n) {} }
__device__ __forceinline__ uint2 ldg64_if(const void* p, uint32_t on) {
  uint2 v;
  asm volatile("{\n.reg .pred p;\nsetp.ne.u32 p, %3, 0;\n@p ld.global.nc.v2.u32 {%0, %1}, [%2];\n}" : "=r"(v.x), "=r"(v.y) : "l"(p), "r"(on));
  return v;
}
template <class T> __device__ __forceinline__ T pin(T v) { asm volatile("" : "+r"(v)); return v; }
__device__ __forceinline__ void st_async2(uint32_t raddr, uint32_t a, uint32_t b, uint32_t rbar) {
  asm volatile("st.async.weak.shared::cluster.mbarrier::complete_tx::bytes.v2.b32 [%0], {%1, %2}, [%3];" ::"r"(raddr), "r"(a), "r"(b), "r"(rbar) : "memory");
}
__device__ __forceinline__ void bulk_prefetch(const void* src, uint32_t sz, uint64_t pol) {
  asm volatile("cp.async.bulk.prefetch.L2.global.L2::cache_hint [%0], %1, %2;" ::"l"(src), "r"(sz), "l"(pol) : "memory");
}
__device__ __forceinline__ void bulk_wait_read() { asm volatile("cp.async.bulk.wait_group.read 0;" ::: "memory"); }
__device__ __forceinline__ uint32_t shfl_ordered(uint32_t v, int src) { uint32_t r; asm volatile("shfl.sync.idx.b32 %0, %1, %2, 0x1f, 0xffffffff;" : "=r"(r) : "r"(v), "r"(src)); return r; }
__device__ __forceinline__ int chan_pos(int d) {
  return d < 512 ? 72 * (d >> 6) + ((d & 33) | ((d & 6) << 2) | ((d >> 2) & 6)) : 72 * ((d - 512) >> 3) + 64 + (d & 7);
}

struct Ring {
  uint32_t s, ph;
  __device__ __forceinline__ void next() { if (++s == ST) { s = 0; ph ^= 1; } }
};
constexpr int B_FULL = 0, B_GO = 40, B_CFULL = 48, B_SEMPTY = 80, B_ZFULL = 96, B_RFULL = 104, B_UDONE = 120, B_KFULL = 136, B_RAW = 168, B_CVGO = 248, B_PEER = 256, B_G2GO = 264, B_KVGO = 280,
              B_EMPTY = 296, B_G1DONE = 336,
              B_CEMPTY = 344, B_SFULL = 376, B_USTG = 392, B_END = 408;

static_assert((B_EMPTY - B_GO) % 16 == 0 && (B_CEMPTY - B_EMPTY) % 16 == 0 && (B_END - B_CEMPTY) % 16 == 0, "barrier groups");

__device__ __forceinline__ void wait_counter(uint32_t* f, int idx, uint32_t want, uint32_t first, uint32_t nap) {
#pragma unroll 1
  for (uint32_t spins = 0; first != want; spins++) {
    if (nap && spins) __nanosleep(nap);
    first = flag_ld(f, idx);
    if (spins > SPIN_LIMIT) asm volatile("trap;");
  }
  fence_async_global();
}

__device__ __forceinline__ void gate_arrive(uint32_t* f, uint32_t back) {
  asm volatile("red.relaxed.gpu.global.max.u32 [%0], %1;" ::"l"(f + FL_GATE * 32 + 1), "r"(time_now() - back) : "memory");
  flag_add(f, FL_GATE, 1);
}

__device__ __forceinline__ float ln_rinv(float var) {
  float rt, rinv;
  asm("sqrt.approx.ftz.f32 %0, %1;" : "=f"(rt) : "f"(bf_round(bf_round(var) + 1e-5f)));
  asm("rcp.approx.ftz.f32 %0, %1;" : "=f"(rinv) : "f"(bf_round(rt)));
  return rinv;
}
__device__ __forceinline__ uint32_t ln_apply(uint32_t x, const uint4& st) {
  const uint32_t d = hsub2(x, st.x);
  return hfma2(d, st.y, hmul2(d, st.z));
}

__device__ __forceinline__ void polling_done(uint32_t* f, int lane) {
  unsigned old = 0;
  if (lane == 0) asm volatile("atom.relaxed.gpu.global.add.u32 %0, [%1], 1;" : "=r"(old) : "l"(f + FL_DONE * 32) : "memory");
  old = __shfl_sync(0xffffffffu, old, 0);
  if (old == 2 * NCTA - 1) {
    if (lane < FL_N) *(uint2*)(f + lane * 32) = make_uint2(0u, 0u);
  }
}

struct Pipe { Ring r; uint32_t prev; bool pending; int cnt; };
__device__ __forceinline__ void pipe_drain(Pipe& p, uint32_t bars, bool leader) {
  wg_wait<0>();
  if (leader) mbar_arrive(bars + B_EMPTY + p.prev * 8);
  p.pending = false;
}
template <int TB, int LEAD, int R>
__device__ __forceinline__ void gemm_run(float (&acc)[R], int n, int accumulate, Pipe& p, uint32_t sb, uint32_t pitch, int wg, bool leader) {
  const uint32_t bars = sb + BAR_OFF;
  const uint32_t dA0 = desc_lo(sb + wg * 8192, 8192), dB0 = desc_lo(sb + ASZ, TB ? 128 : 16);
  constexpr int KB_STEP = TB ? 16 : 2;
#pragma unroll 1
  for (int kb = 0; kb < n; kb++) {
    if (LEAD && kb == n - LEAD && wg == 1) { if (TB) pipe_drain(p, bars, leader); named_bar(8, 256); }
    mbar_wait(bars + B_FULL + p.r.s * 8, p.r.ph);
    if (kb == 0 && !accumulate && threadIdx.x == 0) { PROF(21 + TB); PROFC(49 - 2 * TB); }
    const uint32_t dA = dA0 + p.r.s * (pitch >> 4), dB = dB0 + p.r.s * (pitch >> 4);
    wg_fence();
    wgmma_ss<TB>(acc, dA, dB, accumulate | kb);
#pragma unroll
    for (int k = 1; k < 4; k++) wgmma_ss<TB>(acc, dA + k * 128, dB + k * KB_STEP, 1);
    wg_commit();
    wg_wait<1>();
    if (p.pending && leader) mbar_arrive(bars + B_EMPTY + p.prev * 8);
    p.pending = true;
    p.prev = p.r.s;
    p.r.next();
  }
  if (LEAD && wg == 0) named_arrive(8, 256);
}

template <int BROW0, int I0, int I1>
__device__ __forceinline__ void gemm2_part(float (&c)[36], uint32_t sb, uint32_t pitch, int wg) {
  const uint32_t dA0 = desc_lo(sb + wg * 8192, 8192), dB0 = desc_lo(sb + ASZ + BROW0 * 128, 16);
  wg_fence();
#pragma unroll
  for (int i = I0; i < I1; i++) {
    const int step = 69 - LAG + (i >> 2);
    if ((i & 3) == 0 && BROW0 == 0) mbar_wait_u(sb + BAR_OFF + B_FULL + (step % ST) * 8, (step / ST) & 1);
    if (i == 4 * LAG - TURN && BROW0 && wg == 0) named_arrive(7, 256);
    wgmma_ss<0>(c, dA0 + (step % ST) * (pitch >> 4) + (i & 3) * 128, dB0 + (step % ST) * (pitch >> 4) + (i & 3) * 2, 1);
  }
  wg_commit();
}
__device__ __forceinline__ void split_acc(const float (&acc)[72], float (&a)[36], float (&b)[36]) {
#pragma unroll
  for (int i = 0; i < 36; i++) { asm volatile("mov.b32 %0, %1;" : "=f"(a[i]) : "f"(acc[i])); asm volatile("mov.b32 %0, %1;" : "=f"(b[i]) : "f"(acc[36 + i])); }
}
template <int V0, int V1, int R, class Slice>
__device__ __forceinline__ void gelu_store(const float (&acc)[R], uint32_t bias0, uint32_t bias1, uint32_t sa, uint32_t zero, Slice slice) {
  const uint32_t bb[2] = {pin(bias0) * 0x10001u, pin(bias1) * 0x10001u};
  uint32_t x[2][4], t[2][4], dep[V1 / 8], c3 = 0x3d123d12u;
#pragma unroll
  for (int j = V0 / 8; j <= V1 / 8; j++) {
    if (j < V1 / 8) {
      if (j >= V0 / 8 + GLAG) c3 = (dep[j - GLAG] & zero) | 0x3d123d12u;
#pragma unroll
      for (int u = 0; u < 4; u++) {
        x[j & 1][u] = hadd2(pack_bf16(acc[8 * j + 2 * u], acc[8 * j + 2 * u + 1]), bb[u & 1]);
        t[j & 1][u] = tanh2_ordered(hmul2(x[j & 1][u], hfma2(hmul2(x[j & 1][u], c3), x[j & 1][u], 0x3f4c3f4cu)));
      }
    }
    if (j > V0 / 8) {
      const uint32_t *xx = x[(j - 1) & 1], *tt = t[(j - 1) & 1];
      stsm4_t(sa + (j - 1) * 2048, hfma2(xx[0], tt[0], xx[0]), hfma2(xx[1], tt[1], xx[1]), hfma2(xx[2], tt[2], xx[2]), hfma2(xx[3], tt[3], xx[3]));
      dep[j - 1] = slice(j - 1);
    }
  }
}
struct Role { int half, kind, g2_m, dt, g1_mt, g1_nt, cs, nconv, skip; uint32_t pitch; };
__device__ __forceinline__ Role get_role(const RoleMap& roles) {
  uint32_t b, sm;
  asm volatile("mov.u32 %0, %%ctaid.x;" : "=r"(b));
  asm volatile("mov.u32 %0, %%smid;" : "=r"(sm));
  const uint32_t w = roles.role[(roles.by_sm ? sm : b) >> 1];
  const int half = b & 1, kind = w & 3, m = (w >> 4) & 15, dt = (w >> 2) & 3;
  return Role{half, kind, m * 128, dt, half * 18 + (int)((w >> 8) & 31), (int)(w >> 16), (m * 4 + dt) * 2 + half,
              kind ? kind * kind : 6 - half, kind ? 1 : 2 - 2 * half, kind ? (uint32_t)PITCH_B : (uint32_t)PITCH_S};
}
__device__ __forceinline__ int g2_block(int half, int j) { return j < 0 ? 0 : half * 36 + (j < 12 ? 2 * j : j < 24 ? 2 * j - 23 : j); }
__device__ __forceinline__ int conv_chan(const Role& ro, int i) {
  const bool early = ro.kind == 0 && i < 4;
  const int k = early ? 2 * ro.cs + (i & 1) : ro.kind == 2 ? 176 + 4 * ro.cs + i : ro.kind ? 48 + ro.cs : i == 4 ? ro.cs : 96 + (ro.cs >> 1);
  return (3 * (k >> 6) + (early ? i >> 1 : 2)) * 64 + (k & 63);
}
__device__ __forceinline__ uint32_t conv_buf(uint32_t sb, int kind, int b) {
  return sb + (kind ? (b ? b + 1 : ST) * PITCH_B : b == 3 ? (36 % ST) * PITCH_S : ST * PITCH_S + b * CBUF);
}
__device__ __forceinline__ uint32_t conv_stage(uint32_t sb, int kind) { return sb + (kind ? ST * PITCH_B + CBUF : ST * PITCH_S + 3 * CBUF); }
__device__ __forceinline__ uint32_t u_stage(uint32_t sb, uint32_t pitch, int w) { return sb + (2 - w) * pitch + ASZ; }

__global__ void __cluster_dims__(2, 1, 1) __launch_bounds__(384, 1)
fused_kernel(const __nv_bfloat16* __restrict__ q, Scratch* __restrict__ gs, const __nv_bfloat16* __restrict__ b1,
             const __nv_bfloat16* __restrict__ shiftk, const __nv_bfloat16* __restrict__ ssmk, const __nv_bfloat16* __restrict__ ssmD,
             const __grid_constant__ CUtensorMap tmW1, const __grid_constant__ CUtensorMap tmW2, const __grid_constant__ CUtensorMap tmZ,
             const __grid_constant__ CUtensorMap tmH, const __grid_constant__ CUtensorMap tmK, const __grid_constant__ CUtensorMap tmV,
             const __grid_constant__ CUtensorMap tmKV, const __grid_constant__ CUtensorMap tmKL, const __grid_constant__ RoleMap roles, const __nv_bfloat16* __restrict__ b2,
             __nv_bfloat16* __restrict__ out) {
  const int cta = blockIdx.x;
  const int tid = threadIdx.x;
  if (tid == 288) PROFG(0);

  const uint32_t t_start = clock_now();
  const int lc = (cta + LNROT) & 127;
  const uint32_t do_ln = cta < 128 && tid < 256;
  const int oct = lc + (tid & 128), ln_row = oct * 8 + ((tid >> 4) & 7), l16 = tid & 15;
  uint2 xr[9];
  const __nv_bfloat16* qrow = q + (size_t)ln_row * D_ + l16 * 4;
  asm volatile("" : "+l"(qrow));
  const int warp = __shfl_sync(0xffffffffu, tid >> 5, 0);
  if (warp < 8 || warp == 11) asm volatile("barrier.cluster.arrive.relaxed.aligned;" ::: "memory");
  if (do_ln && oct >= TN(QLATE)) spin_until(t_start, TN(QDELAY) + TN(QRAMP) * oct / 2);
#pragma unroll
  for (int i = 0; i < 9; i++) xr[i] = ldg64_if(qrow + i * 64, do_ln);
  if (tid == 0) PROF(32);
  const uint32_t sb = __shfl_sync(0xffffffffu, (uint32_t)__cvta_generic_to_shared(smem_raw), 0);
  const uint32_t bars = sb + BAR_OFF;
  const int lane = tid & 31;
  const int wg = warp >> 2;
  constexpr int LN_OFF = ST * PITCH_B;

  uint32_t look = 0;
  if (warp < 8 || warp == 11) {
    const int hq = (lane & 16) >> 3, hb = (lane & 16) + hq;
    float da[3][4] = {};
#pragma unroll
    for (int i = 0; i < 9; i++) mma16816(da[i % 3], xr[i].x, 0x3f803f80u, xr[i].y, 0x3f803f80u, xr[i].x, xr[i].y);
    const float r1 = ((da[0][2] + da[0][3]) + (da[1][2] + da[1][3])) + (da[2][2] + da[2][3]);
    const float r2 = (lane & 4) ? (da[0][1] + da[1][1]) + da[2][1] : (da[0][0] + da[1][0]) + da[2][0];
    const float s1 = __shfl_sync(0xffffffffu, r1, hq) + __shfl_sync(0xffffffffu, r1, hq + 1);
    const float s2 = (__shfl_sync(0xffffffffu, r2, hb) + __shfl_sync(0xffffffffu, r2, hb + 4)) + (__shfl_sync(0xffffffffu, r2, hb + 9) + __shfl_sync(0xffffffffu, r2, hb + 13));
    if (tid == 0) { asm volatile("" ::"f"(s2) : "memory"); PROF(27); }
    const float mean = s1 * (1.f / D_), var = fmaxf(fmaf(-mean, mean, s2 * (1.f / D_)), 0.f);
    const float rinv = ln_rinv(var), rinv2 = ln_rinv(var * rinv * rinv), scale = rinv * rinv2, shift = -bf_round((mean - bf_round(mean)) * rinv) * rinv2;
    const uint32_t m2 = pack_bf16(mean, mean), hi2 = pack_bf16(scale, scale), lo2 = pack_bf16(scale - bf_lo(hi2), scale - bf_lo(hi2)), sh2 = pack_bf16(shift, shift);
    const uint32_t hi1 = pack_bf16(rinv, rinv);
    asm volatile("{\n.reg .pred p;\nsetp.eq.u32 p, %5, 0;\n@p st.shared.v4.u32 [%0], {%1, %2, %3, %4};\n}" ::"r"(sb + LN_OFF + 18432 + tid), "r"(m2), "r"(hi1),
                 "r"(pack_bf16(rinv - bf_lo(hi1), rinv - bf_lo(hi1))), "r"(0u), "r"(tid & 0x10f) : "memory");
    const uint32_t g0 = 4 * (l16 >> 3) + 2 * (l16 & 1), hrow = sb + LN_OFF + ((tid >> 7) & 1) * 9216 + (tid & 0x70);
    const uint32_t hs0 = hrow + g0 * 128 + ((l16 >> 1) & 3) * 4, hs8 = ((hrow + (l16 >> 1) * 1152) ^ ((l16 >> 1) << 4)) + 1024 + (l16 & 1) * 8;
    uint32_t w[18];
#pragma unroll
    for (int i = 0; i < 18; i++) {
      const uint32_t d = hsub2((i & 1) ? xr[i >> 1].y : xr[i >> 1].x, m2);
      asm("max.u32 %0, %1, 1;" : "=r"(w[i]) : "r"(hfma2(d, hi2, hfma2(d, lo2, sh2))));
    }
#pragma unroll
    for (int i = 0; i < 16; i++) {
      const int gi = 9 * (i >> 1) + (i & 1);
      asm volatile("{\n.reg .pred p;\nsetp.ne.u32 p, %2, 0;\n@p st.shared.u32 [%0], %1;\n}" ::"r"((hs0 ^ ((g0 * 16 + (gi & 7) * 16) & 0x70)) + gi * 128), "r"(w[i]), "r"(do_ln) : "memory");
    }
    asm volatile("{\n.reg .pred p;\nsetp.ne.u32 p, %3, 0;\n@p st.shared.v2.u32 [%0], {%1, %2};\n}" ::"r"(hs8), "r"(w[16]), "r"(w[17]), "r"(do_ln) : "memory");
    if (tid == 224) PROF(13);
    fence_async_smem();
    if (warp < 8) named_arrive(wg, 160);
  } else if (warp != 8) {
    spin_until(t_start, TN(W9));
  }

  if (wg == 2) {
    asm volatile("setmaxnreg.dec.sync.aligned.u32 56;");
    auto store_h = [&](int w) {
      named_bar(w, 160);
      if (cta < 128 && elect_one()) {
        tma3d_store(&tmH, ((lc >> 3) + 16 * w) * 72, lc & 7, sb + LN_OFF + w * 9216);
        bulk_s2g(gs->stats + (lc + 128 * w) * 8, sb + LN_OFF + 18432 + w * 128, 128);
        bulk_commit();
      }
    };
    auto publish_h = [&](int w) {
      if (cta < 128 && elect_one()) { bulk_wait_all(); flag_add(gs->flags, FL_H + (w ? 2 : lc >> 6), 1); }
      __syncwarp();
    };
    if (warp == 11) {
      if (lc >= 64) spin_until(t_start, TN(HW));
      store_h(0);
      look = flag_ld(gs->flags, FL_H);
      if (lc < 64) publish_h(0);
      if (lane == 0) PROF(1);
    } else {
      if (elect_one()) {
        if (warp == 8) {
#pragma unroll
          for (int o = 0; o < B_GO; o += 8) mbar_init(bars + o, 1);
        } else {
#pragma unroll
          for (int o = 0; o < (B_EMPTY - B_GO) / 2; o += 8) mbar_init(bars + B_GO + (warp - 9) * ((B_EMPTY - B_GO) / 2) + o, 1);
#pragma unroll
          for (int o = 0; o < (B_CEMPTY - B_EMPTY) / 2; o += 8) mbar_init(bars + B_EMPTY + (warp - 9) * ((B_CEMPTY - B_EMPTY) / 2) + o, 2);
#pragma unroll
          for (int o = 0; o < (B_END - B_CEMPTY) / 2; o += 8) mbar_init(bars + B_CEMPTY + (warp - 9) * ((B_END - B_CEMPTY) / 2) + o, 4);
        }
        asm volatile("fence.mbarrier_init.release.cluster;" ::: "memory");
      }
      __syncwarp();
      asm volatile("barrier.cluster.arrive.relaxed.aligned;" ::: "memory");
      if (warp == 8) { prefetch_map(&tmW1); prefetch_map(&tmH); }
      if (warp == 9) { prefetch_map(&tmK); prefetch_map(&tmV); prefetch_map(&tmKV); prefetch_map(&tmKL); prefetch_map(&tmW2); prefetch_map(&tmZ); }
      if (tid == 256) PROF(35);
    }
    const Role ro = get_role(roles);
    if (warp != 8) asm volatile("barrier.cluster.wait.aligned;" ::: "memory");
    if (warp == 11) {
      Ring r{0, 1};
      const uint32_t bsz = ro.pitch - ASZ;
      const uint8_t* src = gs->h + ro.g1_nt * bsz + ST * 73728;
      named_bar(10, 64);
#pragma unroll 1
      for (int i = ST; i < 32; i++) {
        if (i == ST || i == 8 || i == 16) wait_counter(gs->flags, FL_H + (i >> 3), i == 16 ? 128u : 64u, look, 0);
        if (i == TN(LK1) || i == TN(LK2)) look = flag_ld(gs->flags, FL_H + (i >> 3) + 1);
        mbar_wait(bars + B_EMPTY + r.s * 8, r.ph ^ 1);
        if (elect_one()) bulk_g2s(sb + r.s * ro.pitch + ASZ, src, bsz, bars + B_FULL + r.s * 8);
        if (i == ST && lane == 0) PROF(25);
        if (i == TN(HS2)) store_h(1);
        if (i == TN(HS2) + 2 || (i == ST && lc >= 64)) publish_h(i != ST);
        if (i == TN(KVGO1) && lane == 0) mbar_arrive(bars + B_KVGO + 8);
        if (i == TN(KVGO) && lane == 0) mbar_arrive(bars + B_KVGO);
        if (i == TN(CVGO) && lane == 0) mbar_arrive(bars + B_CVGO);
        src += 73728;
        r.next();
      }
      if (ro.kind != 2) {
        look = 0;
#pragma unroll 1
        for (int j = -1; j < 36; j++) {
          const uint8_t* su = gs->u + ((size_t)g2_block(ro.half, j) * D_ + ro.dt * 144) * 128;
          if (j == -1 || j == 12 || j == 24) wait_counter(gs->flags, FL_U + (j < 0 ? 0 : ro.half * 3 + j / 12), j < 0 ? 96u : j == 24 ? 18u : 48u, look, 100);
          if (j == (ro.skip ? 4 : -1) || j == 3) mbar_wait_u(bars + B_UDONE + (j == 3 ? 8 : 0), 0);
          if (j >= ro.skip - 1) mbar_wait(bars + B_EMPTY + r.s * 8, r.ph ^ 1);
          if (j >= ro.skip - 1 && elect_one()) {
            bulk_g2s(sb + r.s * ro.pitch + ASZ, su + (ro.half ^ 1) * 9216, 9216, bars + B_FULL + r.s * 8);
            bulk_g2s(sb + r.s * ro.pitch + ASZ + 9216, su + ro.half * 9216, 9216, bars + B_FULL + r.s * 8);
          }
          if (j == 9 || j == 21) look = flag_ld(gs->flags, FL_U + ro.half * 3 + j / 12 + 1);
          if (j == 1 && lane == 0) PROF(8);
          r.next();
        }
#pragma unroll 1
        for (int o = lane; o < ST * 73728 / 16 / NG2; o += 32) ((uint4*)gs->h)[ro.cs * (ST * 73728 / 16 / NG2) + o] = make_uint4(0u, 0u, 0u, 0u);
      }
    } else if (warp == 8) {
      const uint64_t pol = stream_policy();
      Ring r{0, 0};
#pragma unroll 1
      for (int i = 0; i < 32; i++) {
        if (i < ST) spin_until(t_start, TN(A0) + i * TN(AD) + (i >= TN(AN) ? TN(AL) : 0));
        if (i == ST) {
          asm volatile("barrier.cluster.wait.aligned;" ::: "memory");
          if (roles.by_sm) {
            uint32_t sm;
            asm volatile("mov.u32 %0, %%smid;" : "=r"(sm));
            if (elect_one()) { mbar_expect(bars + B_PEER, 8); st_async2(mapa(bars + B_END, ro.half ^ 1), sm, sm, mapa(bars + B_PEER, ro.half ^ 1)); }
            mbar_wait_u(bars + B_PEER, 0);
            if ((lds32(bars + B_END) ^ sm) != 1 || sm >= NCTA) asm volatile("trap;");
          }
        }
        if (i >= ST) mbar_wait(bars + B_EMPTY + r.s * 8, r.ph ^ 1);
        if (elect_one()) {
          mbar_expect(bars + B_FULL + r.s * 8, ro.pitch);
          tma_weights(sb + r.s * ro.pitch, &tmW1, i * 64, ro.g1_mt * 2, bars + B_FULL + r.s * 8, pol);
        }
        r.next();
      }
      if (ro.kind != 2) {
#pragma unroll 1
        for (int j = -1; j < 36; j++) {
          if (j == 3 && ro.kind == 0) mbar_wait_u(bars + B_CEMPTY + 24, 0);
          if (j >= ro.skip - 1) mbar_wait(bars + B_EMPTY + r.s * 8, r.ph ^ 1);
          if (j >= ro.skip - 1 && elect_one()) {
            mbar_expect(bars + B_FULL + r.s * 8, PITCH_S);
            tma_weights(sb + r.s * ro.pitch, &tmW2, g2_block(ro.half, j) * 64, ro.g2_m >> 6, bars + B_FULL + r.s * 8, pol);
          }
          r.next();
        }
        if (lane < 2) mbar_expect(bars + B_RFULL + lane * 8, 9216);
        __syncwarp();
        mbar_wait(bars + B_EMPTY + r.s * 8, r.ph ^ 1);
        if (lane == 0) mbar_arrive_cluster(mapa(bars + B_GO, ro.half ^ 1));
      }
      if (lane == 0) PROF(28);
    } else {
      const uint64_t pol = stream_policy();
      {
        const uint32_t hb = (ro.pitch - ASZ) >> 1, raw = bars + B_RAW + (warp - 9) * 40, dst = sb + ASZ + (warp - 9) * hb;
        const uint8_t* src = gs->h + (2 * ro.g1_nt + warp - 9) * hb;
        auto fetch_h = [&](int i) { if (elect_one()) { mbar_expect(raw + i * 8, hb); bulk_g2s(dst + i * ro.pitch, src + i * 73728, hb, raw + i * 8); } };
        int next = 0;
#pragma unroll 1
        for (int i = -1; i < ST; i++) {
          if (i >= 0) {
#pragma unroll 1
            for (uint32_t tries = 0;; tries++) {
              mbar_wait_u(raw + i * 8, tries & 1);
              if (lane == 0 && i == 0) PROF(29 + warp);
              const uint32_t pa = dst + i * ro.pitch + lane * 32 + (lane >> 2) * 4;
              uint32_t m = 1;
#pragma unroll
              for (int j = 0; j < 12; j++) m = min(m, lds32(pa + (j < 9 || ro.kind ? j : 0) * 1024));
              if (__all_sync(0xffffffffu, m)) break;
              if (lane == 0) PROF(26);
              fetch_h(i);
            }
            if (elect_one()) asm volatile("mbarrier.complete_tx.relaxed.cta.shared::cta.b64 [%0], %1;" ::"r"(bars + B_FULL + i * 8), "r"(hb) : "memory");
          }
#pragma unroll 1
          for (const int end = min(next + 2, ST); next < end; next++) {
            if (i < 0) spin_until(t_start, TN(H0) + next * TN(HD));
            fetch_h(next);
            if (next == 0 && tid == 288) PROF(3);
          }
          if (i < 0 && warp == 10) named_arrive(10, 64);
        }
      }
      const int chan = conv_chan(ro, lane < ro.nconv ? lane : 0);
      const uint32_t dskip = ldg16(ssmD + chan);
      uint4 shk;
      mbar_wait_u(bars + B_KVGO + (ro.kind ? 8 : (warp - 9) * 8), 0);
      if (ro.kind) shk = ldg128(ssmk + (size_t)chan * S_);
      else {
        const int cs = ro.cs, grp = (cs / 3) * 2 + warp - 9, cb0 = (cs % 3) * 3;
        const uint32_t kin_s = sb + ST * PITCH_S + (warp - 9) * KVW, kout = kin_s + 2 * KVIN, fb = bars + B_KFULL + (warp - 9) * 16;
        auto fetch = [&](int i) {
          if (elect_one()) {
            mbar_expect(fb + (i & 1) * 8, KVIN);
            tma2d_stream(kin_s + (i & 1) * KVIN, &tmK, (cb0 + i) * 64, grp * 32 - 4, fb + (i & 1) * 8, pol);
            tma2d_stream(kin_s + (i & 1) * KVIN + 4608, &tmV, (cb0 + i) * 64, grp * 32 - 1, fb + (i & 1) * 8, pol);
          }
        };
        fetch(0);
        shk = ldg128(shiftk + (cb0 * 64 + lane * 2) * 4);
#pragma unroll 1
        for (int i = 0; i < 3; i++) {
          const uint32_t w0 = __byte_perm(shk.x, shk.z, 0x5410), w1 = __byte_perm(shk.x, shk.z, 0x7632);
          const uint32_t w2 = __byte_perm(shk.y, shk.w, 0x5410), w3 = __byte_perm(shk.y, shk.w, 0x7632);
          const uint32_t ka = kin_s + (i & 1) * KVIN + lane * 4;
          mbar_wait_u(fb + (i & 1) * 8, i >> 1);
          if (tid == 288 && i < 2) PROF(30 + i);
          if (i < 2) fetch(i + 1);
          shk = ldg128(i < 2 ? shiftk + ((cb0 + i + 1) * 64 + lane * 2) * 4 : ssmk + (size_t)chan * S_);
          uint32_t kr[8], vr[8], t1, t2, t3, xp;
          {
            const uint32_t k0 = lds32(ka), k1 = lds32(ka + 128), k2 = lds32(ka + 256), k3 = lds32(ka + 384), v0 = lds32(ka + 4608);
#pragma unroll
            for (int j = 0; j < 8; j++) { kr[j] = lds32(ka + 512 + j * 128); vr[j] = lds32(ka + 4736 + j * 128); }
            xp = hmul2(hfma2(k3, w0, hfma2(k2, w1, hfma2(k1, w2, hmul2(k0, w3)))), v0);
            t1 = hfma2(k3, w1, hfma2(k2, w2, hmul2(k1, w3)));
            t2 = hfma2(k3, w2, hmul2(k2, w3));
            t3 = hmul2(k3, w3);
          }
#pragma unroll 1
          for (int o = 0; o < 4; o++) {
            const uint32_t from = ka + o * 1024, to = kout + (o >> 1) * 5120 + lane * 80 + (o & 1) * 32;
#pragma unroll
            for (int m = 0; m < 8; m += 4) {
              uint32_t x[4];
#pragma unroll
              for (int j = 0; j < 4; j++) {
                x[j] = hmul2(hfma2(kr[m + j], w0, t1), vr[m + j]);
                t1 = hfma2(kr[m + j], w1, t2);
                t2 = hfma2(kr[m + j], w2, t3);
                t3 = hmul2(kr[m + j], w3);
              }
#pragma unroll
              for (int c = 0; c < 2; c++) {
                const uint32_t sel = c ? 0x7632 : 0x5410;
                sts128(to + c * 2560 + m * 4, __byte_perm(x[0], xp, sel), __byte_perm(x[1], x[0], sel), __byte_perm(x[2], x[1], sel), __byte_perm(x[3], x[2], sel));
              }
#pragma unroll
              for (int j = m; j < m + 4; j++) { kr[j] = lds32_if(from + 1536 + j * 128, o < 3); vr[j] = lds32_if(from + 5760 + j * 128, o < 3); }
              xp = x[3];
            }
            if (o & 1) {
              fence_async_smem();
              __syncwarp();
              if (elect_one()) {
                bulk_wait_all();
                if (o == 1 && i) flag_add(gs->flags, FL_KV + i - 1, 1);
                tma4d_store(&tmKV, (cb0 + i) * 32, 0, 2 * grp + (o >> 1), kout + (o >> 1) * 5120);
                bulk_commit();
              }
              __syncwarp();
            }
          }
        }
        look = flag_ld(gs->flags, FL_KV + warp - 9);
        if (lane == 2 * (warp - 9)) bulk_prefetch(ssmk + (size_t)chan * S_, 2 * S_ * 2, pol);
        if (elect_one()) {
          bulk_wait_all();
          flag_add(gs->flags, FL_KV + 2, 1);
          if (warp == 9) PROFG(2);
        }
        __syncwarp();
      }
      {
        shk.x = __byte_perm(pack_bf16(bf_lo(shk.x) + bf_lo(dskip), 0.f), shk.x, 0x7610);
        const int mid = ro.kind ? 1 : 2;
#pragma unroll 1
        for (int i = warp == 9 ? 0 : mid; i < (warp == 9 ? mid : ro.nconv); i++) {
          const int b = i & 3, d = __shfl_sync(0xffffffffu, chan, i);
          const uint32_t base = conv_buf(sb, ro.kind, b), cf = bars + B_CFULL + b * 8;
          if (ro.kind ? i < 2 : !(i & 1)) wait_counter(gs->flags, FL_KV + (ro.kind ? 2 : i >> 1), 192u, i < 4 ? look : 0u, 200);
          if (i == 2) { mbar_wait_u(bars + B_CVGO, 0); spin_until(clock_now(), 600); }
          if (i == 0 && lane == 0) PROF(23);
          if (i == 2 * mid - 1) {
            mbar_wait_u(bars + B_G1DONE, 0);
            if (lane == 4 || lane == 5) bulk_prefetch(ssmk + (size_t)chan * S_, S_ * 2, pol);
          }
          if (i >= 4) mbar_wait_u(bars + B_CEMPTY + b * 8, 0);
          if (lane == i) sts128(base + CH_OFF, shk.x, shk.y, shk.z, shk.w);
          if (lane >= 29) sts128(base + CH_OFF + (lane - 32) * 16, 0u, 0u, 0u, 0u);
          fence_async_smem();
          __syncwarp();
          if (elect_one()) mbar_expect(cf, 4080 + 64 * 160);
#pragma unroll 1
          for (int k = 0; k < 5; k++) {
            if (elect_one()) {
              if (k < 4) asm volatile("cp.async.bulk.tensor.3d.shared::cluster.global.mbarrier::complete_tx::bytes [%0], [%1, {%3, %4, %5}], [%2];"
                                      ::"r"(base + CT_OFF + k * 2560), "l"(&tmKL), "r"(cf), "r"(0), "r"(k * 16), "r"(d) : "memory");
              else bulk_g2s_stream(base + CH_OFF + 16, ssmk + (size_t)d * S_ + 8, 4080, cf, pol);
            }
          }
        }
      }
      if (warp == 9) {
        if (lane < 6) sts32(bars + B_END + 8 + lane * 4, chan_pos(chan));
        __syncwarp();
        if (elect_one()) {
          const uint32_t bsz = ro.pitch - ASZ;
          if (ro.kind) { mbar_wait_u(bars + B_G1DONE, 0); gate_arrive(gs->flags, TN(GDELAY) + BLK_NS - (ro.kind == 1 ? TN(GBIG) : 0)); }
#pragma unroll 1
          for (int w = 0; w < 2; w++) {
            const uint32_t src = u_stage(sb, ro.pitch, w);
            mbar_wait_u(bars + B_USTG + w * 8, 0);
            bulk_s2g(gs->u + (size_t)(2 * ro.g1_mt + w) * D_ * 128 + ro.g1_nt * bsz, src, bsz);
            bulk_commit();
#pragma unroll 1
            for (int k = 0; k < ro.skip * w; k++) {
              mbar_arrive(bars + B_FULL + (2 + k) * 8);
              mbar_arrive(bars + B_EMPTY + (2 + k) * 8);
              mbar_arrive(bars + B_EMPTY + (2 + k) * 8);
            }
            bulk_wait_read();
            mbar_arrive(bars + B_UDONE + w * 8);
            if (ro.kind && !w) continue;
            bulk_wait_all();
            flag_add(gs->flags, FL_U + (w ? ro.half * 3 + (ro.kind ? 2 : 1) : 0), 1);
            PROFG(5 + 12 * w);
          }
#pragma unroll 1
          for (int i = 0; i < ro.nconv; i++) {
            mbar_wait_u(bars + B_SFULL + (i & 1) * 8, (i >> 1) & 1);
            bulk_s2g(gs->z + (size_t)lds32(bars + B_END + 8 + i * 4) * S_, conv_stage(sb, ro.kind) + (i & 1) * 4096, 4096);
            bulk_commit();
            if (ro.kind == 0 && i == ro.nconv - 4) gate_arrive(gs->flags, ro.skip * BLK_NS);
            bulk_wait_read();
            mbar_arrive(bars + B_SEMPTY + (i & 1) * 8);
          }
          bulk_wait_all();
          flag_add(gs->flags, FL_Z, 1);
          PROFG(6);
        }
      } else if (ro.kind != 2) {
        mbar_wait_u(bars + B_G1DONE, 0);
        uint2 gate;
#pragma unroll 1
        for (uint32_t spins = 0;; spins++) {
          asm volatile("ld.relaxed.gpu.global.v2.u32 {%0, %1}, [%2];" : "=r"(gate.x), "=r"(gate.y) : "l"(gs->flags + FL_GATE * 32) : "memory");
          if (gate.x == NCTA) break;
          __nanosleep(100);
          if (spins > SPIN_LIMIT) asm volatile("trap;");
        }
        if (lane == 0) PROF(46);
#pragma unroll 1
        for (int w = 0; w < 2; w++) {
          while (time_now() - gate.y < TN(GDELAY) + ro.skip * BLK_NS + w * TN(GDELAY1)) {}
          if (lane == 0) mbar_arrive(bars + B_G2GO + (w ^ (ro.nconv & 1)) * 8);
          if (lane == 0 && w == 0) PROF(24);
        }
        wait_counter(gs->flags, FL_Z, NCTA, 0, 300);
        spin_until(clock_now(), TN(ZDELAY) + TN(ZRAMP) * cta);
        if (elect_one()) {
          mbar_expect(bars + B_ZFULL, 18432);
          tma2d(sb + ST * ro.pitch, &tmZ, ro.g2_m, ro.dt * 144 + ro.half * 72, bars + B_ZFULL);
          tma2d(sb + ST * ro.pitch + 9216, &tmZ, ro.g2_m + 64, ro.dt * 144 + ro.half * 72, bars + B_ZFULL);
          PROFG(7);
        }
      }
    }
    if (warp >= 10) polling_done(gs->flags, lane);
  } else {
    asm volatile("setmaxnreg.inc.sync.aligned.u32 224;");
    const int wi = warp & 3, g = lane >> 2, qd = lane & 3, wt = tid & 127;
    const bool leader = wt == 0;
    Pipe p{{0, 0}, 0, false, 0};
    asm volatile("barrier.cluster.wait.aligned;" ::: "memory");
    int kind;
    {
      const Role ro = get_role(roles);
      kind = ro.kind;
      const int f0 = ro.g1_mt * 128 + wg * 64 + wi * 16 + g;
      uint32_t bias0 = ldg16(b1 + f0), bias1 = ldg16(b1 + f0 + 8);
      const uint32_t so = ((lane >> 4) * 8 + (lane & 7)) * 128 + (((2 * wi + ((lane >> 3) & 1)) ^ (lane & 7)) << 4);
      const int cB = (g >> 1) & 1, cA = g >> 2, b = 2 * wi + (g & 1), nconv = ro.nconv;
      const uint32_t toff = pin(CT_OFF + (40 * (2 * cA + cB) + 8 + b - 2 * qd) * 4);
      const int phi = 2 * cA + (qd >> 1) + cB, pp = cB ? (phi & 3) : ((phi + 3) & 3);
      const int srcB = shfl_ordered(((pp >> 1) << 4) | ((cB ^ 1) << 3) | ((g & 1) << 2) | ((pp & 1) << 1) | (qd & 1), lane);
      const bool pB1 = cB && phi < 4, pB2 = cB && phi == 4;
      const int word = (8 * cB + 2 * (phi & 3) + (qd & 1)) * 8 + b;
      const uint32_t sto = shfl_ordered(conv_stage(sb, kind) + wg * 4096 + (word ^ (((word >> 5) & 3) << 1)) * 4, lane);
      const uint32_t sa = shfl_ordered(u_stage(sb, ro.pitch, wg) + so, lane);
      uint32_t a[16][4];
      auto load_a = [&](uint32_t base, int t, uint32_t on) {
        const uint32_t pt = base + toff + (t >> 1) * 1280 + (t & 1) * 64;
        a[t][0] = lds32_if(pt + 32, on); a[t][1] = lds32_if(pt + 672, on); a[t][2] = lds32_if(pt, on); a[t][3] = lds32_if(pt + 640, on);
      };
      auto gemm1_done = [&]() {
        pipe_drain(p, bars, leader);
        if (leader) mbar_arrive(bars + B_G1DONE);
        mbar_wait_u(bars + B_EMPTY + (2 - wg) * 8, wg ^ 1);
        if (leader) PROF(4 + 10 * wg);
        if (tid == 128) PROFC(48);
      };
      {
        float acc[72];
        if (kind) {
          float big[96];
          gemm_run<1, LEAD_B>(big, 32, 0, p, sb, PITCH_B, wg, leader);
          if (wg == 1) named_arrive(6, 256);
          gemm1_done();
          if (wg < nconv) mbar_wait_u(bars + B_CFULL + wg * 8, 0);
#pragma unroll
          for (int t = 0; t < 8; t++) load_a(conv_buf(sb, 1, wg), t, 1);
          gelu_store<72, 96>(big, bias0, bias1, sa, 0u, [](int) { return 0u; });
#pragma unroll
          for (int i = 0; i < 72; i++) asm volatile("mov.b32 %0, %1;" : "=f"(acc[i]) : "f"(big[i]));
        } else {
          gemm_run<1, 0>(acc, 32 - LEAD_S - (wg ? 0 : PRE0), 0, p, sb, PITCH_S, wg, leader);
          if (wg == 1) pipe_drain(p, bars, leader);
          mbar_wait_u(bars + B_CFULL + wg * 8, 0);
#pragma unroll
          for (int t = 0; t < 8; t++) load_a(conv_buf(sb, 0, wg), t, 1);
          if (wg == 1) named_bar(8, 256);
          gemm_run<1, 0>(acc, LEAD_S + (wg ? 0 : PRE0), 1, p, sb, PITCH_S, wg, leader);
          named_arrive(8 - 2 * wg, 256);
          gemm1_done();
        }
        gelu_store<0, 72>(acc, bias0, bias1, sa, roles.by_sm >> 1, [&](int t) { return t + GLAG < 9 ? lds32(bars) : 0u; });
        fence_async_smem();
        __syncwarp();
        if (lane == 0) mbar_arrive(bars + B_USTG + wg * 8);
        if (leader) PROF(15 + wg);
      }
      {
#pragma unroll 1
        for (int i = wg; i < nconv; i += 2) {
          const uint32_t base = conv_buf(sb, kind, i & 3), next = conv_buf(sb, kind, (i + 2) & 3);
          const uint64_t dH = mkdesc(base + CH_OFF, 16, 128, 0);
          float y[8][16];
          named_bar(6 + wg, 256);
          wg_fence();
#pragma unroll
          for (int t = 0; t < 16; t++) {
            if (t == 8) wg_fence();
            if (t == CTURN) named_arrive(7 - wg, 256);
#pragma unroll
            for (int cb = t >> 1; cb < 8; cb++) {
              wgmma_rs_n32(y[cb], a[t][0], a[t][1], a[t][2], a[t][3], dH + (32 * cb - 32 * (t >> 1) - 2 * (t & 1) - 1), t);
              const int n = 8 * t - (t >> 1) * ((t - 1) >> 1) - (t >> 1) + cb + 1;
              if (n % CPER == 0 && n / CPER <= 8) load_a(base, 7 + n / CPER, 1);
            }
          }
          wg_commit();
          const bool more = i + 2 < nconv;
          if (more) mbar_wait_u(bars + B_CFULL + ((i + 2) & 3) * 8, (i + 2) >> 2);
          mbar_wait_u(bars + B_SEMPTY + wg * 8, ((i >> 1) & 1) ^ 1);
          wg_wait<0>();
          if (lane == 0) mbar_arrive(bars + B_CEMPTY + (i & 3) * 8);
          if (leader && i == nconv - 1) PROF(45);
          uint32_t P[16], Q[16], R[16], o[8];
#pragma unroll
          for (int j = 0; j < 32; j++) {
            if ((j & 3) == 0) load_a(next, j >> 2, more);
            float v0 = y[j >> 2][4 * (j & 3)], v1 = y[j >> 2][4 * (j & 3) + 1];
            if (j >= 2) { v0 += y[(j - 2) >> 2][4 * ((j - 2) & 3) + 2]; v1 += y[(j - 2) >> 2][4 * ((j - 2) & 3) + 3]; }
            if (j & 1) R[j >> 1] = shfl_ordered(pack_bf16(v0, v1), lane ^ 16);
            else P[j >> 1] = pack_bf16(v0, v1);
          }
#pragma unroll
          for (int m = 0; m < 16; m++) Q[m] = hadd2(P[m], cA ? R[m] : (m ? R[m - 1] : 0u));
#pragma unroll
          for (int m = 0; m < 8; m++) o[m] = shfl_ordered(pB1 ? Q[2 * m] : (pB2 ? (m ? Q[2 * m - 1] : 0u) : Q[2 * m + 1]), srcB);
#pragma unroll
          for (int m = 0; m < 8; m++) sts32(sto + m * 512, hadd2(pB1 ? Q[2 * m + 1] : Q[2 * m], o[m]));
          fence_async_smem();
          __syncwarp();
          if (lane == 0) mbar_arrive(bars + B_SFULL + wg * 8);
          if (leader && i == 5) PROF(53);
        }
        if (wg == (nconv & 1)) named_bar(6 + wg, 256);
      }
    }
    if (kind != 2) {
      const Role ro = get_role(roles);
      const uint32_t pitch = ro.pitch;
      const int s0 = ro.g2_m + wg * 64 + wi * 16 + g;
      const size_t go = (size_t)s0 * D_ + ro.dt * 128 + ro.half * 64 + qd * 8, go8 = (size_t)s0 * D_ + 512 + ro.dt * 16 + ro.half * 8 + qd * 2;
      uint32_t x[2][9], sg[2][9];
      float acc[72];
      p.r = Ring{(uint32_t)(2 + ro.skip), 0};
      mbar_wait_u(bars + B_G2GO + wg * 8, 0);
      gemm_run<0, 0>(acc, XAT + 2 * wg + 1 - ro.skip, 0, p, sb, pitch, wg, leader);
#pragma unroll
      for (int J = 0; J < 4; J++) {
        const uint4 v = ldg128(q + go + (J & 1) * 8 * D_ + (J >> 1) * 32);
        x[J & 1][4 * (J >> 1)] = v.x; x[J & 1][4 * (J >> 1) + 1] = v.y; x[J & 1][4 * (J >> 1) + 2] = v.z; x[J & 1][4 * (J >> 1) + 3] = v.w;
      }
      x[0][8] = ldg32(q + go8); x[1][8] = ldg32(q + go8 + 8 * D_);
      const uint4 st0 = ld_l2(gs->stats + s0), st1 = ld_l2(gs->stats + s0 + 8);
      const uint32_t braw0 = ldg16(b2 + s0), braw1 = ldg16(b2 + s0 + 8);
      gemm_run<0, 0>(acc, ZAT - XAT, 1, p, sb, pitch, wg, leader);
      {
        const int zw = 8 * wi + (g ^ ((((ro.g2_m >> 6) + wg) & 3) << 1));
        const uint32_t za = sb + ST * pitch + wg * 9216 + qd * 256 + (zw & 3) * 4;
        mbar_wait_u(bars + B_ZFULL, 0);
#pragma unroll
        for (int j = 0; j < 9; j++) {
          sg[0][j] = lds32(za + j * 1024 + (((zw >> 2) ^ (2 * qd)) << 4));
          sg[1][j] = lds32(za + j * 1024 + 128 + (((zw >> 2) ^ (2 * qd + 1)) << 4));
        }
      }
      gemm_run<0, 0>(acc, 1, 1, p, sb, pitch, wg, leader);
#pragma unroll
      for (int j = 0; j < 9; j++) {
        const uint32_t z0 = __byte_perm(sg[0][j], sg[1][j], 0x5410), z1 = __byte_perm(sg[0][j], sg[1][j], 0x7632);
        sg[0][j] = hmul2(ln_apply(x[0][j], st0), z0);
        sg[1][j] = hmul2(ln_apply(x[1][j], st1), z1);
        asm volatile("" : "+r"(sg[0][j]), "+r"(sg[1][j]));
      }
      gemm_run<0, SKEW>(acc, 35 - ZAT - LAG - 2 * wg, 1, p, sb, pitch, wg, leader);
      const uint32_t rbuf = sb + (69 % ST) * pitch + warp * 2304;
      const uint32_t rdst = mapa(rbuf, ro.half ^ 1), rbar = mapa(bars + B_RFULL + wg * 8, ro.half ^ 1);
      pipe_drain(p, bars, leader);
      if (leader) PROF(9 + 10 * wg);
      if (tid == 128) PROFC(50);
      float cs[36], ck[36];
      split_acc(acc, cs, ck);
      gemm2_part<0, 0, 4 * LAG>(cs, sb, pitch, wg);
      if (KPRE) gemm2_part<72, 0, KPRE>(ck, sb, pitch, wg);
      const float hb0 = fmaf(bf_lo(braw0), 0.5f, __uint_as_float(st0.w)), hb1 = fmaf(bf_lo(braw1), 0.5f, __uint_as_float(st1.w));
      mbar_wait(bars + B_GO, 0);
      wg_wait<KPRE ? 1 : 0>();
      if (leader) PROF(54 + wg);
#pragma unroll
      for (int i = 0; i < 5; i++) {
        const float* c = &cs[8 * i];
        const uint32_t v0 = pack_bf16(fmaf(c[0], 0.25f, hb0), fmaf(c[1], 0.25f, hb0)), v1 = pack_bf16(fmaf(c[2], 0.25f, hb1), fmaf(c[3], 0.25f, hb1));
        if (i < 4) st_async4(rdst + i * 512 + lane * 16, v0, v1, pack_bf16(fmaf(c[4], 0.25f, hb0), fmaf(c[5], 0.25f, hb0)), pack_bf16(fmaf(c[6], 0.25f, hb1), fmaf(c[7], 0.25f, hb1)), rbar);
        else st_async2(rdst + 2048 + lane * 8, v0, v1, rbar);
      }
      if (wg == 1) named_bar(7, 256);
      gemm2_part<72, KPRE, 4 * LAG>(ck, sb, pitch, wg);
      uint32_t rp[18];
      mbar_wait(bars + B_RFULL + wg * 8, 0);
#pragma unroll
      for (int m = 0; m < 4; m++) {
        const uint4 v = lds128(rbuf + m * 512 + lane * 16);
        rp[4 * m] = v.x; rp[4 * m + 1] = v.y; rp[4 * m + 2] = v.z; rp[4 * m + 3] = v.w;
      }
      { const uint2 v = lds64(rbuf + 2048 + lane * 8); rp[16] = v.x; rp[17] = v.y; }
      __nv_bfloat16* o = out + go;
      wg_wait<0>();
      if (leader) PROF(10 + 10 * wg);
      float h[2][4], t[2][4], half = 0.25f;
#pragma unroll
      for (int j = 0; j <= 9; j++) {
        if (j < 9) {
          const uint32_t ra = rp[2 * j], rb = rp[2 * j + 1];
          if (j >= 2) half = fmaf(t[j & 1][3], 0.f, 0.25f);
          h[j & 1][0] = fmaf(ck[4 * j], half, bf_lo(ra)); h[j & 1][1] = fmaf(ck[4 * j + 1], half, bf_hi(ra));
          h[j & 1][2] = fmaf(ck[4 * j + 2], half, bf_lo(rb)); h[j & 1][3] = fmaf(ck[4 * j + 3], half, bf_hi(rb));
#pragma unroll
          for (int u = 0; u < 4; u++) t[j & 1][u] = tanh_ordered(h[j & 1][u]);
        }
        if (j > 0) {
          const int k = j - 1;
          const float* hh = h[k & 1];
          const float* tt = t[k & 1];
          x[0][k] = hfma2(sg[0][k], pack_bf16(fmaf(hh[0], tt[0], hh[0]), fmaf(hh[1], tt[1], hh[1])), x[0][k]);
          x[1][k] = hfma2(sg[1][k], pack_bf16(fmaf(hh[2], tt[2], hh[2]), fmaf(hh[3], tt[3], hh[3])), x[1][k]);
          if ((k & 3) == 3) {
            *(uint4*)(o + (k >> 2) * 32) = make_uint4(x[0][k - 3], x[0][k - 2], x[0][k - 1], x[0][k]);
            *(uint4*)(o + 8 * D_ + (k >> 2) * 32) = make_uint4(x[1][k - 3], x[1][k - 2], x[1][k - 1], x[1][k]);
          }
        }
      }
      *(uint32_t*)(out + go8) = x[0][8];
      *(uint32_t*)(out + go8 + 8 * D_) = x[1][8];
      if (leader) PROF(11 + 7 * wg);
      if (tid == 128) PROFC(51);
    }
  }
}

typedef CUresult (*EncodeFn)(CUtensorMap*, CUtensorMapDataType, cuuint32_t, void*, const cuuint64_t*, const cuuint64_t*, const cuuint32_t*,
                             const cuuint32_t*, CUtensorMapInterleave, CUtensorMapSwizzle, CUtensorMapL2promotion, CUtensorMapFloatOOBfill);

uint32_t role_of_pair(int t) {
  int grp, i;
  if (t < 32) { const int j = t & 7; i = t >> 3; grp = j < 6 ? 1 + j : 12 + 2 * (j - 6); }
  else if (t < 60) { const int j = (t - 32) % 7; i = (t - 32) / 7; grp = j < 5 ? 7 + j : 13 + 2 * (j - 5); }
  else if (t < 62) return 2u | (uint32_t)(t - 60) << 2 | (uint32_t)(14 + 3 * (t - 60)) << 8 | 2u << 16;
  else { grp = 0; i = t - 62; }
  if (grp < 12) return (uint32_t)(i << 2 | grp << 4 | grp << 8 | i << 16);
  const int u = (grp & 1) * 4 + i;
  return (uint32_t)(1 | i << 2 | grp << 4 | (12 + 3 * ((grp - 12) >> 1) + u / 3) << 8 | (u % 3) << 16);
}

}

extern "C" void kernel_launch(void* const* d_in, const int* in_sizes, int n_in, void* d_out, int out_size) {
  (void)in_sizes; (void)n_in; (void)out_size;
  EncodeFn enc = nullptr;
  cudaDriverEntryPointQueryResult qr;
  cudaGetDriverEntryPoint("cuTensorMapEncodeTiled", (void**)&enc, cudaEnableDefault, &qr);
  Scratch* gs = nullptr;
  cudaGetSymbolAddress((void**)&gs, g_scratch);
  void *zp = gs->z, *hp = gs->h, *kvp = gs->kv + 128;
  CUtensorMap tmW1, tmW2, tmZ, tmH, tmK, tmV, tmKV, tmKL;
  for (int w = 0; w < 2; w++) {
    cuuint64_t gd[2] = {D_, S_};
    cuuint64_t st[1] = {D_ * 2};
    cuuint32_t bx[2] = {64, w ? 33u : 36u};
    cuuint32_t es[2] = {1, 1};
    enc(w ? &tmV : &tmK, CU_TENSOR_MAP_DATA_TYPE_BFLOAT16, 2, d_in[1 + w], gd, st, bx, es, CU_TENSOR_MAP_INTERLEAVE_NONE, CU_TENSOR_MAP_SWIZZLE_NONE,
        CU_TENSOR_MAP_L2_PROMOTION_L2_128B, CU_TENSOR_MAP_FLOAT_OOB_FILL_NONE);
  }
  {
    cuuint64_t gd[4] = {16, D_ / 2, 2, 128};
    cuuint64_t st[3] = {2 * KVT, KVT, 64};
    cuuint32_t bx[4] = {20, 32, 2, 1};
    cuuint32_t es[4] = {1, 1, 1, 1};
    enc(&tmKV, CU_TENSOR_MAP_DATA_TYPE_UINT32, 4, kvp, gd, st, bx, es, CU_TENSOR_MAP_INTERLEAVE_NONE, CU_TENSOR_MAP_SWIZZLE_NONE,
        CU_TENSOR_MAP_L2_PROMOTION_NONE, CU_TENSOR_MAP_FLOAT_OOB_FILL_NONE);
  }
  {
    cuuint64_t gd[3] = {40, 64, D_};
    cuuint64_t st[2] = {128, KVT};
    cuuint32_t bx[3] = {40, 16, 1};
    cuuint32_t es[3] = {1, 1, 1};
    enc(&tmKL, CU_TENSOR_MAP_DATA_TYPE_UINT32, 3, gs->kv + 96, gd, st, bx, es, CU_TENSOR_MAP_INTERLEAVE_NONE, CU_TENSOR_MAP_SWIZZLE_NONE,
        CU_TENSOR_MAP_L2_PROMOTION_NONE, CU_TENSOR_MAP_FLOAT_OOB_FILL_NONE);
  }
  {
    cuuint64_t gd[3] = {64, 32 * 72, 8};
    cuuint64_t st[2] = {1024, 128};
    cuuint32_t bx[3] = {64, 72, 1};
    cuuint32_t es[3] = {1, 1, 1};
    enc(&tmH, CU_TENSOR_MAP_DATA_TYPE_BFLOAT16, 3, hp, gd, st, bx, es, CU_TENSOR_MAP_INTERLEAVE_NONE, CU_TENSOR_MAP_SWIZZLE_128B,
        CU_TENSOR_MAP_L2_PROMOTION_NONE, CU_TENSOR_MAP_FLOAT_OOB_FILL_NONE);
  }
  for (int w = 0; w < 2; w++) {
    const cuuint64_t M = w ? S_ : F_, K = w ? F_ : S_;
    cuuint64_t gd[3] = {64, K, M / 64};
    cuuint64_t st[2] = {M * 2, 128};
    cuuint32_t bx[3] = {64, 64, 2};
    cuuint32_t es[3] = {1, 1, 1};
    enc(w ? &tmW2 : &tmW1, CU_TENSOR_MAP_DATA_TYPE_BFLOAT16, 3, d_in[w ? 9 : 7], gd, st, bx, es, CU_TENSOR_MAP_INTERLEAVE_NONE,
        CU_TENSOR_MAP_SWIZZLE_128B, CU_TENSOR_MAP_L2_PROMOTION_L2_256B, CU_TENSOR_MAP_FLOAT_OOB_FILL_NONE);
  }
  {
    cuuint64_t gd[2] = {S_, D_};
    cuuint64_t st[1] = {S_ * 2};
    cuuint32_t bx[2] = {64, 72};
    cuuint32_t es[2] = {1, 1};
    enc(&tmZ, CU_TENSOR_MAP_DATA_TYPE_BFLOAT16, 2, zp, gd, st, bx, es, CU_TENSOR_MAP_INTERLEAVE_NONE, CU_TENSOR_MAP_SWIZZLE_128B,
        CU_TENSOR_MAP_L2_PROMOTION_L2_256B, CU_TENSOR_MAP_FLOAT_OOB_FILL_NONE);
  }
  RoleMap roles;
  int dev = 0, sms = 0;
  cudaGetDevice(&dev);
  cudaDeviceGetAttribute(&sms, cudaDevAttrMultiProcessorCount, dev);
  roles.by_sm = sms == NCTA;
  for (int k = 0; k < NCTA / 2; k++) roles.role[k] = role_of_pair(k);
  cudaFuncSetAttribute(fused_kernel, cudaFuncAttributeMaxDynamicSharedMemorySize, SMEM_BYTES);
  fused_kernel<<<NCTA, 384, SMEM_BYTES>>>((const __nv_bfloat16*)d_in[0], gs, (const __nv_bfloat16*)d_in[8], (const __nv_bfloat16*)d_in[3],
                                          (const __nv_bfloat16*)d_in[4], (const __nv_bfloat16*)d_in[5], tmW1, tmW2, tmZ, tmH, tmK, tmV, tmKV, tmKL,
                                          roles, (const __nv_bfloat16*)d_in[10], (__nv_bfloat16*)d_out);
}
```

```cpp
#include <cuda_runtime.h>
#include <cuda_bf16.h>
#include <cuda.h>
#include <stdint.h>

namespace {

constexpr int S_ = 2048, D_ = 576, F_ = 4608;
constexpr int NCTA = 132, NG2 = 128;
constexpr int ST = 5, ASZ = 16384, PITCH_S = ASZ + 144 * 128, PITCH_B = ASZ + 192 * 128;
constexpr int CBUF = 14464, CH_OFF = 128, CT_OFF = 4224, KVT = 8192;
constexpr int KVIN = (36 + 33) * 128, KVW = 2 * CBUF;
constexpr int BAR_OFF = ST * PITCH_S + 2 * KVW;
constexpr int SMEM_BYTES = BAR_OFF + 512;
constexpr int LEAD_S = 4, LEAD_B = 3;
constexpr int PRE0 = 1;
constexpr int GLAG = 4;
constexpr int CTURN = 14, CPER = 4;
constexpr int XAT = 12, ZAT = 25;
constexpr int SKEW = 1;
constexpr int LAG = 4;
constexpr int KPRE = 2, TURN = 4;
constexpr int LNROT = 120;
constexpr int QLATE = 40, QDELAY = 400, QRAMP = 5;
constexpr int W9 = 1200;
constexpr int A0 = 1200, AD = 300, AN = 2, AL = 1500;
constexpr int H0 = 3100, HD = 400, HW = 4200;
constexpr int HS2 = 8, LK1 = 7, LK2 = 14, KVGO = 6, KVGO1 = 10, CVGO = 31;
constexpr int BLK_NS = 336, GDELAY = 1280, GBIG = 960, GDELAY1 = 128, ZRAMP = 30;
constexpr uint32_t SPIN_LIMIT = 1u << 22;

constexpr int FL_H = 0, FL_U = 3, FL_KV = 9, FL_Z = 12, FL_GATE = 13, FL_DONE = 14, FL_N = 15;
struct Scratch {
  uint32_t flags[64 * 32];
  uint4 stats[S_];
  uint8_t h[32 * 72 * 1024];
  uint8_t u[72 * D_ * 128];
  uint8_t kv[D_ * KVT];
  __nv_bfloat16 z[D_ * S_];
};
__device__ __align__(1024) Scratch g_scratch;
extern __shared__ __align__(1024) uint8_t smem_raw[];
struct RoleMap { uint32_t role[NCTA / 2]; uint32_t by_sm; };

template<int TB> __device__ __forceinline__ void wgmma_ss(float (&d)[96], uint32_t da, uint32_t db, int sd) {
  asm volatile("{\n.reg .pred p;\n.reg .b64 a, b;\nsetp.ne.b32 p, %98, 0;\nmov.b64 a, {%96, %100};\nmov.b64 b, {%97, %101};\n"
    "wgmma.mma_async.sync.aligned.m64n192k16.f32.bf16.bf16 {%0, %1, %2, %3, %4, %5, %6, %7, %8, %9, %10, %11, %12, %13, %14, %15, %16, %17, %18, %19, %20, %21, %22, %23, %24, %25, %26, %27, %28, %29, %30, %31, %32, %33, %34, %35, %36, %37, %38, %39, %40, %41, %42, %43, %44, %45, %46, %47, %48, %49, %50, %51, %52, %53, %54, %55, %56, %57, %58, %59, %60, %61, %62, %63, %64, %65, %66, %67, %68, %69, %70, %71, %72, %73, %74, %75, %76, %77, %78, %79, %80, %81, %82, %83, %84, %85, %86, %87, %88, %89, %90, %91, %92, %93, %94, %95}, a, b, p, 1, 1, 1, %99;\n}\n"
    : "+f"(d[0]), "+f"(d[1]), "+f"(d[2]), "+f"(d[3]), "+f"(d[4]), "+f"(d[5]), "+f"(d[6]), "+f"(d[7]), "+f"(d[8]), "+f"(d[9]), "+f"(d[10]), "+f"(d[11]), "+f"(d[12]), "+f"(d[13]), "+f"(d[14]), "+f"(d[15]), "+f"(d[16]), "+f"(d[17]), "+f"(d[18]), "+f"(d[19]), "+f"(d[20]), "+f"(d[21]), "+f"(d[22]), "+f"(d[23]), "+f"(d[24]), "+f"(d[25]), "+f"(d[26]), "+f"(d[27]), "+f"(d[28]), "+f"(d[29]), "+f"(d[30]), "+f"(d[31]), "+f"(d[32]), "+f"(d[33]), "+f"(d[34]), "+f"(d[35]), "+f"(d[36]), "+f"(d[37]), "+f"(d[38]), "+f"(d[39]), "+f"(d[40]), "+f"(d[41]), "+f"(d[42]), "+f"(d[43]), "+f"(d[44]), "+f"(d[45]), "+f"(d[46]), "+f"(d[47]), "+f"(d[48]), "+f"(d[49]), "+f"(d[50]), "+f"(d[51]), "+f"(d[52]), "+f"(d[53]), "+f"(d[54]), "+f"(d[55]), "+f"(d[56]), "+f"(d[57]), "+f"(d[58]), "+f"(d[59]), "+f"(d[60]), "+f"(d[61]), "+f"(d[62]), "+f"(d[63]), "+f"(d[64]), "+f"(d[65]), "+f"(d[66]), "+f"(d[67]), "+f"(d[68]), "+f"(d[69]), "+f"(d[70]), "+f"(d[71]), "+f"(d[72]), "+f"(d[73]), "+f"(d[74]), "+f"(d[75]), "+f"(d[76]), "+f"(d[77]), "+f"(d[78]), "+f"(d[79]), "+f"(d[80]), "+f"(d[81]), "+f"(d[82]), "+f"(d[83]), "+f"(d[84]), "+f"(d[85]), "+f"(d[86]), "+f"(d[87]), "+f"(d[88]), "+f"(d[89]), "+f"(d[90]), "+f"(d[91]), "+f"(d[92]), "+f"(d[93]), "+f"(d[94]), "+f"(d[95])
    : "r"(da), "r"(db), "r"(sd), "n"(TB), "r"(0x40000040u), "r"(TB ? 0x40u : 0x40000040u));
}
template<int TB> __device__ __forceinline__ void wgmma_ss(float (&d)[72], uint32_t da, uint32_t db, int sd) {
  asm volatile("{\n.reg .pred p;\n.reg .b64 a, b;\nsetp.ne.b32 p, %74, 0;\nmov.b64 a, {%72, %76};\nmov.b64 b, {%73, %77};\n"
    "wgmma.mma_async.sync.aligned.m64n144k16.f32.bf16.bf16 {%0, %1, %2, %3, %4, %5, %6, %7, %8, %9, %10, %11, %12, %13, %14, %15, %16, %17, %18, %19, %20, %21, %22, %23, %24, %25, %26, %27, %28, %29, %30, %31, %32, %33, %34, %35, %36, %37, %38, %39, %40, %41, %42, %43, %44, %45, %46, %47, %48, %49, %50, %51, %52, %53, %54, %55, %56, %57, %58, %59, %60, %61, %62, %63, %64, %65, %66, %67, %68, %69, %70, %71}, a, b, p, 1, 1, 1, %75;\n}\n"
    : "+f"(d[0]), "+f"(d[1]), "+f"(d[2]), "+f"(d[3]), "+f"(d[4]), "+f"(d[5]), "+f"(d[6]), "+f"(d[7]), "+f"(d[8]), "+f"(d[9]), "+f"(d[10]), "+f"(d[11]), "+f"(d[12]), "+f"(d[13]), "+f"(d[14]), "+f"(d[15]), "+f"(d[16]), "+f"(d[17]), "+f"(d[18]), "+f"(d[19]), "+f"(d[20]), "+f"(d[21]), "+f"(d[22]), "+f"(d[23]), "+f"(d[24]), "+f"(d[25]), "+f"(d[26]), "+f"(d[27]), "+f"(d[28]), "+f"(d[29]), "+f"(d[30]), "+f"(d[31]), "+f"(d[32]), "+f"(d[33]), "+f"(d[34]), "+f"(d[35]), "+f"(d[36]), "+f"(d[37]), "+f"(d[38]), "+f"(d[39]), "+f"(d[40]), "+f"(d[41]), "+f"(d[42]), "+f"(d[43]), "+f"(d[44]), "+f"(d[45]), "+f"(d[46]), "+f"(d[47]), "+f"(d[48]), "+f"(d[49]), "+f"(d[50]), "+f"(d[51]), "+f"(d[52]), "+f"(d[53]), "+f"(d[54]), "+f"(d[55]), "+f"(d[56]), "+f"(d[57]), "+f"(d[58]), "+f"(d[59]), "+f"(d[60]), "+f"(d[61]), "+f"(d[62]), "+f"(d[63]), "+f"(d[64]), "+f"(d[65]), "+f"(d[66]), "+f"(d[67]), "+f"(d[68]), "+f"(d[69]), "+f"(d[70]), "+f"(d[71])
    : "r"(da), "r"(db), "r"(sd), "n"(TB), "r"(0x40000040u), "r"(TB ? 0x40u : 0x40000040u));
}
template<int TB> __device__ __forceinline__ void wgmma_ss(float (&d)[36], uint32_t da, uint32_t db, int sd) {
  asm volatile("{\n.reg .pred p;\n.reg .b64 a, b;\nsetp.ne.b32 p, %38, 0;\nmov.b64 a, {%36, %40};\nmov.b64 b, {%37, %41};\n"
    "wgmma.mma_async.sync.aligned.m64n72k16.f32.bf16.bf16 {%0, %1, %2, %3, %4, %5, %6, %7, %8, %9, %10, %11, %12, %13, %14, %15, %16, %17, %18, %19, %20, %21, %22, %23, %24, %25, %26, %27, %28, %29, %30, %31, %32, %33, %34, %35}, a, b, p, 1, 1, 1, %39;\n}\n"
    : "+f"(d[0]), "+f"(d[1]), "+f"(d[2]), "+f"(d[3]), "+f"(d[4]), "+f"(d[5]), "+f"(d[6]), "+f"(d[7]), "+f"(d[8]), "+f"(d[9]), "+f"(d[10]), "+f"(d[11]), "+f"(d[12]), "+f"(d[13]), "+f"(d[14]), "+f"(d[15]), "+f"(d[16]), "+f"(d[17]), "+f"(d[18]), "+f"(d[19]), "+f"(d[20]), "+f"(d[21]), "+f"(d[22]), "+f"(d[23]), "+f"(d[24]), "+f"(d[25]), "+f"(d[26]), "+f"(d[27]), "+f"(d[28]), "+f"(d[29]), "+f"(d[30]), "+f"(d[31]), "+f"(d[32]), "+f"(d[33]), "+f"(d[34]), "+f"(d[35])
    : "r"(da), "r"(db), "r"(sd), "n"(TB), "r"(0x40000040u), "r"(TB ? 0x40u : 0x40000040u));
}
__device__ __forceinline__ void wgmma_rs_n32(float (&d)[16], uint32_t a0, uint32_t a1, uint32_t a2, uint32_t a3, uint64_t db, int sd) {
  asm volatile("{\n.reg .pred p;\nsetp.ne.b32 p, %21, 0;\n"
    "wgmma.mma_async.sync.aligned.m64n32k16.f32.bf16.bf16 {%0, %1, %2, %3, %4, %5, %6, %7, %8, %9, %10, %11, %12, %13, %14, %15}, {%16, %17, %18, %19}, %20, p, 1, 1, 0;\n}\n"
    : "+f"(d[0]), "+f"(d[1]), "+f"(d[2]), "+f"(d[3]), "+f"(d[4]), "+f"(d[5]), "+f"(d[6]), "+f"(d[7]), "+f"(d[8]), "+f"(d[9]), "+f"(d[10]), "+f"(d[11]), "+f"(d[12]), "+f"(d[13]), "+f"(d[14]), "+f"(d[15])
    : "r"(a0), "r"(a1), "r"(a2), "r"(a3), "l"(db), "r"(sd));
}

__device__ __forceinline__ void wg_fence() { asm volatile("wgmma.fence.sync.aligned;" ::: "memory"); }
__device__ __forceinline__ void wg_commit() { asm volatile("wgmma.commit_group.sync.aligned;" ::: "memory"); }
template <int n> __device__ __forceinline__ void wg_wait() { asm volatile("wgmma.wait_group.sync.aligned %0;" ::"n"(n) : "memory"); }
__device__ __forceinline__ uint64_t mkdesc(uint32_t addr, uint32_t lbo, uint32_t sbo, uint32_t sw) {
  return (uint64_t)((addr & 0x3FFFF) >> 4) | ((uint64_t)(lbo >> 4) << 16) | ((uint64_t)(sbo >> 4) << 32) | ((uint64_t)sw << 62);
}
__device__ __forceinline__ void mbar_init(uint32_t a, int c) { asm volatile("mbarrier.init.shared::cta.b64 [%0], %1;" ::"r"(a), "r"(c)); }
__device__ __forceinline__ void mbar_expect(uint32_t a, uint32_t b) { asm volatile("mbarrier.arrive.expect_tx.shared::cta.b64 _, [%0], %1;" ::"r"(a), "r"(b) : "memory"); }
__device__ __forceinline__ void mbar_arrive(uint32_t a) { asm volatile("mbarrier.arrive.shared::cta.b64 _, [%0];" ::"r"(a) : "memory"); }
__device__ __forceinline__ void mbar_arrive_cluster(uint32_t raddr) { asm volatile("mbarrier.arrive.shared::cluster.b64 _, [%0];" ::"r"(raddr) : "memory"); }
__device__ __forceinline__ uint32_t mapa(uint32_t a, uint32_t cta) { uint32_t r; asm("mapa.shared::cluster.u32 %0, %1, %2;" : "=r"(r) : "r"(a), "r"(cta)); return r; }
__device__ __forceinline__ void mbar_wait(uint32_t a, uint32_t ph) {
  asm volatile(
      "{\n.reg .pred p;\n.reg .u32 c;\nmov.u32 c, 0;\n"
      "WAIT_LOOP:\nmbarrier.try_wait.parity.shared::cta.b64 p, [%0], %1;\n@p bra WAIT_DONE;\n"
      "add.u32 c, c, 1;\nsetp.lt.u32 p, c, %2;\n@p bra WAIT_LOOP;\ntrap;\nWAIT_DONE:\n}" ::"r"(a), "r"(ph), "n"(SPIN_LIMIT) : "memory");
}
__device__ __forceinline__ void mbar_wait_u(uint32_t a, uint32_t ph) {
  asm volatile("{\n.reg .pred p;\nWAIT_LOOP:\nmbarrier.try_wait.parity.shared::cta.b64 p, [%0], %1;\n@!p bra WAIT_LOOP;\n}" ::"r"(a), "r"(ph) : "memory");
}
__device__ __forceinline__ uint32_t desc_lo(uint32_t addr, uint32_t lbo) { return ((addr & 0x3FFFF) >> 4) | ((lbo >> 4) << 16); }
__device__ __forceinline__ void tma2d(uint32_t dst, const CUtensorMap* m, int c0, int c1, uint32_t bar) {
  asm volatile("cp.async.bulk.tensor.2d.shared::cluster.global.mbarrier::complete_tx::bytes [%0], [%1, {%3, %4}], [%2];" ::"r"(dst), "l"(m), "r"(bar), "r"(c0), "r"(c1) : "memory");
}
__device__ __forceinline__ void bulk_g2s(uint32_t dst, const void* src, uint32_t sz, uint32_t bar) {
  asm volatile("cp.async.bulk.shared::cluster.global.mbarrier::complete_tx::bytes [%0], [%1], %2, [%3];" ::"r"(dst), "l"(src), "r"(sz), "r"(bar) : "memory");
}
__device__ __forceinline__ void bulk_s2g(void* dst, uint32_t src, uint32_t sz) {
  asm volatile("cp.async.bulk.global.shared::cta.bulk_group [%0], [%1], %2;" ::"l"(dst), "r"(src), "r"(sz) : "memory");
}
__device__ __forceinline__ uint64_t stream_policy() {
  uint64_t p;
  asm volatile("createpolicy.fractional.L2::evict_first.b64 %0, 1.0;" : "=l"(p));
  return p;
}
__device__ __forceinline__ void tma_weights(uint32_t dst, const CUtensorMap* m, int k0, int mchunk, uint32_t bar, uint64_t pol) {
  asm volatile("cp.async.bulk.tensor.3d.shared::cluster.global.mbarrier::complete_tx::bytes.L2::cache_hint [%0], [%1, {%6, %3, %4}], [%2], %5;"
               ::"r"(dst), "l"(m), "r"(bar), "r"(k0), "r"(mchunk), "l"(pol), "r"(0) : "memory");
}
__device__ __forceinline__ void tma_weights_prefetch(const CUtensorMap* m, int k0, int mchunk, uint64_t pol) {
  asm volatile("cp.async.bulk.prefetch.tensor.3d.L2.global.L2::cache_hint [%0, {%4, %1, %2}], %3;" ::"l"(m), "r"(k0), "r"(mchunk), "l"(pol), "r"(0) : "memory");
}
__device__ __forceinline__ bool elect_one() {
  uint32_t p;
  asm volatile("{\n.reg .pred P;\nelect.sync _|P, 0xffffffff;\nselp.u32 %0, 1, 0, P;\n}" : "=r"(p));
  return p;
}
__device__ __forceinline__ void bulk_g2s_stream(uint32_t dst, const void* src, uint32_t sz, uint32_t bar, uint64_t pol) {
  asm volatile("cp.async.bulk.shared::cluster.global.mbarrier::complete_tx::bytes.L2::cache_hint [%0], [%1], %2, [%3], %4;"
               ::"r"(dst), "l"(src), "r"(sz), "r"(bar), "l"(pol) : "memory");
}
__device__ __forceinline__ void tma3d_store(const CUtensorMap* m, int c1, int c2, uint32_t src) {
  asm volatile("cp.async.bulk.tensor.3d.global.shared::cta.bulk_group [%0, {%4, %2, %3}], [%1];" ::"l"(m), "r"(src), "r"(c1), "r"(c2), "r"(0) : "memory");
}
__device__ __forceinline__ void tma2d_stream(uint32_t dst, const CUtensorMap* m, int c0, int c1, uint32_t bar, uint64_t pol) {
  asm volatile("cp.async.bulk.tensor.2d.shared::cluster.global.mbarrier::complete_tx::bytes.L2::cache_hint [%0], [%1, {%3, %4}], [%2], %5;"
               ::"r"(dst), "l"(m), "r"(bar), "r"(c0), "r"(c1), "l"(pol) : "memory");
}
__device__ __forceinline__ void tma4d_store(const CUtensorMap* m, int c1, int c2, int c3, uint32_t src) {
  asm volatile("cp.async.bulk.tensor.4d.global.shared::cta.bulk_group [%0, {%5, %2, %3, %4}], [%1];" ::"l"(m), "r"(src), "r"(c1), "r"(c2), "r"(c3), "r"(0) : "memory");
}
__device__ __forceinline__ void bulk_commit() { asm volatile("cp.async.bulk.commit_group;" ::: "memory"); }
__device__ __forceinline__ void bulk_wait_all() { asm volatile("cp.async.bulk.wait_group 0;" ::: "memory"); }
__device__ __forceinline__ void fence_async_smem() { asm volatile("fence.proxy.async.shared::cta;" ::: "memory"); }
__device__ __forceinline__ void fence_async_global() { asm volatile("fence.proxy.async.global;" ::: "memory"); }
__device__ __forceinline__ void named_bar(int id, int n) { asm volatile("bar.sync %0, %1;" ::"r"(id), "r"(n) : "memory"); }
__device__ __forceinline__ void named_arrive(int id, int n) { asm volatile("bar.arrive %0, %1;" ::"r"(id), "r"(n) : "memory"); }
__device__ __forceinline__ void flag_add(uint32_t* f, int i, uint32_t v) { asm volatile("red.relaxed.gpu.global.add.u32 [%0], %1;" ::"l"(f + i * 32), "r"(v) : "memory"); }
__device__ __forceinline__ uint32_t flag_ld(uint32_t* f, int i) { uint32_t v; asm volatile("ld.relaxed.gpu.global.u32 %0, [%1];" : "=r"(v) : "l"(f + i * 32) : "memory"); return v; }
__device__ __forceinline__ void prefetch_map(const CUtensorMap* m) { asm volatile("prefetch.tensormap [%0];" ::"l"(m) : "memory"); }
__device__ __forceinline__ void stsm4_t(uint32_t a, uint32_t r0, uint32_t r1, uint32_t r2, uint32_t r3) {
  asm volatile("stmatrix.sync.aligned.m8n8.x4.trans.shared.b16 [%0], {%1, %2, %3, %4};" ::"r"(a), "r"(r0), "r"(r1), "r"(r2), "r"(r3) : "memory");
}
__device__ __forceinline__ uint32_t lds32(uint32_t a) { uint32_t v; asm volatile("ld.shared.u32 %0, [%1];" : "=r"(v) : "r"(a) : "memory"); return v; }
__device__ __forceinline__ void sts32(uint32_t a, uint32_t v) { asm volatile("st.shared.u32 [%0], %1;" ::"r"(a), "r"(v) : "memory"); }
__device__ __forceinline__ uint4 ld_l2(const uint4* p) { uint4 v; asm volatile("ld.relaxed.gpu.global.v4.u32 {%0, %1, %2, %3}, [%4];" : "=r"(v.x), "=r"(v.y), "=r"(v.z), "=r"(v.w) : "l"(p) : "memory"); return v; }
__device__ __forceinline__ void sts128(uint32_t a, uint32_t x, uint32_t y, uint32_t z, uint32_t w) { asm volatile("st.shared.v4.u32 [%0], {%1, %2, %3, %4};" ::"r"(a), "r"(x), "r"(y), "r"(z), "r"(w) : "memory"); }
__device__ __forceinline__ uint4 lds128(uint32_t a) { uint4 v; asm volatile("ld.shared.v4.u32 {%0, %1, %2, %3}, [%4];" : "=r"(v.x), "=r"(v.y), "=r"(v.z), "=r"(v.w) : "r"(a) : "memory"); return v; }
__device__ __forceinline__ void st_async4(uint32_t raddr, uint32_t a, uint32_t b, uint32_t c, uint32_t d, uint32_t rbar) {
  asm volatile("st.async.weak.shared::cluster.mbarrier::complete_tx::bytes.v4.b32 [%0], {%1, %2, %3, %4}, [%5];" ::"r"(raddr), "r"(a), "r"(b), "r"(c), "r"(d), "r"(rbar) : "memory");
}
__device__ __forceinline__ uint32_t pack_bf16(float lo, float hi) { uint32_t r; asm("cvt.rn.bf16x2.f32 %0, %1, %2;" : "=r"(r) : "f"(hi), "f"(lo)); return r; }
__device__ __forceinline__ float bf_lo(uint32_t v) { return __uint_as_float(v << 16); }
__device__ __forceinline__ float bf_hi(uint32_t v) { return __uint_as_float(v & 0xffff0000u); }
__device__ __forceinline__ float bf_round(float x) { return bf_lo(pack_bf16(x, 0.f)); }
__device__ __forceinline__ uint32_t hmul2(uint32_t a, uint32_t b) { uint32_t r; asm("mul.rn.bf16x2 %0, %1, %2;" : "=r"(r) : "r"(a), "r"(b)); return r; }
__device__ __forceinline__ uint32_t hsub2(uint32_t a, uint32_t b) { uint32_t r; asm("sub.rn.bf16x2 %0, %1, %2;" : "=r"(r) : "r"(a), "r"(b)); return r; }
__device__ __forceinline__ uint32_t hfma2(uint32_t a, uint32_t b, uint32_t c) { uint32_t r; asm("fma.rn.bf16x2 %0, %1, %2, %3;" : "=r"(r) : "r"(a), "r"(b), "r"(c)); return r; }
__device__ __forceinline__ uint4 ldg128(const void* p) { uint4 v; asm volatile("ld.global.nc.v4.u32 {%0, %1, %2, %3}, [%4];" : "=r"(v.x), "=r"(v.y), "=r"(v.z), "=r"(v.w) : "l"(p)); return v; }
__device__ __forceinline__ uint32_t ldg16(const void* p) { uint32_t v; asm volatile("ld.global.nc.u16 %0, [%1];" : "=r"(v) : "l"(p)); return v; }
__device__ __forceinline__ float tanh_ordered(float x) { float y; asm volatile("tanh.approx.f32 %0, %1;" : "=f"(y) : "f"(x)); return y; }
__device__ __forceinline__ uint32_t tanh2_ordered(uint32_t x) { uint32_t y; asm volatile("tanh.approx.bf16x2 %0, %1;" : "=r"(y) : "r"(x)); return y; }
__device__ __forceinline__ void mma16816(float (&d)[4], uint32_t a0, uint32_t a1, uint32_t a2, uint32_t a3, uint32_t b0, uint32_t b1) {
  asm("mma.sync.aligned.m16n8k16.row.col.f32.bf16.bf16.f32 {%0, %1, %2, %3}, {%4, %5, %6, %7}, {%8, %9}, {%0, %1, %2, %3};"
      : "+f"(d[0]), "+f"(d[1]), "+f"(d[2]), "+f"(d[3]) : "r"(a0), "r"(a1), "r"(a2), "r"(a3), "r"(b0), "r"(b1));
}
__device__ __forceinline__ uint32_t hadd2(uint32_t a, uint32_t b) { uint32_t r; asm("add.rn.bf16x2 %0, %1, %2;" : "=r"(r) : "r"(a), "r"(b)); return r; }
__device__ __forceinline__ uint32_t ldg32(const void* p) { uint32_t v; asm volatile("ld.global.nc.L1::no_allocate.u32 %0, [%1];" : "=r"(v) : "l"(p)); return v; }
__device__ __forceinline__ uint2 lds64(uint32_t a) { uint2 v; asm volatile("ld.shared.v2.u32 {%0, %1}, [%2];" : "=r"(v.x), "=r"(v.y) : "r"(a) : "memory"); return v; }
__device__ __forceinline__ uint32_t lds32_if(uint32_t a, uint32_t on) {
  uint32_t v;
  asm volatile("{\n.reg .pred p;\nsetp.ne.u32 p, %2, 0;\n@p ld.shared.u32 %0, [%1];\n}" : "=r"(v) : "r"(a), "r"(on) : "memory");
  return v;
}
__device__ __forceinline__ uint32_t clock_now() { uint32_t t; asm volatile("mov.u32 %0, %%clock;" : "=r"(t)); return t; }
__device__ __forceinline__ uint32_t time_now() { uint32_t t; asm volatile("mov.u32 %0, %%globaltimer_lo;" : "=r"(t)); return t; }
__device__ __forceinline__ void spin_until(uint32_t t0, uint32_t n) { while (clock_now() - t0 < n) {} }
__device__ __forceinline__ uint2 ldg64_if(const void* p, uint32_t on) {
  uint2 v;
  asm volatile("{\n.reg .pred p;\nsetp.ne.u32 p, %3, 0;\n@p ld.global.nc.v2.u32 {%0, %1}, [%2];\n}" : "=r"(v.x), "=r"(v.y) : "l"(p), "r"(on));
  return v;
}
template <class T> __device__ __forceinline__ T pin(T v) { asm volatile("" : "+r"(v)); return v; }
__device__ __forceinline__ void st_async2(uint32_t raddr, uint32_t a, uint32_t b, uint32_t rbar) {
  asm volatile("st.async.weak.shared::cluster.mbarrier::complete_tx::bytes.v2.b32 [%0], {%1, %2}, [%3];" ::"r"(raddr), "r"(a), "r"(b), "r"(rbar) : "memory");
}
__device__ __forceinline__ void bulk_prefetch(const void* src, uint32_t sz, uint64_t pol) {
  asm volatile("cp.async.bulk.prefetch.L2.global.L2::cache_hint [%0], %1, %2;" ::"l"(src), "r"(sz), "l"(pol) : "memory");
}
__device__ __forceinline__ void bulk_wait_read() { asm volatile("cp.async.bulk.wait_group.read 0;" ::: "memory"); }
__device__ __forceinline__ uint32_t shfl_ordered(uint32_t v, int src) { uint32_t r; asm volatile("shfl.sync.idx.b32 %0, %1, %2, 0x1f, 0xffffffff;" : "=r"(r) : "r"(v), "r"(src)); return r; }
__device__ __forceinline__ int chan_pos(int d) {
  return d < 512 ? 72 * (d >> 6) + ((d & 33) | ((d & 6) << 2) | ((d >> 2) & 6)) : 72 * ((d - 512) >> 3) + 64 + (d & 7);
}

struct Ring {
  uint32_t s, ph;
  __device__ __forceinline__ void next() { if (++s == ST) { s = 0; ph ^= 1; } }
};
constexpr int B_FULL = 0, B_GO = 40, B_CFULL = 48, B_SEMPTY = 80, B_ZFULL = 96, B_RFULL = 104, B_UDONE = 120, B_KFULL = 136, B_RAW = 168, B_CVGO = 248, B_PEER = 256, B_G2GO = 264, B_KVGO = 280,
              B_EMPTY = 296, B_G1DONE = 336,
              B_CEMPTY = 344, B_SFULL = 376, B_USTG = 392, B_END = 408;

static_assert((B_EMPTY - B_GO) % 16 == 0 && (B_CEMPTY - B_EMPTY) % 16 == 0 && (B_END - B_CEMPTY) % 16 == 0, "barrier groups");

__device__ __forceinline__ void wait_counter(uint32_t* f, int idx, uint32_t want, uint32_t first, uint32_t nap) {
#pragma unroll 1
  for (uint32_t spins = 0; first != want; spins++) {
    if (nap && spins) __nanosleep(nap);
    first = flag_ld(f, idx);
    if (spins > SPIN_LIMIT) asm volatile("trap;");
  }
  fence_async_global();
}

__device__ __forceinline__ void gate_arrive(uint32_t* f, uint32_t back) {
  asm volatile("red.relaxed.gpu.global.max.u32 [%0], %1;" ::"l"(f + FL_GATE * 32 + 1), "r"(time_now() - back) : "memory");
  flag_add(f, FL_GATE, 1);
}

__device__ __forceinline__ float ln_rinv(float var) {
  float rt, rinv;
  asm("sqrt.approx.ftz.f32 %0, %1;" : "=f"(rt) : "f"(bf_round(bf_round(var) + 1e-5f)));
  asm("rcp.approx.ftz.f32 %0, %1;" : "=f"(rinv) : "f"(bf_round(rt)));
  return rinv;
}
__device__ __forceinline__ uint32_t ln_apply(uint32_t x, const uint4& st) {
  const uint32_t d = hsub2(x, st.x);
  return hfma2(d, st.y, hmul2(d, st.z));
}

__device__ __forceinline__ void polling_done(uint32_t* f, int lane) {
  unsigned old = 0;
  if (lane == 0) asm volatile("atom.relaxed.gpu.global.add.u32 %0, [%1], 1;" : "=r"(old) : "l"(f + FL_DONE * 32) : "memory");
  old = __shfl_sync(0xffffffffu, old, 0);
  if (old == 2 * NCTA - 1) {
    if (lane < FL_N) *(uint2*)(f + lane * 32) = make_uint2(0u, 0u);
  }
}

struct Pipe { Ring r; uint32_t prev; bool pending; };
__device__ __forceinline__ void pipe_drain(Pipe& p, uint32_t bars, bool leader) {
  wg_wait<0>();
  if (leader) mbar_arrive(bars + B_EMPTY + p.prev * 8);
  p.pending = false;
}
template <int TB, int LEAD, int R>
__device__ __forceinline__ void gemm_run(float (&acc)[R], int n, int accumulate, Pipe& p, uint32_t sb, uint32_t pitch, int wg, bool leader) {
  const uint32_t bars = sb + BAR_OFF;
  const uint32_t dA0 = desc_lo(sb + wg * 8192, 8192), dB0 = desc_lo(sb + ASZ, TB ? 128 : 16);
  constexpr int KB_STEP = TB ? 16 : 2;
#pragma unroll 1
  for (int kb = 0; kb < n; kb++) {
    if (LEAD && kb == n - LEAD && wg == 1) { if (TB) pipe_drain(p, bars, leader); named_bar(8, 256); }
    mbar_wait(bars + B_FULL + p.r.s * 8, p.r.ph);
    const uint32_t dA = dA0 + p.r.s * (pitch >> 4), dB = dB0 + p.r.s * (pitch >> 4);
    wg_fence();
    wgmma_ss<TB>(acc, dA, dB, accumulate | kb);
#pragma unroll
    for (int k = 1; k < 4; k++) wgmma_ss<TB>(acc, dA + k * 128, dB + k * KB_STEP, 1);
    wg_commit();
    wg_wait<1>();
    if (p.pending && leader) mbar_arrive(bars + B_EMPTY + p.prev * 8);
    p.pending = true;
    p.prev = p.r.s;
    p.r.next();
  }
  if (LEAD && wg == 0) named_arrive(8, 256);
}

template <int BROW0, int I0, int I1>
__device__ __forceinline__ void gemm2_part(float (&c)[36], uint32_t sb, uint32_t pitch, int wg) {
  const uint32_t dA0 = desc_lo(sb + wg * 8192, 8192), dB0 = desc_lo(sb + ASZ + BROW0 * 128, 16);
  wg_fence();
#pragma unroll
  for (int i = I0; i < I1; i++) {
    const int step = 69 - LAG + (i >> 2);
    if ((i & 3) == 0 && BROW0 == 0) mbar_wait_u(sb + BAR_OFF + B_FULL + (step % ST) * 8, (step / ST) & 1);
    if (i == 4 * LAG - TURN && BROW0 && wg == 0) named_arrive(7, 256);
    wgmma_ss<0>(c, dA0 + (step % ST) * (pitch >> 4) + (i & 3) * 128, dB0 + (step % ST) * (pitch >> 4) + (i & 3) * 2, 1);
  }
  wg_commit();
}
__device__ __forceinline__ void split_acc(const float (&acc)[72], float (&a)[36], float (&b)[36]) {
#pragma unroll
  for (int i = 0; i < 36; i++) { asm volatile("mov.b32 %0, %1;" : "=f"(a[i]) : "f"(acc[i])); asm volatile("mov.b32 %0, %1;" : "=f"(b[i]) : "f"(acc[36 + i])); }
}
template <int V0, int V1, int R, class Slice>
__device__ __forceinline__ void gelu_store(const float (&acc)[R], uint32_t bias0, uint32_t bias1, uint32_t sa, uint32_t zero, Slice slice) {
  const uint32_t bb[2] = {pin(bias0) * 0x10001u, pin(bias1) * 0x10001u};
  uint32_t x[2][4], t[2][4], dep[V1 / 8], c3 = 0x3d123d12u;
#pragma unroll
  for (int j = V0 / 8; j <= V1 / 8; j++) {
    if (j < V1 / 8) {
      if (j >= V0 / 8 + GLAG) c3 = (dep[j - GLAG] & zero) | 0x3d123d12u;
#pragma unroll
      for (int u = 0; u < 4; u++) {
        x[j & 1][u] = hadd2(pack_bf16(acc[8 * j + 2 * u], acc[8 * j + 2 * u + 1]), bb[u & 1]);
        t[j & 1][u] = tanh2_ordered(hmul2(x[j & 1][u], hfma2(hmul2(x[j & 1][u], c3), x[j & 1][u], 0x3f4c3f4cu)));
      }
    }
    if (j > V0 / 8) {
      const uint32_t *xx = x[(j - 1) & 1], *tt = t[(j - 1) & 1];
      stsm4_t(sa + (j - 1) * 2048, hfma2(xx[0], tt[0], xx[0]), hfma2(xx[1], tt[1], xx[1]), hfma2(xx[2], tt[2], xx[2]), hfma2(xx[3], tt[3], xx[3]));
      dep[j - 1] = slice(j - 1);
    }
  }
}
struct Role { int half, kind, g2_m, dt, g1_mt, g1_nt, cs, nconv, skip; uint32_t pitch; };
__device__ __forceinline__ Role get_role(const RoleMap& roles) {
  uint32_t b, sm;
  asm volatile("mov.u32 %0, %%ctaid.x;" : "=r"(b));
  asm volatile("mov.u32 %0, %%smid;" : "=r"(sm));
  const uint32_t w = roles.role[(roles.by_sm ? sm : b) >> 1];
  const int half = b & 1, kind = w & 3, m = (w >> 4) & 15, dt = (w >> 2) & 3;
  return Role{half, kind, m * 128, dt, half * 18 + (int)((w >> 8) & 31), (int)(w >> 16), (m * 4 + dt) * 2 + half,
              kind ? kind * kind : 6 - half, kind ? 1 : 2 - 2 * half, kind ? (uint32_t)PITCH_B : (uint32_t)PITCH_S};
}
__device__ __forceinline__ int g2_block(int half, int j) { return j < 0 ? 0 : half * 36 + (j < 12 ? 2 * j : j < 24 ? 2 * j - 23 : j); }
__device__ __forceinline__ int conv_chan(const Role& ro, int i) {
  const bool early = ro.kind == 0 && i < 4;
  const int k = early ? 2 * ro.cs + (i & 1) : ro.kind == 2 ? 176 + 4 * ro.cs + i : ro.kind ? 48 + ro.cs : i == 4 ? ro.cs : 96 + (ro.cs >> 1);
  return (3 * (k >> 6) + (early ? i >> 1 : 2)) * 64 + (k & 63);
}
__device__ __forceinline__ uint32_t conv_buf(uint32_t sb, int kind, int b) {
  return sb + (kind ? (b ? b + 1 : ST) * PITCH_B : b == 3 ? (36 % ST) * PITCH_S : ST * PITCH_S + b * CBUF);
}
__device__ __forceinline__ uint32_t conv_stage(uint32_t sb, int kind) { return sb + (kind ? ST * PITCH_B + CBUF : ST * PITCH_S + 3 * CBUF); }
__device__ __forceinline__ uint32_t u_stage(uint32_t sb, uint32_t pitch, int w) { return sb + (2 - w) * pitch + ASZ; }

__global__ void __cluster_dims__(2, 1, 1) __launch_bounds__(384, 1)
fused_kernel(const __nv_bfloat16* __restrict__ q, Scratch* __restrict__ gs, const __nv_bfloat16* __restrict__ b1,
             const __nv_bfloat16* __restrict__ shiftk, const __nv_bfloat16* __restrict__ ssmk, const __nv_bfloat16* __restrict__ ssmD,
             const __grid_constant__ CUtensorMap tmW1, const __grid_constant__ CUtensorMap tmW2, const __grid_constant__ CUtensorMap tmZ,
             const __grid_constant__ CUtensorMap tmH, const __grid_constant__ CUtensorMap tmK, const __grid_constant__ CUtensorMap tmV,
             const __grid_constant__ CUtensorMap tmKV, const __grid_constant__ CUtensorMap tmKL, const __grid_constant__ RoleMap roles, const __nv_bfloat16* __restrict__ b2,
             __nv_bfloat16* __restrict__ out) {
  const int cta = blockIdx.x;
  const int tid = threadIdx.x;

  const uint32_t t_start = clock_now();
  const int lc = (cta + LNROT) & 127;
  const uint32_t do_ln = cta < 128 && tid < 256;
  const int oct = lc + (tid & 128), ln_row = oct * 8 + ((tid >> 4) & 7), l16 = tid & 15;
  uint2 xr[9];
  const __nv_bfloat16* qrow = q + (size_t)ln_row * D_ + l16 * 4;
  asm volatile("" : "+l"(qrow));
  const int warp = __shfl_sync(0xffffffffu, tid >> 5, 0);
  if (warp < 8 || warp == 11) asm volatile("barrier.cluster.arrive.relaxed.aligned;" ::: "memory");
  if (do_ln && oct >= QLATE) spin_until(t_start, QDELAY + QRAMP * oct / 2);
#pragma unroll
  for (int i = 0; i < 9; i++) xr[i] = ldg64_if(qrow + i * 64, do_ln);
  const uint32_t sb = __shfl_sync(0xffffffffu, (uint32_t)__cvta_generic_to_shared(smem_raw), 0);
  const uint32_t bars = sb + BAR_OFF;
  const int lane = tid & 31;
  const int wg = warp >> 2;
  constexpr int LN_OFF = ST * PITCH_B;

  uint32_t look = 0;
  if (warp < 8 || warp == 11) {
    const int hq = (lane & 16) >> 3, hb = (lane & 16) + hq;
    float da[3][4] = {};
#pragma unroll
    for (int i = 0; i < 9; i++) mma16816(da[i % 3], xr[i].x, 0x3f803f80u, xr[i].y, 0x3f803f80u, xr[i].x, xr[i].y);
    const float r1 = ((da[0][2] + da[0][3]) + (da[1][2] + da[1][3])) + (da[2][2] + da[2][3]);
    const float r2 = (lane & 4) ? (da[0][1] + da[1][1]) + da[2][1] : (da[0][0] + da[1][0]) + da[2][0];
    const float s1 = __shfl_sync(0xffffffffu, r1, hq) + __shfl_sync(0xffffffffu, r1, hq + 1);
    const float s2 = (__shfl_sync(0xffffffffu, r2, hb) + __shfl_sync(0xffffffffu, r2, hb + 4)) + (__shfl_sync(0xffffffffu, r2, hb + 9) + __shfl_sync(0xffffffffu, r2, hb + 13));
    const float mean = s1 * (1.f / D_), var = fmaxf(fmaf(-mean, mean, s2 * (1.f / D_)), 0.f);
    const float rinv = ln_rinv(var), rinv2 = ln_rinv(var * rinv * rinv), scale = rinv * rinv2, shift = -bf_round((mean - bf_round(mean)) * rinv) * rinv2;
    const uint32_t m2 = pack_bf16(mean, mean), hi2 = pack_bf16(scale, scale), lo2 = pack_bf16(scale - bf_lo(hi2), scale - bf_lo(hi2)), sh2 = pack_bf16(shift, shift);
    const uint32_t hi1 = pack_bf16(rinv, rinv);
    asm volatile("{\n.reg .pred p;\nsetp.eq.u32 p, %5, 0;\n@p st.shared.v4.u32 [%0], {%1, %2, %3, %4};\n}" ::"r"(sb + LN_OFF + 18432 + tid), "r"(m2), "r"(hi1),
                 "r"(pack_bf16(rinv - bf_lo(hi1), rinv - bf_lo(hi1))), "r"(0u), "r"(tid & 0x10f) : "memory");
    const uint32_t g0 = 4 * (l16 >> 3) + 2 * (l16 & 1), hrow = sb + LN_OFF + ((tid >> 7) & 1) * 9216 + (tid & 0x70);
    const uint32_t hs0 = hrow + g0 * 128 + ((l16 >> 1) & 3) * 4, hs8 = ((hrow + (l16 >> 1) * 1152) ^ ((l16 >> 1) << 4)) + 1024 + (l16 & 1) * 8;
    uint32_t w[18];
#pragma unroll
    for (int i = 0; i < 18; i++) {
      const uint32_t d = hsub2((i & 1) ? xr[i >> 1].y : xr[i >> 1].x, m2);
      asm("max.u32 %0, %1, 1;" : "=r"(w[i]) : "r"(hfma2(d, hi2, hfma2(d, lo2, sh2))));
    }
#pragma unroll
    for (int i = 0; i < 16; i++) {
      const int gi = 9 * (i >> 1) + (i & 1);
      asm volatile("{\n.reg .pred p;\nsetp.ne.u32 p, %2, 0;\n@p st.shared.u32 [%0], %1;\n}" ::"r"((hs0 ^ ((g0 * 16 + (gi & 7) * 16) & 0x70)) + gi * 128), "r"(w[i]), "r"(do_ln) : "memory");
    }
    asm volatile("{\n.reg .pred p;\nsetp.ne.u32 p, %3, 0;\n@p st.shared.v2.u32 [%0], {%1, %2};\n}" ::"r"(hs8), "r"(w[16]), "r"(w[17]), "r"(do_ln) : "memory");
    fence_async_smem();
    if (warp < 8) named_arrive(wg, 160);
  } else if (warp != 8) {
    spin_until(t_start, W9);
  }

  if (wg == 2) {
    asm volatile("setmaxnreg.dec.sync.aligned.u32 56;");
    auto store_h = [&](int w) {
      named_bar(w, 160);
      if (cta < 128 && elect_one()) {
        tma3d_store(&tmH, ((lc >> 3) + 16 * w) * 72, lc & 7, sb + LN_OFF + w * 9216);
        bulk_s2g(gs->stats + (lc + 128 * w) * 8, sb + LN_OFF + 18432 + w * 128, 128);
        bulk_commit();
      }
    };
    auto publish_h = [&](int w) {
      if (cta < 128 && elect_one()) { bulk_wait_all(); flag_add(gs->flags, FL_H + (w ? 2 : lc >> 6), 1); }
      __syncwarp();
    };
    if (warp == 11) {
      if (lc >= 64) spin_until(t_start, HW);
      store_h(0);
      look = flag_ld(gs->flags, FL_H);
      if (lc < 64) publish_h(0);
    } else {
      if (elect_one()) {
        if (warp == 8) {
#pragma unroll
          for (int o = 0; o < B_GO; o += 8) mbar_init(bars + o, 1);
        } else {
#pragma unroll
          for (int o = 0; o < (B_EMPTY - B_GO) / 2; o += 8) mbar_init(bars + B_GO + (warp - 9) * ((B_EMPTY - B_GO) / 2) + o, 1);
#pragma unroll
          for (int o = 0; o < (B_CEMPTY - B_EMPTY) / 2; o += 8) mbar_init(bars + B_EMPTY + (warp - 9) * ((B_CEMPTY - B_EMPTY) / 2) + o, 2);
#pragma unroll
          for (int o = 0; o < (B_END - B_CEMPTY) / 2; o += 8) mbar_init(bars + B_CEMPTY + (warp - 9) * ((B_END - B_CEMPTY) / 2) + o, 4);
        }
        asm volatile("fence.mbarrier_init.release.cluster;" ::: "memory");
      }
      __syncwarp();
      asm volatile("barrier.cluster.arrive.relaxed.aligned;" ::: "memory");
      if (warp == 8) { prefetch_map(&tmW1); prefetch_map(&tmH); }
      if (warp == 9) { prefetch_map(&tmK); prefetch_map(&tmV); prefetch_map(&tmKV); prefetch_map(&tmKL); prefetch_map(&tmW2); prefetch_map(&tmZ); }
    }
    const Role ro = get_role(roles);
    if (warp != 8) asm volatile("barrier.cluster.wait.aligned;" ::: "memory");
    if (warp == 11) {
      Ring r{0, 1};
      const uint32_t bsz = ro.pitch - ASZ;
      const uint8_t* src = gs->h + ro.g1_nt * bsz + ST * 73728;
      named_bar(10, 64);
#pragma unroll 1
      for (int i = ST; i < 32; i++) {
        if (i == ST || i == 8 || i == 16) wait_counter(gs->flags, FL_H + (i >> 3), i == 16 ? 128u : 64u, look, 0);
        if (i == LK1 || i == LK2) look = flag_ld(gs->flags, FL_H + (i >> 3) + 1);
        mbar_wait(bars + B_EMPTY + r.s * 8, r.ph ^ 1);
        if (elect_one()) bulk_g2s(sb + r.s * ro.pitch + ASZ, src, bsz, bars + B_FULL + r.s * 8);
        if (i == HS2) store_h(1);
        if (i == HS2 + 2 || (i == ST && lc >= 64)) publish_h(i != ST);
        if (i == KVGO1 && lane == 0) mbar_arrive(bars + B_KVGO + 8);
        if (i == KVGO && lane == 0) mbar_arrive(bars + B_KVGO);
        if (i == CVGO && lane == 0) mbar_arrive(bars + B_CVGO);
        src += 73728;
        r.next();
      }
      if (ro.kind != 2) {
        look = 0;
#pragma unroll 1
        for (int j = -1; j < 36; j++) {
          const uint8_t* su = gs->u + ((size_t)g2_block(ro.half, j) * D_ + ro.dt * 144) * 128;
          if (j == -1 || j == 12 || j == 24) wait_counter(gs->flags, FL_U + (j < 0 ? 0 : ro.half * 3 + j / 12), j < 0 ? 96u : j == 24 ? 18u : 48u, look, 100);
          if (j == (ro.skip ? 4 : -1) || j == 3) mbar_wait_u(bars + B_UDONE + (j == 3 ? 8 : 0), 0);
          if (j >= ro.skip - 1) mbar_wait(bars + B_EMPTY + r.s * 8, r.ph ^ 1);
          if (j >= ro.skip - 1 && elect_one()) {
            bulk_g2s(sb + r.s * ro.pitch + ASZ, su + (ro.half ^ 1) * 9216, 9216, bars + B_FULL + r.s * 8);
            bulk_g2s(sb + r.s * ro.pitch + ASZ + 9216, su + ro.half * 9216, 9216, bars + B_FULL + r.s * 8);
          }
          if (j == 9 || j == 21) look = flag_ld(gs->flags, FL_U + ro.half * 3 + j / 12 + 1);
          r.next();
        }
#pragma unroll 1
        for (int o = lane; o < ST * 73728 / 16 / NG2; o += 32) ((uint4*)gs->h)[ro.cs * (ST * 73728 / 16 / NG2) + o] = make_uint4(0u, 0u, 0u, 0u);
      }
    } else if (warp == 8) {
      const uint64_t pol = stream_policy();
      Ring r{0, 0};
#pragma unroll 1
      for (int i = 0; i < 32; i++) {
        if (i < ST) spin_until(t_start, A0 + i * AD + (i >= AN ? AL : 0));
        if (i == ST) {
          asm volatile("barrier.cluster.wait.aligned;" ::: "memory");
          if (roles.by_sm) {
            uint32_t sm;
            asm volatile("mov.u32 %0, %%smid;" : "=r"(sm));
            if (elect_one()) { mbar_expect(bars + B_PEER, 8); st_async2(mapa(bars + B_END, ro.half ^ 1), sm, sm, mapa(bars + B_PEER, ro.half ^ 1)); }
            mbar_wait_u(bars + B_PEER, 0);
            if ((lds32(bars + B_END) ^ sm) != 1 || sm >= NCTA) asm volatile("trap;");
          }
        }
        if (i >= ST) mbar_wait(bars + B_EMPTY + r.s * 8, r.ph ^ 1);
        if (elect_one()) {
          mbar_expect(bars + B_FULL + r.s * 8, ro.pitch);
          tma_weights(sb + r.s * ro.pitch, &tmW1, i * 64, ro.g1_mt * 2, bars + B_FULL + r.s * 8, pol);
        }
        r.next();
      }
      if (ro.kind != 2) {
#pragma unroll 1
        for (int j = -1; j < 36; j++) {
          if (j == 3 && ro.kind == 0) mbar_wait_u(bars + B_CEMPTY + 24, 0);
          if (j >= ro.skip - 1) mbar_wait(bars + B_EMPTY + r.s * 8, r.ph ^ 1);
          if (j >= ro.skip - 1 && elect_one()) {
            mbar_expect(bars + B_FULL + r.s * 8, PITCH_S);
            tma_weights(sb + r.s * ro.pitch, &tmW2, g2_block(ro.half, j) * 64, ro.g2_m >> 6, bars + B_FULL + r.s * 8, pol);
            if (j == 26 + ro.dt) tma_weights_prefetch(&tmW2, g2_block(ro.half, j + 6) * 64, ro.g2_m >> 6, pol);
          }
          r.next();
        }
        if (lane < 2) mbar_expect(bars + B_RFULL + lane * 8, 9216);
        __syncwarp();
        mbar_wait(bars + B_EMPTY + r.s * 8, r.ph ^ 1);
        if (lane == 0) mbar_arrive_cluster(mapa(bars + B_GO, ro.half ^ 1));
      }
    } else {
      const uint64_t pol = stream_policy();
      {
        const uint32_t hb = (ro.pitch - ASZ) >> 1, raw = bars + B_RAW + (warp - 9) * 40, dst = sb + ASZ + (warp - 9) * hb;
        const uint8_t* src = gs->h + (2 * ro.g1_nt + warp - 9) * hb;
        auto fetch_h = [&](int i) { if (elect_one()) { mbar_expect(raw + i * 8, hb); bulk_g2s(dst + i * ro.pitch, src + i * 73728, hb, raw + i * 8); } };
        int next = 0;
#pragma unroll 1
        for (int i = -1; i < ST; i++) {
          if (i >= 0) {
#pragma unroll 1
            for (uint32_t tries = 0;; tries++) {
              mbar_wait_u(raw + i * 8, tries & 1);
              const uint32_t pa = dst + i * ro.pitch + lane * 32 + (lane >> 2) * 4;
              uint32_t m = 1;
#pragma unroll
              for (int j = 0; j < 12; j++) m = min(m, lds32(pa + (j < 9 || ro.kind ? j : 0) * 1024));
              if (__all_sync(0xffffffffu, m)) break;
              fetch_h(i);
            }
            if (elect_one()) asm volatile("mbarrier.complete_tx.relaxed.cta.shared::cta.b64 [%0], %1;" ::"r"(bars + B_FULL + i * 8), "r"(hb) : "memory");
          }
#pragma unroll 1
          for (const int end = min(next + 2, ST); next < end; next++) {
            if (i < 0) spin_until(t_start, H0 + next * HD);
            fetch_h(next);
          }
          if (i < 0 && warp == 10) named_arrive(10, 64);
        }
      }
      const int chan = conv_chan(ro, lane < ro.nconv ? lane : 0);
      const uint32_t dskip = ldg16(ssmD + chan);
      uint4 shk;
      mbar_wait_u(bars + B_KVGO + (ro.kind ? 8 : (warp - 9) * 8), 0);
      if (ro.kind) shk = ldg128(ssmk + (size_t)chan * S_);
      else {
        const int cs = ro.cs, grp = (cs / 3) * 2 + warp - 9, cb0 = (cs % 3) * 3;
        const uint32_t kin_s = sb + ST * PITCH_S + (warp - 9) * KVW, kout = kin_s + 2 * KVIN, fb = bars + B_KFULL + (warp - 9) * 16;
        auto fetch = [&](int i) {
          if (elect_one()) {
            mbar_expect(fb + (i & 1) * 8, KVIN);
            tma2d_stream(kin_s + (i & 1) * KVIN, &tmK, (cb0 + i) * 64, grp * 32 - 4, fb + (i & 1) * 8, pol);
            tma2d_stream(kin_s + (i & 1) * KVIN + 4608, &tmV, (cb0 + i) * 64, grp * 32 - 1, fb + (i & 1) * 8, pol);
          }
        };
        fetch(0);
        shk = ldg128(shiftk + (cb0 * 64 + lane * 2) * 4);
#pragma unroll 1
        for (int i = 0; i < 3; i++) {
          const uint32_t w0 = __byte_perm(shk.x, shk.z, 0x5410), w1 = __byte_perm(shk.x, shk.z, 0x7632);
          const uint32_t w2 = __byte_perm(shk.y, shk.w, 0x5410), w3 = __byte_perm(shk.y, shk.w, 0x7632);
          const uint32_t ka = kin_s + (i & 1) * KVIN + lane * 4;
          mbar_wait_u(fb + (i & 1) * 8, i >> 1);
          if (i < 2) fetch(i + 1);
          shk = ldg128(i < 2 ? shiftk + ((cb0 + i + 1) * 64 + lane * 2) * 4 : ssmk + (size_t)chan * S_);
          uint32_t kr[8], vr[8], t1, t2, t3, xp;
          {
            const uint32_t k0 = lds32(ka), k1 = lds32(ka + 128), k2 = lds32(ka + 256), k3 = lds32(ka + 384), v0 = lds32(ka + 4608);
#pragma unroll
            for (int j = 0; j < 8; j++) { kr[j] = lds32(ka + 512 + j * 128); vr[j] = lds32(ka + 4736 + j * 128); }
            xp = hmul2(hfma2(k3, w0, hfma2(k2, w1, hfma2(k1, w2, hmul2(k0, w3)))), v0);
            t1 = hfma2(k3, w1, hfma2(k2, w2, hmul2(k1, w3)));
            t2 = hfma2(k3, w2, hmul2(k2, w3));
            t3 = hmul2(k3, w3);
          }
#pragma unroll 1
          for (int o = 0; o < 4; o++) {
            const uint32_t from = ka + o * 1024, to = kout + (o >> 1) * 5120 + lane * 80 + (o & 1) * 32;
#pragma unroll
            for (int m = 0; m < 8; m += 4) {
              uint32_t x[4];
#pragma unroll
              for (int j = 0; j < 4; j++) {
                x[j] = hmul2(hfma2(kr[m + j], w0, t1), vr[m + j]);
                t1 = hfma2(kr[m + j], w1, t2);
                t2 = hfma2(kr[m + j], w2, t3);
                t3 = hmul2(kr[m + j], w3);
              }
#pragma unroll
              for (int c = 0; c < 2; c++) {
                const uint32_t sel = c ? 0x7632 : 0x5410;
                sts128(to + c * 2560 + m * 4, __byte_perm(x[0], xp, sel), __byte_perm(x[1], x[0], sel), __byte_perm(x[2], x[1], sel), __byte_perm(x[3], x[2], sel));
              }
#pragma unroll
              for (int j = m; j < m + 4; j++) { kr[j] = lds32_if(from + 1536 + j * 128, o < 3); vr[j] = lds32_if(from + 5760 + j * 128, o < 3); }
              xp = x[3];
            }
            if (o & 1) {
              fence_async_smem();
              __syncwarp();
              if (elect_one()) {
                bulk_wait_all();
                if (o == 1 && i) flag_add(gs->flags, FL_KV + i - 1, 1);
                tma4d_store(&tmKV, (cb0 + i) * 32, 0, 2 * grp + (o >> 1), kout + (o >> 1) * 5120);
                bulk_commit();
              }
              __syncwarp();
            }
          }
        }
        look = flag_ld(gs->flags, FL_KV + warp - 9);
        if (lane == 2 * (warp - 9)) bulk_prefetch(ssmk + (size_t)chan * S_, 2 * S_ * 2, pol);
        if (elect_one()) {
          bulk_wait_all();
          flag_add(gs->flags, FL_KV + 2, 1);
        }
        __syncwarp();
      }
      {
        shk.x = __byte_perm(pack_bf16(bf_lo(shk.x) + bf_lo(dskip), 0.f), shk.x, 0x7610);
        const int mid = ro.kind ? 1 : 2;
#pragma unroll 1
        for (int i = warp == 9 ? 0 : mid; i < (warp == 9 ? mid : ro.nconv); i++) {
          const int b = i & 3, d = __shfl_sync(0xffffffffu, chan, i);
          const uint32_t base = conv_buf(sb, ro.kind, b), cf = bars + B_CFULL + b * 8;
          if (ro.kind ? i < 2 : !(i & 1)) wait_counter(gs->flags, FL_KV + (ro.kind ? 2 : i >> 1), 192u, i < 4 ? look : 0u, 200);
          if (i == 2) { mbar_wait_u(bars + B_CVGO, 0); spin_until(clock_now(), 600); }
          if (i == 2 * mid - 1) {
            mbar_wait_u(bars + B_G1DONE, 0);
            if (lane == 4 || lane == 5) bulk_prefetch(ssmk + (size_t)chan * S_, S_ * 2, pol);
          }
          if (i >= 4) mbar_wait_u(bars + B_CEMPTY + b * 8, 0);
          if (lane == i) sts128(base + CH_OFF, shk.x, shk.y, shk.z, shk.w);
          if (lane >= 29) sts128(base + CH_OFF + (lane - 32) * 16, 0u, 0u, 0u, 0u);
          fence_async_smem();
          __syncwarp();
          if (elect_one()) mbar_expect(cf, 4080 + 64 * 160);
#pragma unroll 1
          for (int k = 0; k < 5; k++) {
            if (elect_one()) {
              if (k < 4) asm volatile("cp.async.bulk.tensor.3d.shared::cluster.global.mbarrier::complete_tx::bytes [%0], [%1, {%3, %4, %5}], [%2];"
                                      ::"r"(base + CT_OFF + k * 2560), "l"(&tmKL), "r"(cf), "r"(0), "r"(k * 16), "r"(d) : "memory");
              else bulk_g2s_stream(base + CH_OFF + 16, ssmk + (size_t)d * S_ + 8, 4080, cf, pol);
            }
          }
        }
      }
      if (warp == 9) {
        if (lane < 6) sts32(bars + B_END + 8 + lane * 4, chan_pos(chan));
        __syncwarp();
        if (elect_one()) {
          const uint32_t bsz = ro.pitch - ASZ;
          if (ro.kind) { mbar_wait_u(bars + B_G1DONE, 0); gate_arrive(gs->flags, GDELAY + BLK_NS - (ro.kind == 1 ? GBIG : 0)); }
#pragma unroll 1
          for (int w = 0; w < 2; w++) {
            const uint32_t src = u_stage(sb, ro.pitch, w);
            mbar_wait_u(bars + B_USTG + w * 8, 0);
            bulk_s2g(gs->u + (size_t)(2 * ro.g1_mt + w) * D_ * 128 + ro.g1_nt * bsz, src, bsz);
            bulk_commit();
#pragma unroll 1
            for (int k = 0; k < ro.skip * w; k++) {
              mbar_arrive(bars + B_FULL + (2 + k) * 8);
              mbar_arrive(bars + B_EMPTY + (2 + k) * 8);
              mbar_arrive(bars + B_EMPTY + (2 + k) * 8);
            }
            bulk_wait_read();
            mbar_arrive(bars + B_UDONE + w * 8);
            if (ro.kind && !w) continue;
            bulk_wait_all();
            flag_add(gs->flags, FL_U + (w ? ro.half * 3 + (ro.kind ? 2 : 1) : 0), 1);
          }
#pragma unroll 1
          for (int i = 0; i < ro.nconv; i++) {
            mbar_wait_u(bars + B_SFULL + (i & 1) * 8, (i >> 1) & 1);
            bulk_s2g(gs->z + (size_t)lds32(bars + B_END + 8 + i * 4) * S_, conv_stage(sb, ro.kind) + (i & 1) * 4096, 4096);
            bulk_commit();
            if (ro.kind == 0 && i == ro.nconv - 4) gate_arrive(gs->flags, ro.skip * BLK_NS);
            bulk_wait_read();
            mbar_arrive(bars + B_SEMPTY + (i & 1) * 8);
          }
          bulk_wait_all();
          flag_add(gs->flags, FL_Z, 1);
        }
      } else if (ro.kind != 2) {
        mbar_wait_u(bars + B_G1DONE, 0);
        uint2 gate;
#pragma unroll 1
        for (uint32_t spins = 0;; spins++) {
          asm volatile("ld.relaxed.gpu.global.v2.u32 {%0, %1}, [%2];" : "=r"(gate.x), "=r"(gate.y) : "l"(gs->flags + FL_GATE * 32) : "memory");
          if (gate.x == NCTA) break;
          __nanosleep(100);
          if (spins > SPIN_LIMIT) asm volatile("trap;");
        }
#pragma unroll 1
        for (int w = 0; w < 2; w++) {
          while (time_now() - gate.y < GDELAY + ro.skip * BLK_NS + w * GDELAY1) {}
          if (lane == 0) mbar_arrive(bars + B_G2GO + (w ^ (ro.nconv & 1)) * 8);
        }
        wait_counter(gs->flags, FL_Z, NCTA, 0, 300);
        spin_until(clock_now(), ZRAMP * cta);
        if (elect_one()) {
          mbar_expect(bars + B_ZFULL, 18432);
          tma2d(sb + ST * ro.pitch, &tmZ, ro.g2_m, ro.dt * 144 + ro.half * 72, bars + B_ZFULL);
          tma2d(sb + ST * ro.pitch + 9216, &tmZ, ro.g2_m + 64, ro.dt * 144 + ro.half * 72, bars + B_ZFULL);
        }
      }
    }
    if (warp >= 10) polling_done(gs->flags, lane);
  } else {
    asm volatile("setmaxnreg.inc.sync.aligned.u32 224;");
    const int wi = warp & 3, g = lane >> 2, qd = lane & 3, wt = tid & 127;
    const bool leader = wt == 0;
    Pipe p{{0, 0}, 0, false};
    asm volatile("barrier.cluster.wait.aligned;" ::: "memory");
    int kind;
    {
      const Role ro = get_role(roles);
      kind = ro.kind;
      const int f0 = ro.g1_mt * 128 + wg * 64 + wi * 16 + g;
      uint32_t bias0 = ldg16(b1 + f0), bias1 = ldg16(b1 + f0 + 8);
      const uint32_t so = ((lane >> 4) * 8 + (lane & 7)) * 128 + (((2 * wi + ((lane >> 3) & 1)) ^ (lane & 7)) << 4);
      const int cB = (g >> 1) & 1, cA = g >> 2, b = 2 * wi + (g & 1), nconv = ro.nconv;
      const uint32_t toff = pin(CT_OFF + (40 * (2 * cA + cB) + 8 + b - 2 * qd) * 4);
      const int phi = 2 * cA + (qd >> 1) + cB, pp = cB ? (phi & 3) : ((phi + 3) & 3);
      const int srcB = shfl_ordered(((pp >> 1) << 4) | ((cB ^ 1) << 3) | ((g & 1) << 2) | ((pp & 1) << 1) | (qd & 1), lane);
      const bool pB1 = cB && phi < 4, pB2 = cB && phi == 4;
      const int word = (8 * cB + 2 * (phi & 3) + (qd & 1)) * 8 + b;
      const uint32_t sto = shfl_ordered(conv_stage(sb, kind) + wg * 4096 + (word ^ (((word >> 5) & 3) << 1)) * 4, lane);
      const uint32_t sa = shfl_ordered(u_stage(sb, ro.pitch, wg) + so, lane);
      uint32_t a[16][4];
      auto load_a = [&](uint32_t base, int t, uint32_t on) {
        const uint32_t pt = base + toff + (t >> 1) * 1280 + (t & 1) * 64;
        a[t][0] = lds32_if(pt + 32, on); a[t][1] = lds32_if(pt + 672, on); a[t][2] = lds32_if(pt, on); a[t][3] = lds32_if(pt + 640, on);
      };
      auto gemm1_done = [&]() {
        pipe_drain(p, bars, leader);
        if (leader) mbar_arrive(bars + B_G1DONE);
        mbar_wait_u(bars + B_EMPTY + (2 - wg) * 8, wg ^ 1);
      };
      {
        float acc[72];
        if (kind) {
          float big[96];
          gemm_run<1, LEAD_B>(big, 32, 0, p, sb, PITCH_B, wg, leader);
          if (wg == 1) named_arrive(6, 256);
          gemm1_done();
          if (wg < nconv) mbar_wait_u(bars + B_CFULL + wg * 8, 0);
#pragma unroll
          for (int t = 0; t < 8; t++) load_a(conv_buf(sb, 1, wg), t, 1);
          gelu_store<72, 96>(big, bias0, bias1, sa, 0u, [](int) { return 0u; });
#pragma unroll
          for (int i = 0; i < 72; i++) asm volatile("mov.b32 %0, %1;" : "=f"(acc[i]) : "f"(big[i]));
        } else {
          gemm_run<1, 0>(acc, 32 - LEAD_S - (wg ? 0 : PRE0), 0, p, sb, PITCH_S, wg, leader);
          if (wg == 1) pipe_drain(p, bars, leader);
          mbar_wait_u(bars + B_CFULL + wg * 8, 0);
#pragma unroll
          for (int t = 0; t < 8; t++) load_a(conv_buf(sb, 0, wg), t, 1);
          if (wg == 1) named_bar(8, 256);
          gemm_run<1, 0>(acc, LEAD_S + (wg ? 0 : PRE0), 1, p, sb, PITCH_S, wg, leader);
          named_arrive(8 - 2 * wg, 256);
          gemm1_done();
        }
        gelu_store<0, 72>(acc, bias0, bias1, sa, roles.by_sm >> 1, [&](int t) { return t + GLAG < 9 ? lds32(bars) : 0u; });
        fence_async_smem();
        __syncwarp();
        if (lane == 0) mbar_arrive(bars + B_USTG + wg * 8);
      }
      {
#pragma unroll 1
        for (int i = wg; i < nconv; i += 2) {
          const uint32_t base = conv_buf(sb, kind, i & 3), next = conv_buf(sb, kind, (i + 2) & 3);
          const uint64_t dH = mkdesc(base + CH_OFF, 16, 128, 0);
          float y[8][16];
          if (toff < CT_OFF + 32) a[0][2] = 0u;
          named_bar(6 + wg, 256);
          wg_fence();
#pragma unroll
          for (int t = 0; t < 16; t++) {
            if (t == 8) wg_fence();
            if (t == CTURN) named_arrive(7 - wg, 256);
#pragma unroll
            for (int cb = t >> 1; cb < 8; cb++) {
              wgmma_rs_n32(y[cb], a[t][0], a[t][1], a[t][2], a[t][3], dH + (32 * cb - 32 * (t >> 1) - 2 * (t & 1) - 1), t);
              const int n = 8 * t - (t >> 1) * ((t - 1) >> 1) - (t >> 1) + cb + 1;
              if (n % CPER == 0 && n / CPER <= 8) load_a(base, 7 + n / CPER, 1);
            }
          }
          wg_commit();
          const bool more = i + 2 < nconv;
          if (more) mbar_wait_u(bars + B_CFULL + ((i + 2) & 3) * 8, (i + 2) >> 2);
          mbar_wait_u(bars + B_SEMPTY + wg * 8, ((i >> 1) & 1) ^ 1);
          wg_wait<0>();
          if (lane == 0) mbar_arrive(bars + B_CEMPTY + (i & 3) * 8);
          uint32_t P[16], Q[16], R[16], o[8];
#pragma unroll
          for (int j = 0; j < 32; j++) {
            if ((j & 3) == 0) load_a(next, j >> 2, more);
            float v0 = y[j >> 2][4 * (j & 3)], v1 = y[j >> 2][4 * (j & 3) + 1];
            if (j >= 2) { v0 += y[(j - 2) >> 2][4 * ((j - 2) & 3) + 2]; v1 += y[(j - 2) >> 2][4 * ((j - 2) & 3) + 3]; }
            if (j & 1) R[j >> 1] = shfl_ordered(pack_bf16(v0, v1), lane ^ 16);
            else P[j >> 1] = pack_bf16(v0, v1);
          }
#pragma unroll
          for (int m = 0; m < 16; m++) Q[m] = hadd2(P[m], cA ? R[m] : (m ? R[m - 1] : 0u));
#pragma unroll
          for (int m = 0; m < 8; m++) o[m] = shfl_ordered(pB1 ? Q[2 * m] : (pB2 ? (m ? Q[2 * m - 1] : 0u) : Q[2 * m + 1]), srcB);
#pragma unroll
          for (int m = 0; m < 8; m++) sts32(sto + m * 512, hadd2(pB1 ? Q[2 * m + 1] : Q[2 * m], o[m]));
          fence_async_smem();
          __syncwarp();
          if (lane == 0) mbar_arrive(bars + B_SFULL + wg * 8);
        }
        if (wg == (nconv & 1)) named_bar(6 + wg, 256);
      }
    }
    if (kind != 2) {
      const Role ro = get_role(roles);
      const uint32_t pitch = ro.pitch;
      const int s0 = ro.g2_m + wg * 64 + wi * 16 + g;
      const size_t go = (size_t)s0 * D_ + ro.dt * 128 + ro.half * 64 + qd * 8, go8 = (size_t)s0 * D_ + 512 + ro.dt * 16 + ro.half * 8 + qd * 2;
      uint32_t x[2][9], sg[2][9];
      float acc[72];
      p.r = Ring{(uint32_t)(2 + ro.skip), 0};
      mbar_wait_u(bars + B_G2GO + wg * 8, 0);
      gemm_run<0, 0>(acc, XAT + 2 * wg + 1 - ro.skip, 0, p, sb, pitch, wg, leader);
#pragma unroll
      for (int J = 0; J < 4; J++) {
        const uint4 v = ldg128(q + go + (J & 1) * 8 * D_ + (J >> 1) * 32);
        x[J & 1][4 * (J >> 1)] = v.x; x[J & 1][4 * (J >> 1) + 1] = v.y; x[J & 1][4 * (J >> 1) + 2] = v.z; x[J & 1][4 * (J >> 1) + 3] = v.w;
      }
      x[0][8] = ldg32(q + go8); x[1][8] = ldg32(q + go8 + 8 * D_);
      const uint4 st0 = ld_l2(gs->stats + s0), st1 = ld_l2(gs->stats + s0 + 8);
      const uint32_t braw0 = ldg16(b2 + s0), braw1 = ldg16(b2 + s0 + 8);
      gemm_run<0, 0>(acc, ZAT - XAT, 1, p, sb, pitch, wg, leader);
      {
        const int zw = 8 * wi + (g ^ ((((ro.g2_m >> 6) + wg) & 3) << 1));
        const uint32_t za = sb + ST * pitch + wg * 9216 + qd * 256 + (zw & 3) * 4;
        mbar_wait_u(bars + B_ZFULL, 0);
#pragma unroll
        for (int j = 0; j < 9; j++) {
          sg[0][j] = lds32(za + j * 1024 + (((zw >> 2) ^ (2 * qd)) << 4));
          sg[1][j] = lds32(za + j * 1024 + 128 + (((zw >> 2) ^ (2 * qd + 1)) << 4));
        }
      }
      gemm_run<0, 0>(acc, 1, 1, p, sb, pitch, wg, leader);
#pragma unroll
      for (int j = 0; j < 9; j++) {
        const uint32_t z0 = __byte_perm(sg[0][j], sg[1][j], 0x5410), z1 = __byte_perm(sg[0][j], sg[1][j], 0x7632);
        sg[0][j] = hmul2(ln_apply(x[0][j], st0), z0);
        sg[1][j] = hmul2(ln_apply(x[1][j], st1), z1);
        asm volatile("" : "+r"(sg[0][j]), "+r"(sg[1][j]));
      }
      gemm_run<0, SKEW>(acc, 35 - ZAT - LAG - 2 * wg, 1, p, sb, pitch, wg, leader);
      const uint32_t rbuf = sb + (69 % ST) * pitch + warp * 2304;
      const uint32_t rdst = mapa(rbuf, ro.half ^ 1), rbar = mapa(bars + B_RFULL + wg * 8, ro.half ^ 1);
      pipe_drain(p, bars, leader);
      float cs[36], ck[36];
      split_acc(acc, cs, ck);
      gemm2_part<0, 0, 4 * LAG>(cs, sb, pitch, wg);
      if (KPRE) gemm2_part<72, 0, KPRE>(ck, sb, pitch, wg);
      const float hb0 = fmaf(bf_lo(braw0), 0.5f, __uint_as_float(st0.w)), hb1 = fmaf(bf_lo(braw1), 0.5f, __uint_as_float(st1.w));
      mbar_wait(bars + B_GO, 0);
      wg_wait<KPRE ? 1 : 0>();
#pragma unroll
      for (int i = 0; i < 5; i++) {
        const float* c = &cs[8 * i];
        const uint32_t v0 = pack_bf16(fmaf(c[0], 0.25f, hb0), fmaf(c[1], 0.25f, hb0)), v1 = pack_bf16(fmaf(c[2], 0.25f, hb1), fmaf(c[3], 0.25f, hb1));
        if (i < 4) st_async4(rdst + i * 512 + lane * 16, v0, v1, pack_bf16(fmaf(c[4], 0.25f, hb0), fmaf(c[5], 0.25f, hb0)), pack_bf16(fmaf(c[6], 0.25f, hb1), fmaf(c[7], 0.25f, hb1)), rbar);
        else st_async2(rdst + 2048 + lane * 8, v0, v1, rbar);
      }
      if (wg == 1) named_bar(7, 256);
      gemm2_part<72, KPRE, 4 * LAG>(ck, sb, pitch, wg);
      uint32_t rp[18];
      mbar_wait(bars + B_RFULL + wg * 8, 0);
#pragma unroll
      for (int m = 0; m < 4; m++) {
        const uint4 v = lds128(rbuf + m * 512 + lane * 16);
        rp[4 * m] = v.x; rp[4 * m + 1] = v.y; rp[4 * m + 2] = v.z; rp[4 * m + 3] = v.w;
      }
      { const uint2 v = lds64(rbuf + 2048 + lane * 8); rp[16] = v.x; rp[17] = v.y; }
      __nv_bfloat16* o = out + go;
      wg_wait<0>();
      float h[2][4], t[2][4], half = 0.25f;
#pragma unroll
      for (int j = 0; j <= 9; j++) {
        if (j < 9) {
          const uint32_t ra = rp[2 * j], rb = rp[2 * j + 1];
          if (j >= 2) half = fmaf(t[j & 1][3], 0.f, 0.25f);
          h[j & 1][0] = fmaf(ck[4 * j], half, bf_lo(ra)); h[j & 1][1] = fmaf(ck[4 * j + 1], half, bf_hi(ra));
          h[j & 1][2] = fmaf(ck[4 * j + 2], half, bf_lo(rb)); h[j & 1][3] = fmaf(ck[4 * j + 3], half, bf_hi(rb));
#pragma unroll
          for (int u = 0; u < 4; u++) t[j & 1][u] = tanh_ordered(h[j & 1][u]);
        }
        if (j > 0) {
          const int k = j - 1;
          const float* hh = h[k & 1];
          const float* tt = t[k & 1];
          x[0][k] = hfma2(sg[0][k], pack_bf16(fmaf(hh[0], tt[0], hh[0]), fmaf(hh[1], tt[1], hh[1])), x[0][k]);
          x[1][k] = hfma2(sg[1][k], pack_bf16(fmaf(hh[2], tt[2], hh[2]), fmaf(hh[3], tt[3], hh[3])), x[1][k]);
          if ((k & 3) == 3) {
            *(uint4*)(o + (k >> 2) * 32) = make_uint4(x[0][k - 3], x[0][k - 2], x[0][k - 1], x[0][k]);
            *(uint4*)(o + 8 * D_ + (k >> 2) * 32) = make_uint4(x[1][k - 3], x[1][k - 2], x[1][k - 1], x[1][k]);
          }
        }
      }
      *(uint32_t*)(out + go8) = x[0][8];
      *(uint32_t*)(out + go8 + 8 * D_) = x[1][8];
    }
  }
}

typedef CUresult (*EncodeFn)(CUtensorMap*, CUtensorMapDataType, cuuint32_t, void*, const cuuint64_t*, const cuuint64_t*, const cuuint32_t*,
                             const cuuint32_t*, CUtensorMapInterleave, CUtensorMapSwizzle, CUtensorMapL2promotion, CUtensorMapFloatOOBfill);

uint32_t role_of_pair(int t) {
  int grp, i;
  if (t < 32) { const int j = t & 7; i = t >> 3; grp = j < 6 ? 1 + j : 12 + 2 * (j - 6); }
  else if (t < 60) { const int j = (t - 32) % 7; i = (t - 32) / 7; grp = j < 5 ? 7 + j : 13 + 2 * (j - 5); }
  else if (t < 62) return 2u | (uint32_t)(t - 60) << 2 | (uint32_t)(14 + 3 * (t - 60)) << 8 | 2u << 16;
  else { grp = 0; i = t - 62; }
  if (grp < 12) return (uint32_t)(i << 2 | grp << 4 | grp << 8 | i << 16);
  const int u = (grp & 1) * 4 + i;
  return (uint32_t)(1 | i << 2 | grp << 4 | (12 + 3 * ((grp - 12) >> 1) + u / 3) << 8 | (u % 3) << 16);
}

}

extern "C" void kernel_launch(void* const* d_in, const int* in_sizes, int n_in, void* d_out, int out_size) {
  (void)in_sizes; (void)n_in; (void)out_size;
  EncodeFn enc = nullptr;
  cudaDriverEntryPointQueryResult qr;
  cudaGetDriverEntryPoint("cuTensorMapEncodeTiled", (void**)&enc, cudaEnableDefault, &qr);
  Scratch* gs = nullptr;
  cudaGetSymbolAddress((void**)&gs, g_scratch);
  void *zp = gs->z, *hp = gs->h, *kvp = gs->kv;
  CUtensorMap tmW1, tmW2, tmZ, tmH, tmK, tmV, tmKV, tmKL;
  for (int w = 0; w < 2; w++) {
    cuuint64_t gd[2] = {D_, S_};
    cuuint64_t st[1] = {D_ * 2};
    cuuint32_t bx[2] = {64, w ? 33u : 36u};
    cuuint32_t es[2] = {1, 1};
    enc(w ? &tmV : &tmK, CU_TENSOR_MAP_DATA_TYPE_BFLOAT16, 2, d_in[1 + w], gd, st, bx, es, CU_TENSOR_MAP_INTERLEAVE_NONE, CU_TENSOR_MAP_SWIZZLE_NONE,
        CU_TENSOR_MAP_L2_PROMOTION_L2_128B, CU_TENSOR_MAP_FLOAT_OOB_FILL_NONE);
  }
  {
    cuuint64_t gd[4] = {16, D_ / 2, 2, 128};
    cuuint64_t st[3] = {2 * KVT, KVT, 64};
    cuuint32_t bx[4] = {20, 32, 2, 1};
    cuuint32_t es[4] = {1, 1, 1, 1};
    enc(&tmKV, CU_TENSOR_MAP_DATA_TYPE_UINT32, 4, kvp, gd, st, bx, es, CU_TENSOR_MAP_INTERLEAVE_NONE, CU_TENSOR_MAP_SWIZZLE_NONE,
        CU_TENSOR_MAP_L2_PROMOTION_NONE, CU_TENSOR_MAP_FLOAT_OOB_FILL_NONE);
  }
  {
    cuuint64_t gd[3] = {40, 64, D_};
    cuuint64_t st[2] = {128, KVT};
    cuuint32_t bx[3] = {40, 16, 1};
    cuuint32_t es[3] = {1, 1, 1};
    enc(&tmKL, CU_TENSOR_MAP_DATA_TYPE_UINT32, 3, gs->kv - 32, gd, st, bx, es, CU_TENSOR_MAP_INTERLEAVE_NONE, CU_TENSOR_MAP_SWIZZLE_NONE,
        CU_TENSOR_MAP_L2_PROMOTION_NONE, CU_TENSOR_MAP_FLOAT_OOB_FILL_NONE);
  }
  {
    cuuint64_t gd[3] = {64, 32 * 72, 8};
    cuuint64_t st[2] = {1024, 128};
    cuuint32_t bx[3] = {64, 72, 1};
    cuuint32_t es[3] = {1, 1, 1};
    enc(&tmH, CU_TENSOR_MAP_DATA_TYPE_BFLOAT16, 3, hp, gd, st, bx, es, CU_TENSOR_MAP_INTERLEAVE_NONE, CU_TENSOR_MAP_SWIZZLE_128B,
        CU_TENSOR_MAP_L2_PROMOTION_NONE, CU_TENSOR_MAP_FLOAT_OOB_FILL_NONE);
  }
  for (int w = 0; w < 2; w++) {
    const cuuint64_t M = w ? S_ : F_, K = w ? F_ : S_;
    cuuint64_t gd[3] = {64, K, M / 64};
    cuuint64_t st[2] = {M * 2, 128};
    cuuint32_t bx[3] = {64, 64, 2};
    cuuint32_t es[3] = {1, 1, 1};
    enc(w ? &tmW2 : &tmW1, CU_TENSOR_MAP_DATA_TYPE_BFLOAT16, 3, d_in[w ? 9 : 7], gd, st, bx, es, CU_TENSOR_MAP_INTERLEAVE_NONE,
        CU_TENSOR_MAP_SWIZZLE_128B, CU_TENSOR_MAP_L2_PROMOTION_L2_256B, CU_TENSOR_MAP_FLOAT_OOB_FILL_NONE);
  }
  {
    cuuint64_t gd[2] = {S_, D_};
    cuuint64_t st[1] = {S_ * 2};
    cuuint32_t bx[2] = {64, 72};
    cuuint32_t es[2] = {1, 1};
    enc(&tmZ, CU_TENSOR_MAP_DATA_TYPE_BFLOAT16, 2, zp, gd, st, bx, es, CU_TENSOR_MAP_INTERLEAVE_NONE, CU_TENSOR_MAP_SWIZZLE_128B,
        CU_TENSOR_MAP_L2_PROMOTION_L2_256B, CU_TENSOR_MAP_FLOAT_OOB_FILL_NONE);
  }
  RoleMap roles;
  int dev = 0, sms = 0;
  cudaGetDevice(&dev);
  cudaDeviceGetAttribute(&sms, cudaDevAttrMultiProcessorCount, dev);
  roles.by_sm = sms == NCTA;
  for (int k = 0; k < NCTA / 2; k++) roles.role[k] = role_of_pair(k);
  cudaFuncSetAttribute(fused_kernel, cudaFuncAttributeMaxDynamicSharedMemorySize, SMEM_BYTES);
  fused_kernel<<<NCTA, 384, SMEM_BYTES>>>((const __nv_bfloat16*)d_in[0], gs, (const __nv_bfloat16*)d_in[8], (const __nv_bfloat16*)d_in[3],
                                          (const __nv_bfloat16*)d_in[4], (const __nv_bfloat16*)d_in[5], tmW1, tmW2, tmZ, tmH, tmK, tmV, tmKV, tmKL,
                                          roles, (const __nv_bfloat16*)d_in[10], (__nv_bfloat16*)d_out);
}
```

```cpp
#include <cuda_runtime.h>
#include <cuda_bf16.h>
#include <cuda.h>
#include <stdint.h>

namespace {

constexpr int S_ = 2048, D_ = 576, F_ = 4608;
constexpr int NCTA = 132, NG2 = 128;
constexpr int ST = 5, ASZ = 16384, PITCH_S = ASZ + 144 * 128, PITCH_B = ASZ + 192 * 128;
constexpr int CBUF = 14464, CH_OFF = 128, CT_OFF = 4224, KVT = 8192;
constexpr int KVIN = (36 + 33) * 128, KVW = 2 * CBUF;
constexpr int BAR_OFF = ST * PITCH_S + 2 * KVW;
constexpr int SMEM_BYTES = BAR_OFF + 512;
constexpr int LEAD_S = 4, LEAD_B = 3;
constexpr int PRE0 = 1;
constexpr int GLAG = 4;
constexpr int CTURN = 14, CPER = 4;
constexpr int XAT = 12, ZAT = 25;
constexpr int SKEW = 1;
constexpr int LAG = 4;
constexpr int KPRE = 2, TURN = 4;
constexpr int LNROT = 120;
constexpr int QLATE = 40, QDELAY = 400, QRAMP = 5;
constexpr int W9 = 1200;
constexpr int A0 = 1200, AD = 300, AN = 2, AL = 1500;
constexpr int H0 = 3100, HD = 400, HW = 4200;
constexpr int HS2 = 8, LK1 = 7, LK2 = 14, KVGO = 6, KVGO1 = 10, CVGO = 31;
constexpr int BLK_NS = 336, GDELAY = 1280, GBIG = 960, GDELAY1 = 128, ZRAMP = 30;
constexpr uint32_t SPIN_LIMIT = 1u << 22;

constexpr int FL_H = 0, FL_U = 3, FL_KV = 8, FL_Z = 11, FL_GATE = 12, FL_DONE = 13, FL_N = 14;
struct Scratch {
  uint32_t flags[64 * 32];
  uint4 stats[S_];
  uint8_t h[32 * 72 * 1024];
  uint8_t u[72 * D_ * 128];
  uint8_t kv[D_ * KVT];
  __nv_bfloat16 z[D_ * S_];
};
__device__ __align__(1024) Scratch g_scratch;
extern __shared__ __align__(1024) uint8_t smem_raw[];
enum { M_W1, M_H, M_K, M_V, M_KV, M_KL, M_W2, M_Z, M_N };
struct Maps { CUtensorMap m[M_N]; };
struct RoleMap { uint32_t role[NCTA / 2]; uint32_t by_sm; };

template<int TB> __device__ __forceinline__ void wgmma_ss(float (&d)[96], uint32_t da, uint32_t db, int sd) {
  asm volatile("{\n.reg .pred p;\n.reg .b64 a, b;\nsetp.ne.b32 p, %98, 0;\nmov.b64 a, {%96, %100};\nmov.b64 b, {%97, %101};\n"
    "wgmma.mma_async.sync.aligned.m64n192k16.f32.bf16.bf16 {%0, %1, %2, %3, %4, %5, %6, %7, %8, %9, %10, %11, %12, %13, %14, %15, %16, %17, %18, %19, %20, %21, %22, %23, %24, %25, %26, %27, %28, %29, %30, %31, %32, %33, %34, %35, %36, %37, %38, %39, %40, %41, %42, %43, %44, %45, %46, %47, %48, %49, %50, %51, %52, %53, %54, %55, %56, %57, %58, %59, %60, %61, %62, %63, %64, %65, %66, %67, %68, %69, %70, %71, %72, %73, %74, %75, %76, %77, %78, %79, %80, %81, %82, %83, %84, %85, %86, %87, %88, %89, %90, %91, %92, %93, %94, %95}, a, b, p, 1, 1, 1, %99;\n}\n"
    : "+f"(d[0]), "+f"(d[1]), "+f"(d[2]), "+f"(d[3]), "+f"(d[4]), "+f"(d[5]), "+f"(d[6]), "+f"(d[7]), "+f"(d[8]), "+f"(d[9]), "+f"(d[10]), "+f"(d[11]), "+f"(d[12]), "+f"(d[13]), "+f"(d[14]), "+f"(d[15]), "+f"(d[16]), "+f"(d[17]), "+f"(d[18]), "+f"(d[19]), "+f"(d[20]), "+f"(d[21]), "+f"(d[22]), "+f"(d[23]), "+f"(d[24]), "+f"(d[25]), "+f"(d[26]), "+f"(d[27]), "+f"(d[28]), "+f"(d[29]), "+f"(d[30]), "+f"(d[31]), "+f"(d[32]), "+f"(d[33]), "+f"(d[34]), "+f"(d[35]), "+f"(d[36]), "+f"(d[37]), "+f"(d[38]), "+f"(d[39]), "+f"(d[40]), "+f"(d[41]), "+f"(d[42]), "+f"(d[43]), "+f"(d[44]), "+f"(d[45]), "+f"(d[46]), "+f"(d[47]), "+f"(d[48]), "+f"(d[49]), "+f"(d[50]), "+f"(d[51]), "+f"(d[52]), "+f"(d[53]), "+f"(d[54]), "+f"(d[55]), "+f"(d[56]), "+f"(d[57]), "+f"(d[58]), "+f"(d[59]), "+f"(d[60]), "+f"(d[61]), "+f"(d[62]), "+f"(d[63]), "+f"(d[64]), "+f"(d[65]), "+f"(d[66]), "+f"(d[67]), "+f"(d[68]), "+f"(d[69]), "+f"(d[70]), "+f"(d[71]), "+f"(d[72]), "+f"(d[73]), "+f"(d[74]), "+f"(d[75]), "+f"(d[76]), "+f"(d[77]), "+f"(d[78]), "+f"(d[79]), "+f"(d[80]), "+f"(d[81]), "+f"(d[82]), "+f"(d[83]), "+f"(d[84]), "+f"(d[85]), "+f"(d[86]), "+f"(d[87]), "+f"(d[88]), "+f"(d[89]), "+f"(d[90]), "+f"(d[91]), "+f"(d[92]), "+f"(d[93]), "+f"(d[94]), "+f"(d[95])
    : "r"(da), "r"(db), "r"(sd), "n"(TB), "r"(0x40000040u), "r"(TB ? 0x40u : 0x40000040u));
}
template<int TB> __device__ __forceinline__ void wgmma_ss(float (&d)[72], uint32_t da, uint32_t db, int sd) {
  asm volatile("{\n.reg .pred p;\n.reg .b64 a, b;\nsetp.ne.b32 p, %74, 0;\nmov.b64 a, {%72, %76};\nmov.b64 b, {%73, %77};\n"
    "wgmma.mma_async.sync.aligned.m64n144k16.f32.bf16.bf16 {%0, %1, %2, %3, %4, %5, %6, %7, %8, %9, %10, %11, %12, %13, %14, %15, %16, %17, %18, %19, %20, %21, %22, %23, %24, %25, %26, %27, %28, %29, %30, %31, %32, %33, %34, %35, %36, %37, %38, %39, %40, %41, %42, %43, %44, %45, %46, %47, %48, %49, %50, %51, %52, %53, %54, %55, %56, %57, %58, %59, %60, %61, %62, %63, %64, %65, %66, %67, %68, %69, %70, %71}, a, b, p, 1, 1, 1, %75;\n}\n"
    : "+f"(d[0]), "+f"(d[1]), "+f"(d[2]), "+f"(d[3]), "+f"(d[4]), "+f"(d[5]), "+f"(d[6]), "+f"(d[7]), "+f"(d[8]), "+f"(d[9]), "+f"(d[10]), "+f"(d[11]), "+f"(d[12]), "+f"(d[13]), "+f"(d[14]), "+f"(d[15]), "+f"(d[16]), "+f"(d[17]), "+f"(d[18]), "+f"(d[19]), "+f"(d[20]), "+f"(d[21]), "+f"(d[22]), "+f"(d[23]), "+f"(d[24]), "+f"(d[25]), "+f"(d[26]), "+f"(d[27]), "+f"(d[28]), "+f"(d[29]), "+f"(d[30]), "+f"(d[31]), "+f"(d[32]), "+f"(d[33]), "+f"(d[34]), "+f"(d[35]), "+f"(d[36]), "+f"(d[37]), "+f"(d[38]), "+f"(d[39]), "+f"(d[40]), "+f"(d[41]), "+f"(d[42]), "+f"(d[43]), "+f"(d[44]), "+f"(d[45]), "+f"(d[46]), "+f"(d[47]), "+f"(d[48]), "+f"(d[49]), "+f"(d[50]), "+f"(d[51]), "+f"(d[52]), "+f"(d[53]), "+f"(d[54]), "+f"(d[55]), "+f"(d[56]), "+f"(d[57]), "+f"(d[58]), "+f"(d[59]), "+f"(d[60]), "+f"(d[61]), "+f"(d[62]), "+f"(d[63]), "+f"(d[64]), "+f"(d[65]), "+f"(d[66]), "+f"(d[67]), "+f"(d[68]), "+f"(d[69]), "+f"(d[70]), "+f"(d[71])
    : "r"(da), "r"(db), "r"(sd), "n"(TB), "r"(0x40000040u), "r"(TB ? 0x40u : 0x40000040u));
}
template<int TB> __device__ __forceinline__ void wgmma_ss(float (&d)[36], uint32_t da, uint32_t db, int sd) {
  asm volatile("{\n.reg .pred p;\n.reg .b64 a, b;\nsetp.ne.b32 p, %38, 0;\nmov.b64 a, {%36, %40};\nmov.b64 b, {%37, %41};\n"
    "wgmma.mma_async.sync.aligned.m64n72k16.f32.bf16.bf16 {%0, %1, %2, %3, %4, %5, %6, %7, %8, %9, %10, %11, %12, %13, %14, %15, %16, %17, %18, %19, %20, %21, %22, %23, %24, %25, %26, %27, %28, %29, %30, %31, %32, %33, %34, %35}, a, b, p, 1, 1, 1, %39;\n}\n"
    : "+f"(d[0]), "+f"(d[1]), "+f"(d[2]), "+f"(d[3]), "+f"(d[4]), "+f"(d[5]), "+f"(d[6]), "+f"(d[7]), "+f"(d[8]), "+f"(d[9]), "+f"(d[10]), "+f"(d[11]), "+f"(d[12]), "+f"(d[13]), "+f"(d[14]), "+f"(d[15]), "+f"(d[16]), "+f"(d[17]), "+f"(d[18]), "+f"(d[19]), "+f"(d[20]), "+f"(d[21]), "+f"(d[22]), "+f"(d[23]), "+f"(d[24]), "+f"(d[25]), "+f"(d[26]), "+f"(d[27]), "+f"(d[28]), "+f"(d[29]), "+f"(d[30]), "+f"(d[31]), "+f"(d[32]), "+f"(d[33]), "+f"(d[34]), "+f"(d[35])
    : "r"(da), "r"(db), "r"(sd), "n"(TB), "r"(0x40000040u), "r"(TB ? 0x40u : 0x40000040u));
}
__device__ __forceinline__ void wgmma_rs_n32(float (&d)[16], uint32_t a0, uint32_t a1, uint32_t a2, uint32_t a3, uint64_t db, int sd) {
  asm volatile("{\n.reg .pred p;\nsetp.ne.b32 p, %21, 0;\n"
    "wgmma.mma_async.sync.aligned.m64n32k16.f32.bf16.bf16 {%0, %1, %2, %3, %4, %5, %6, %7, %8, %9, %10, %11, %12, %13, %14, %15}, {%16, %17, %18, %19}, %20, p, 1, 1, 0;\n}\n"
    : "+f"(d[0]), "+f"(d[1]), "+f"(d[2]), "+f"(d[3]), "+f"(d[4]), "+f"(d[5]), "+f"(d[6]), "+f"(d[7]), "+f"(d[8]), "+f"(d[9]), "+f"(d[10]), "+f"(d[11]), "+f"(d[12]), "+f"(d[13]), "+f"(d[14]), "+f"(d[15])
    : "r"(a0), "r"(a1), "r"(a2), "r"(a3), "l"(db), "r"(sd));
}

__device__ __forceinline__ void wg_fence() { asm volatile("wgmma.fence.sync.aligned;" ::: "memory"); }
__device__ __forceinline__ void wg_commit() { asm volatile("wgmma.commit_group.sync.aligned;" ::: "memory"); }
template <int n> __device__ __forceinline__ void wg_wait() { asm volatile("wgmma.wait_group.sync.aligned %0;" ::"n"(n) : "memory"); }
__device__ __forceinline__ uint64_t mkdesc(uint32_t addr, uint32_t lbo, uint32_t sbo, uint32_t sw) {
  return (uint64_t)((addr & 0x3FFFF) >> 4) | ((uint64_t)(lbo >> 4) << 16) | ((uint64_t)(sbo >> 4) << 32) | ((uint64_t)sw << 62);
}
__device__ __forceinline__ void mbar_init(uint32_t a, int c) { asm volatile("mbarrier.init.shared::cta.b64 [%0], %1;" ::"r"(a), "r"(c)); }
__device__ __forceinline__ void mbar_expect(uint32_t a, uint32_t b) { asm volatile("mbarrier.arrive.expect_tx.shared::cta.b64 _, [%0], %1;" ::"r"(a), "r"(b) : "memory"); }
__device__ __forceinline__ void mbar_arrive(uint32_t a) { asm volatile("mbarrier.arrive.shared::cta.b64 _, [%0];" ::"r"(a) : "memory"); }
__device__ __forceinline__ void mbar_arrive_cluster(uint32_t raddr) { asm volatile("mbarrier.arrive.shared::cluster.b64 _, [%0];" ::"r"(raddr) : "memory"); }
__device__ __forceinline__ uint32_t mapa(uint32_t a, uint32_t cta) { uint32_t r; asm("mapa.shared::cluster.u32 %0, %1, %2;" : "=r"(r) : "r"(a), "r"(cta)); return r; }
__device__ __forceinline__ void mbar_wait(uint32_t a, uint32_t ph) {
  asm volatile(
      "{\n.reg .pred p;\n.reg .u32 c;\nmov.u32 c, 0;\n"
      "WAIT_LOOP:\nmbarrier.try_wait.parity.shared::cta.b64 p, [%0], %1;\n@p bra WAIT_DONE;\n"
      "add.u32 c, c, 1;\nsetp.lt.u32 p, c, %2;\n@p bra WAIT_LOOP;\ntrap;\nWAIT_DONE:\n}" ::"r"(a), "r"(ph), "n"(SPIN_LIMIT) : "memory");
}
__device__ __forceinline__ void mbar_wait_u(uint32_t a, uint32_t ph) {
  asm volatile("{\n.reg .pred p;\nWAIT_LOOP:\nmbarrier.try_wait.parity.shared::cta.b64 p, [%0], %1;\n@!p bra WAIT_LOOP;\n}" ::"r"(a), "r"(ph) : "memory");
}
__device__ __forceinline__ uint32_t desc_lo(uint32_t addr, uint32_t lbo) { return ((addr & 0x3FFFF) >> 4) | ((lbo >> 4) << 16); }
__device__ __forceinline__ void tma2d(uint32_t dst, const CUtensorMap* m, int c0, int c1, uint32_t bar) {
  asm volatile("cp.async.bulk.tensor.2d.shared::cluster.global.mbarrier::complete_tx::bytes [%0], [%1, {%3, %4}], [%2];" ::"r"(dst), "l"(m), "r"(bar), "r"(c0), "r"(c1) : "memory");
}
__device__ __forceinline__ void bulk_g2s(uint32_t dst, const void* src, uint32_t sz, uint32_t bar) {
  asm volatile("cp.async.bulk.shared::cluster.global.mbarrier::complete_tx::bytes [%0], [%1], %2, [%3];" ::"r"(dst), "l"(src), "r"(sz), "r"(bar) : "memory");
}
__device__ __forceinline__ void bulk_s2g(void* dst, uint32_t src, uint32_t sz) {
  asm volatile("cp.async.bulk.global.shared::cta.bulk_group [%0], [%1], %2;" ::"l"(dst), "r"(src), "r"(sz) : "memory");
}
__device__ __forceinline__ uint64_t stream_policy() {
  uint64_t p;
  asm volatile("createpolicy.fractional.L2::evict_first.b64 %0, 1.0;" : "=l"(p));
  return p;
}
__device__ __forceinline__ void tma_weights(uint32_t dst, const CUtensorMap* m, int k0, int mchunk, uint32_t bar, uint64_t pol) {
  asm volatile("cp.async.bulk.tensor.3d.shared::cluster.global.mbarrier::complete_tx::bytes.L2::cache_hint [%0], [%1, {%6, %3, %4}], [%2], %5;"
               ::"r"(dst), "l"(m), "r"(bar), "r"(k0), "r"(mchunk), "l"(pol), "r"(0) : "memory");
}
__device__ __forceinline__ void tma_weights_prefetch(const CUtensorMap* m, int k0, int mchunk, uint64_t pol) {
  asm volatile("cp.async.bulk.prefetch.tensor.3d.L2.global.L2::cache_hint [%0, {%4, %1, %2}], %3;" ::"l"(m), "r"(k0), "r"(mchunk), "l"(pol), "r"(0) : "memory");
}
__device__ __forceinline__ bool elect_one() {
  uint32_t p;
  asm volatile("{\n.reg .pred P;\nelect.sync _|P, 0xffffffff;\nselp.u32 %0, 1, 0, P;\n}" : "=r"(p));
  return p;
}
__device__ __forceinline__ void bulk_g2s_stream(uint32_t dst, const void* src, uint32_t sz, uint32_t bar, uint64_t pol) {
  asm volatile("cp.async.bulk.shared::cluster.global.mbarrier::complete_tx::bytes.L2::cache_hint [%0], [%1], %2, [%3], %4;"
               ::"r"(dst), "l"(src), "r"(sz), "r"(bar), "l"(pol) : "memory");
}
__device__ __forceinline__ void tma3d_store(const CUtensorMap* m, int c1, int c2, uint32_t src) {
  asm volatile("cp.async.bulk.tensor.3d.global.shared::cta.bulk_group [%0, {%4, %2, %3}], [%1];" ::"l"(m), "r"(src), "r"(c1), "r"(c2), "r"(0) : "memory");
}
__device__ __forceinline__ void tma2d_stream(uint32_t dst, const CUtensorMap* m, int c0, int c1, uint32_t bar, uint64_t pol) {
  asm volatile("cp.async.bulk.tensor.2d.shared::cluster.global.mbarrier::complete_tx::bytes.L2::cache_hint [%0], [%1, {%3, %4}], [%2], %5;"
               ::"r"(dst), "l"(m), "r"(bar), "r"(c0), "r"(c1), "l"(pol) : "memory");
}
__device__ __forceinline__ void tma4d_store(const CUtensorMap* m, int c1, int c2, int c3, uint32_t src) {
  asm volatile("cp.async.bulk.tensor.4d.global.shared::cta.bulk_group [%0, {%5, %2, %3, %4}], [%1];" ::"l"(m), "r"(src), "r"(c1), "r"(c2), "r"(c3), "r"(0) : "memory");
}
__device__ __forceinline__ void bulk_commit() { asm volatile("cp.async.bulk.commit_group;" ::: "memory"); }
__device__ __forceinline__ void bulk_wait_all() { asm volatile("cp.async.bulk.wait_group 0;" ::: "memory"); }
__device__ __forceinline__ void fence_async_smem() { asm volatile("fence.proxy.async.shared::cta;" ::: "memory"); }
__device__ __forceinline__ void fence_async_global() { asm volatile("fence.proxy.async.global;" ::: "memory"); }
__device__ __forceinline__ void named_bar(int id, int n) { asm volatile("bar.sync %0, %1;" ::"r"(id), "r"(n) : "memory"); }
__device__ __forceinline__ void named_arrive(int id, int n) { asm volatile("bar.arrive %0, %1;" ::"r"(id), "r"(n) : "memory"); }
__device__ __forceinline__ void flag_add(uint32_t* f, int i, uint32_t v) { asm volatile("red.relaxed.gpu.global.add.u32 [%0], %1;" ::"l"(f + i * 32), "r"(v) : "memory"); }
__device__ __forceinline__ uint32_t flag_ld(uint32_t* f, int i) { uint32_t v; asm volatile("ld.relaxed.gpu.global.u32 %0, [%1];" : "=r"(v) : "l"(f + i * 32) : "memory"); return v; }
__device__ __forceinline__ void prefetch_map(const CUtensorMap* m) { asm volatile("prefetch.tensormap [%0];" ::"l"(m) : "memory"); }
__device__ __forceinline__ void stsm4_t(uint32_t a, uint32_t r0, uint32_t r1, uint32_t r2, uint32_t r3) {
  asm volatile("stmatrix.sync.aligned.m8n8.x4.trans.shared.b16 [%0], {%1, %2, %3, %4};" ::"r"(a), "r"(r0), "r"(r1), "r"(r2), "r"(r3) : "memory");
}
__device__ __forceinline__ uint32_t lds32(uint32_t a) { uint32_t v; asm volatile("ld.shared.u32 %0, [%1];" : "=r"(v) : "r"(a) : "memory"); return v; }
__device__ __forceinline__ void sts32(uint32_t a, uint32_t v) { asm volatile("st.shared.u32 [%0], %1;" ::"r"(a), "r"(v) : "memory"); }
__device__ __forceinline__ uint4 ld_l2(const uint4* p) { uint4 v; asm volatile("ld.relaxed.gpu.global.v4.u32 {%0, %1, %2, %3}, [%4];" : "=r"(v.x), "=r"(v.y), "=r"(v.z), "=r"(v.w) : "l"(p) : "memory"); return v; }
__device__ __forceinline__ void sts128(uint32_t a, uint32_t x, uint32_t y, uint32_t z, uint32_t w) { asm volatile("st.shared.v4.u32 [%0], {%1, %2, %3, %4};" ::"r"(a), "r"(x), "r"(y), "r"(z), "r"(w) : "memory"); }
__device__ __forceinline__ uint4 lds128(uint32_t a) { uint4 v; asm volatile("ld.shared.v4.u32 {%0, %1, %2, %3}, [%4];" : "=r"(v.x), "=r"(v.y), "=r"(v.z), "=r"(v.w) : "r"(a) : "memory"); return v; }
__device__ __forceinline__ void st_async4(uint32_t raddr, uint32_t a, uint32_t b, uint32_t c, uint32_t d, uint32_t rbar) {
  asm volatile("st.async.weak.shared::cluster.mbarrier::complete_tx::bytes.v4.b32 [%0], {%1, %2, %3, %4}, [%5];" ::"r"(raddr), "r"(a), "r"(b), "r"(c), "r"(d), "r"(rbar) : "memory");
}
__device__ __forceinline__ uint32_t pack_bf16(float lo, float hi) { uint32_t r; asm("cvt.rn.bf16x2.f32 %0, %1, %2;" : "=r"(r) : "f"(hi), "f"(lo)); return r; }
__device__ __forceinline__ float bf_lo(uint32_t v) { return __uint_as_float(v << 16); }
__device__ __forceinline__ float bf_hi(uint32_t v) { return __uint_as_float(v & 0xffff0000u); }
__device__ __forceinline__ float bf_round(float x) { return bf_lo(pack_bf16(x, 0.f)); }
__device__ __forceinline__ uint32_t hmul2(uint32_t a, uint32_t b) { uint32_t r; asm("mul.rn.bf16x2 %0, %1, %2;" : "=r"(r) : "r"(a), "r"(b)); return r; }
__device__ __forceinline__ uint32_t hsub2(uint32_t a, uint32_t b) { uint32_t r; asm("sub.rn.bf16x2 %0, %1, %2;" : "=r"(r) : "r"(a), "r"(b)); return r; }
__device__ __forceinline__ uint32_t hfma2(uint32_t a, uint32_t b, uint32_t c) { uint32_t r; asm("fma.rn.bf16x2 %0, %1, %2, %3;" : "=r"(r) : "r"(a), "r"(b), "r"(c)); return r; }
__device__ __forceinline__ uint4 ldg128(const void* p) { uint4 v; asm volatile("ld.global.nc.v4.u32 {%0, %1, %2, %3}, [%4];" : "=r"(v.x), "=r"(v.y), "=r"(v.z), "=r"(v.w) : "l"(p)); return v; }
__device__ __forceinline__ uint32_t ldg16(const void* p) { uint32_t v; asm volatile("ld.global.nc.u16 %0, [%1];" : "=r"(v) : "l"(p)); return v; }
__device__ __forceinline__ float tanh_ordered(float x) { float y; asm volatile("tanh.approx.f32 %0, %1;" : "=f"(y) : "f"(x)); return y; }
__device__ __forceinline__ uint32_t tanh2_ordered(uint32_t x) { uint32_t y; asm volatile("tanh.approx.bf16x2 %0, %1;" : "=r"(y) : "r"(x)); return y; }
__device__ __forceinline__ void mma16816(float (&d)[4], uint32_t a0, uint32_t a1, uint32_t a2, uint32_t a3, uint32_t b0, uint32_t b1) {
  asm("mma.sync.aligned.m16n8k16.row.col.f32.bf16.bf16.f32 {%0, %1, %2, %3}, {%4, %5, %6, %7}, {%8, %9}, {%0, %1, %2, %3};"
      : "+f"(d[0]), "+f"(d[1]), "+f"(d[2]), "+f"(d[3]) : "r"(a0), "r"(a1), "r"(a2), "r"(a3), "r"(b0), "r"(b1));
}
__device__ __forceinline__ uint32_t hadd2(uint32_t a, uint32_t b) { uint32_t r; asm("add.rn.bf16x2 %0, %1, %2;" : "=r"(r) : "r"(a), "r"(b)); return r; }
__device__ __forceinline__ uint32_t ldg32(const void* p) { uint32_t v; asm volatile("ld.global.nc.L1::no_allocate.u32 %0, [%1];" : "=r"(v) : "l"(p)); return v; }
__device__ __forceinline__ uint2 lds64(uint32_t a) { uint2 v; asm volatile("ld.shared.v2.u32 {%0, %1}, [%2];" : "=r"(v.x), "=r"(v.y) : "r"(a) : "memory"); return v; }
__device__ __forceinline__ uint32_t lds32_if(uint32_t a, uint32_t on) {
  uint32_t v;
  asm volatile("{\n.reg .pred p;\nsetp.ne.u32 p, %2, 0;\n@p ld.shared.u32 %0, [%1];\n}" : "=r"(v) : "r"(a), "r"(on) : "memory");
  return v;
}
__device__ __forceinline__ uint32_t clock_now() { uint32_t t; asm volatile("mov.u32 %0, %%clock;" : "=r"(t)); return t; }
__device__ __forceinline__ uint32_t time_now() { uint32_t t; asm volatile("mov.u32 %0, %%globaltimer_lo;" : "=r"(t)); return t; }
__device__ __forceinline__ void spin_until(uint32_t t0, uint32_t n) { while (clock_now() - t0 < n) {} }
__device__ __forceinline__ uint2 ldg64_if(const void* p, uint32_t on) {
  uint2 v;
  asm volatile("{\n.reg .pred p;\nsetp.ne.u32 p, %3, 0;\n@p ld.global.nc.v2.u32 {%0, %1}, [%2];\n}" : "=r"(v.x), "=r"(v.y) : "l"(p), "r"(on));
  return v;
}
template <class T> __device__ __forceinline__ T pin(T v) { asm volatile("" : "+r"(v)); return v; }
__device__ __forceinline__ void st_async2(uint32_t raddr, uint32_t a, uint32_t b, uint32_t rbar) {
  asm volatile("st.async.weak.shared::cluster.mbarrier::complete_tx::bytes.v2.b32 [%0], {%1, %2}, [%3];" ::"r"(raddr), "r"(a), "r"(b), "r"(rbar) : "memory");
}
__device__ __forceinline__ void bulk_prefetch(const void* src, uint32_t sz, uint64_t pol) {
  asm volatile("cp.async.bulk.prefetch.L2.global.L2::cache_hint [%0], %1, %2;" ::"l"(src), "r"(sz), "l"(pol) : "memory");
}
__device__ __forceinline__ void bulk_wait_read() { asm volatile("cp.async.bulk.wait_group.read 0;" ::: "memory"); }
__device__ __forceinline__ uint32_t shfl_ordered(uint32_t v, int src) { uint32_t r; asm volatile("shfl.sync.idx.b32 %0, %1, %2, 0x1f, 0xffffffff;" : "=r"(r) : "r"(v), "r"(src)); return r; }
__device__ __forceinline__ int chan_pos(int d) {
  return d < 512 ? 72 * (d >> 6) + ((d & 33) | ((d & 6) << 2) | ((d >> 2) & 6)) : 72 * ((d - 512) >> 3) + 64 + (d & 7);
}

struct Ring {
  uint32_t s, ph;
  __device__ __forceinline__ void next() { if (++s == ST) { s = 0; ph ^= 1; } }
};
constexpr int B_FULL = 0, B_GO = 40, B_CFULL = 48, B_SEMPTY = 80, B_ZFULL = 96, B_RFULL = 104, B_UDONE = 120, B_KFULL = 136, B_RAW = 168, B_CVGO = 248, B_PEER = 256, B_G2GO = 264, B_KVGO = 280,
              B_EMPTY = 296, B_G1DONE = 336,
              B_CEMPTY = 344, B_SFULL = 376, B_USTG = 392, B_END = 408;

static_assert((B_EMPTY - B_GO) % 16 == 0 && (B_CEMPTY - B_EMPTY) % 16 == 0 && (B_END - B_CEMPTY) % 16 == 0, "barrier groups");

__device__ __forceinline__ void wait_counter(uint32_t* f, int idx, uint32_t want, uint32_t first, uint32_t nap) {
#pragma unroll 1
  for (uint32_t spins = 0; first != want; spins++) {
    if (nap && spins) __nanosleep(nap);
    first = flag_ld(f, idx);
    if (spins > SPIN_LIMIT) asm volatile("trap;");
  }
  fence_async_global();
}

__device__ __forceinline__ void gate_arrive(uint32_t* f, uint32_t back) {
  asm volatile("red.relaxed.gpu.global.max.u32 [%0], %1;" ::"l"(f + FL_GATE * 32 + 1), "r"(time_now() - back) : "memory");
  flag_add(f, FL_GATE, 1);
}

__device__ __forceinline__ float ln_rinv(float var) {
  float rt, rinv;
  asm("sqrt.approx.ftz.f32 %0, %1;" : "=f"(rt) : "f"(bf_round(bf_round(var) + 1e-5f)));
  asm("rcp.approx.ftz.f32 %0, %1;" : "=f"(rinv) : "f"(bf_round(rt)));
  return rinv;
}
__device__ __forceinline__ uint32_t ln_apply(uint32_t x, const uint4& st) {
  const uint32_t d = hsub2(x, st.x);
  return hfma2(d, st.y, hmul2(d, st.z));
}

__device__ __forceinline__ void polling_done(uint32_t* f, int lane) {
  unsigned old = 0;
  if (elect_one()) asm volatile("atom.relaxed.gpu.global.inc.u32 %0, [%1], 0xffff;" : "=r"(old) : "l"(f + FL_DONE * 32) : "memory");
  if (__any_sync(0xffffffffu, old == 2 * NCTA - 1)) {
    if (lane < FL_N) *(uint2*)(f + lane * 32) = make_uint2(0u, 0u);
  }
}

struct Pipe { Ring r; uint32_t prev; bool pending; };
__device__ __forceinline__ void pipe_drain(Pipe& p, uint32_t bars, bool leader) {
  wg_wait<0>();
  if (leader) mbar_arrive(bars + B_EMPTY + p.prev * 8);
  p.pending = false;
}
template <int TB, int LEAD, int R>
__device__ __forceinline__ void gemm_run(float (&acc)[R], int n, int accumulate, Pipe& p, uint32_t sb, uint32_t pitch, int wg, bool leader) {
  const uint32_t bars = sb + BAR_OFF;
  const uint32_t dA0 = desc_lo(sb + wg * 8192, 8192), dB0 = desc_lo(sb + ASZ, TB ? 128 : 16);
  constexpr int KB_STEP = TB ? 16 : 2;
#pragma unroll 1
  for (int kb = 0; kb < n; kb++) {
    if (LEAD && kb == n - LEAD && wg == 1) { if (TB) pipe_drain(p, bars, leader); named_bar(8, 256); }
    mbar_wait(bars + B_FULL + p.r.s * 8, p.r.ph);
    const uint32_t dA = dA0 + p.r.s * (pitch >> 4), dB = dB0 + p.r.s * (pitch >> 4);
    wg_fence();
    wgmma_ss<TB>(acc, dA, dB, accumulate | kb);
#pragma unroll
    for (int k = 1; k < 4; k++) wgmma_ss<TB>(acc, dA + k * 128, dB + k * KB_STEP, 1);
    wg_commit();
    wg_wait<1>();
    if (p.pending && leader) mbar_arrive(bars + B_EMPTY + p.prev * 8);
    p.pending = true;
    p.prev = p.r.s;
    p.r.next();
  }
  if (LEAD && wg == 0) named_arrive(8, 256);
}

template <int BROW0, int I0, int I1>
__device__ __forceinline__ void gemm2_part(float (&c)[36], uint32_t sb, uint32_t pitch, int wg) {
  const uint32_t dA0 = desc_lo(sb + wg * 8192, 8192), dB0 = desc_lo(sb + ASZ + BROW0 * 128, 16);
  wg_fence();
#pragma unroll
  for (int i = I0; i < I1; i++) {
    const int step = 69 - LAG + (i >> 2);
    if ((i & 3) == 0 && BROW0 == 0) mbar_wait_u(sb + BAR_OFF + B_FULL + (step % ST) * 8, (step / ST) & 1);
    if (i == 4 * LAG - TURN && BROW0 && wg == 0) named_arrive(7, 256);
    wgmma_ss<0>(c, dA0 + (step % ST) * (pitch >> 4) + (i & 3) * 128, dB0 + (step % ST) * (pitch >> 4) + (i & 3) * 2, 1);
  }
  wg_commit();
}
__device__ __forceinline__ void split_acc(const float (&acc)[72], float (&a)[36], float (&b)[36]) {
#pragma unroll
  for (int i = 0; i < 36; i++) { asm volatile("mov.b32 %0, %1;" : "=f"(a[i]) : "f"(acc[i])); asm volatile("mov.b32 %0, %1;" : "=f"(b[i]) : "f"(acc[36 + i])); }
}
template <int V0, int V1, int R, class Slice>
__device__ __forceinline__ void gelu_store(const float (&acc)[R], uint32_t bias0, uint32_t bias1, uint32_t sa, uint32_t zero, Slice slice) {
  const uint32_t bb[2] = {pin(bias0) * 0x10001u, pin(bias1) * 0x10001u};
  uint32_t x[2][4], t[2][4], dep[V1 / 8], c3 = 0x3d123d12u;
#pragma unroll
  for (int j = V0 / 8; j <= V1 / 8; j++) {
    if (j < V1 / 8) {
      if (j >= V0 / 8 + GLAG) c3 = (dep[j - GLAG] & zero) | 0x3d123d12u;
#pragma unroll
      for (int u = 0; u < 4; u++) {
        x[j & 1][u] = hadd2(pack_bf16(acc[8 * j + 2 * u], acc[8 * j + 2 * u + 1]), bb[u & 1]);
        t[j & 1][u] = tanh2_ordered(hmul2(x[j & 1][u], hfma2(hmul2(x[j & 1][u], c3), x[j & 1][u], 0x3f4c3f4cu)));
      }
    }
    if (j > V0 / 8) {
      const uint32_t *xx = x[(j - 1) & 1], *tt = t[(j - 1) & 1];
      stsm4_t(sa + (j - 1) * 2048, hfma2(xx[0], tt[0], xx[0]), hfma2(xx[1], tt[1], xx[1]), hfma2(xx[2], tt[2], xx[2]), hfma2(xx[3], tt[3], xx[3]));
      dep[j - 1] = slice(j - 1);
    }
  }
}
struct Role { int half, kind, g2_m, dt, g1_mt, g1_nt, cs, nconv, skip; uint32_t pitch; };
__device__ __forceinline__ Role get_role(const RoleMap& roles) {
  uint32_t b, sm;
  asm volatile("mov.u32 %0, %%ctaid.x;" : "=r"(b));
  asm volatile("mov.u32 %0, %%smid;" : "=r"(sm));
  const uint32_t w = roles.role[(roles.by_sm ? sm : b) >> 1];
  const int half = b & 1, kind = w & 3, m = (w >> 4) & 15, dt = (w >> 2) & 3;
  return Role{half, kind, m * 128, dt, half * 18 + (int)((w >> 8) & 31), (int)(w >> 16), (m * 4 + dt) * 2 + half,
              kind ? kind * kind : 6 - half, kind ? 1 : 2 - 2 * half, kind ? (uint32_t)PITCH_B : (uint32_t)PITCH_S};
}
__device__ __forceinline__ int g2_block(int half, int j) { return j < 0 ? 0 : half * 36 + (j < 12 ? 2 * j : j < 24 ? 2 * j - 23 : j); }
__device__ __forceinline__ int conv_chan(const Role& ro, int i) {
  const bool early = ro.kind == 0 && i < 4;
  const int big = ro.kind == 2 ? 176 + 4 * ro.cs : 48 + ro.cs, late = ro.kind ? big + i : i == 4 ? ro.cs : 96 + (ro.cs >> 1);
  const int k = early ? 2 * ro.cs + (i & 1) : late;
  return (3 * (k >> 6) + (early ? i >> 1 : 2)) * 64 + (k & 63);
}
__device__ __forceinline__ uint32_t conv_buf(uint32_t sb, int kind, int b) {
  return sb + (kind ? (b ? b + 1 : ST) * PITCH_B : b == 3 ? (36 % ST) * PITCH_S : ST * PITCH_S + b * CBUF);
}
__device__ __forceinline__ uint32_t conv_stage(uint32_t sb, int kind) { return sb + (kind ? ST * PITCH_B + CBUF : ST * PITCH_S + 3 * CBUF); }
__device__ __forceinline__ uint32_t u_stage(uint32_t sb, uint32_t pitch, int w) { return sb + (2 - w) * pitch + ASZ; }

__global__ void __cluster_dims__(2, 1, 1) __launch_bounds__(384, 1)
fused_kernel(const __nv_bfloat16* __restrict__ q, Scratch* __restrict__ gs, const __nv_bfloat16* __restrict__ b1,
             const __nv_bfloat16* __restrict__ shiftk, const __nv_bfloat16* __restrict__ ssmk, const __nv_bfloat16* __restrict__ ssmD,
             const __grid_constant__ Maps tm, const __grid_constant__ RoleMap roles, const __nv_bfloat16* __restrict__ b2,
             __nv_bfloat16* __restrict__ out) {
  const int cta = blockIdx.x;
  const int tid = threadIdx.x;

  const uint32_t t_start = clock_now();
  const int lc = (cta + LNROT) & 127;
  const uint32_t do_ln = cta < 128 && tid < 256;
  const int oct = lc + (tid & 128), ln_row = oct * 8 + ((tid >> 4) & 7), l16 = tid & 15;
  uint2 xr[9];
  const __nv_bfloat16* qrow = q + (size_t)ln_row * D_ + l16 * 4;
  asm volatile("" : "+l"(qrow));
  const int warp = __shfl_sync(0xffffffffu, tid >> 5, 0);
  if (warp < 8 || warp == 11) asm volatile("barrier.cluster.arrive.relaxed.aligned;" ::: "memory");
  if (do_ln && oct >= QLATE) spin_until(t_start, QDELAY + QRAMP * oct / 2);
#pragma unroll
  for (int i = 0; i < 9; i++) xr[i] = ldg64_if(qrow + i * 64, do_ln);
  const uint32_t sb = __shfl_sync(0xffffffffu, (uint32_t)__cvta_generic_to_shared(smem_raw), 0);
  const uint32_t bars = sb + BAR_OFF;
  const int lane = tid & 31;
  const int wg = warp >> 2;
  constexpr int LN_OFF = ST * PITCH_B;

  uint32_t look = 0;
  if (warp < 8 || warp == 11) {
    const int hq = (lane & 16) >> 3, hb = (lane & 16) + hq;
    float da[3][4] = {};
#pragma unroll
    for (int i = 0; i < 9; i++) mma16816(da[i % 3], xr[i].x, 0x3f803f80u, xr[i].y, 0x3f803f80u, xr[i].x, xr[i].y);
    const float r1 = ((da[0][2] + da[0][3]) + (da[1][2] + da[1][3])) + (da[2][2] + da[2][3]);
    const float r2 = (lane & 4) ? (da[0][1] + da[1][1]) + da[2][1] : (da[0][0] + da[1][0]) + da[2][0];
    const float s1 = __shfl_sync(0xffffffffu, r1, hq) + __shfl_sync(0xffffffffu, r1, hq + 1);
    const float s2 = (__shfl_sync(0xffffffffu, r2, hb) + __shfl_sync(0xffffffffu, r2, hb + 4)) + (__shfl_sync(0xffffffffu, r2, hb + 9) + __shfl_sync(0xffffffffu, r2, hb + 13));
    const float mean = s1 * (1.f / D_), var = fmaxf(fmaf(-mean, mean, s2 * (1.f / D_)), 0.f);
    const float rinv = ln_rinv(var), rinv2 = ln_rinv(var * rinv * rinv), scale = rinv * rinv2, shift = -bf_round((mean - bf_round(mean)) * rinv) * rinv2;
    const uint32_t m2 = pack_bf16(mean, mean), hi2 = pack_bf16(scale, scale), lo2 = pack_bf16(scale - bf_lo(hi2), scale - bf_lo(hi2)), sh2 = pack_bf16(shift, shift);
    const uint32_t hi1 = pack_bf16(rinv, rinv);
    asm volatile("{\n.reg .pred p;\nsetp.eq.u32 p, %5, 0;\n@p st.shared.v4.u32 [%0], {%1, %2, %3, %4};\n}" ::"r"(sb + LN_OFF + 18432 + tid), "r"(m2), "r"(hi1),
                 "r"(pack_bf16(rinv - bf_lo(hi1), rinv - bf_lo(hi1))), "r"(0u), "r"(tid & 0x10f) : "memory");
    const uint32_t g0 = 4 * (l16 >> 3) + 2 * (l16 & 1), hrow = sb + LN_OFF + ((tid >> 7) & 1) * 9216 + (tid & 0x70);
    const uint32_t hs0 = hrow + g0 * 128 + ((l16 >> 1) & 3) * 4, hs8 = ((hrow + (l16 >> 1) * 1152) ^ ((l16 >> 1) << 4)) + 1024 + (l16 & 1) * 8;
    uint32_t w[18];
#pragma unroll
    for (int i = 0; i < 18; i++) {
      const uint32_t d = hsub2((i & 1) ? xr[i >> 1].y : xr[i >> 1].x, m2);
      asm("max.u32 %0, %1, 1;" : "=r"(w[i]) : "r"(hfma2(d, hi2, hfma2(d, lo2, sh2))));
    }
#pragma unroll
    for (int i = 0; i < 16; i++) {
      const int gi = 9 * (i >> 1) + (i & 1);
      asm volatile("{\n.reg .pred p;\nsetp.ne.u32 p, %2, 0;\n@p st.shared.u32 [%0], %1;\n}" ::"r"((hs0 ^ ((g0 * 16 + (gi & 7) * 16) & 0x70)) + gi * 128), "r"(w[i]), "r"(do_ln) : "memory");
    }
    asm volatile("{\n.reg .pred p;\nsetp.ne.u32 p, %3, 0;\n@p st.shared.v2.u32 [%0], {%1, %2};\n}" ::"r"(hs8), "r"(w[16]), "r"(w[17]), "r"(do_ln) : "memory");
    fence_async_smem();
    if (warp < 8) named_arrive(wg, 160);
  } else if (warp != 8) {
    spin_until(t_start, W9);
  }

  if (wg == 2) {
    asm volatile("setmaxnreg.dec.sync.aligned.u32 56;");
    auto store_h = [&](int w) {
      named_bar(w, 160);
      if (cta < 128 && elect_one()) {
        tma3d_store(&tm.m[M_H], ((lc >> 3) + 16 * w) * 72, lc & 7, sb + LN_OFF + w * 9216);
        bulk_s2g(gs->stats + (lc + 128 * w) * 8, sb + LN_OFF + 18432 + w * 128, 128);
        bulk_commit();
      }
    };
    auto publish_h = [&](int w) {
      if (cta < 128 && elect_one()) { bulk_wait_all(); flag_add(gs->flags, FL_H + (w ? 2 : lc >> 6), 2 - w); }
      __syncwarp();
    };
    if (warp == 11) {
      if (lc >= 64) spin_until(t_start, HW);
      store_h(0);
      look = flag_ld(gs->flags, FL_H);
      if (lc < 64) publish_h(0);
    } else {
      if (elect_one()) {
        if (warp == 8) {
#pragma unroll
          for (int o = 0; o < B_GO; o += 8) mbar_init(bars + o, 1);
        } else {
#pragma unroll
          for (int o = 0; o < (B_EMPTY - B_GO) / 2; o += 8) mbar_init(bars + B_GO + (warp - 9) * ((B_EMPTY - B_GO) / 2) + o, 1);
#pragma unroll
          for (int o = 0; o < (B_CEMPTY - B_EMPTY) / 2; o += 8) mbar_init(bars + B_EMPTY + (warp - 9) * ((B_CEMPTY - B_EMPTY) / 2) + o, 2);
#pragma unroll
          for (int o = 0; o < (B_END - B_CEMPTY) / 2; o += 8) mbar_init(bars + B_CEMPTY + (warp - 9) * ((B_END - B_CEMPTY) / 2) + o, 4);
        }
        asm volatile("fence.mbarrier_init.release.cluster;" ::: "memory");
      }
      __syncwarp();
      asm volatile("barrier.cluster.arrive.relaxed.aligned;" ::: "memory");
#pragma unroll
      for (int k = 0; k < 3; k++) prefetch_map(&tm.m[warp == 8 ? k : 3 * warp - 25 + k]);
    }
    const Role ro = get_role(roles);
    if (warp != 8) asm volatile("barrier.cluster.wait.aligned;" ::: "memory");
    if (warp == 11) {
      Ring r{0, 1};
      const uint32_t bsz = ro.pitch - ASZ;
      const uint8_t* src = gs->h + ro.g1_nt * bsz + ST * 73728;
      named_bar(10, 64);
#pragma unroll 1
      for (int i = ST; i < 32; i++) {
        if (i == ST || i == 8 || i == 16) wait_counter(gs->flags, FL_H + (i >> 3), 128u, look, 0);
        if (i == LK1 || i == LK2) look = flag_ld(gs->flags, FL_H + (i >> 3) + 1);
        mbar_wait(bars + B_EMPTY + r.s * 8, r.ph ^ 1);
        if (elect_one()) bulk_g2s(sb + r.s * ro.pitch + ASZ, src, bsz, bars + B_FULL + r.s * 8);
        if (i == HS2) store_h(1);
        if (i == HS2 + 2 || (i == ST && lc >= 64)) publish_h(i != ST);
        if (i == KVGO1 && lane == 0) mbar_arrive(bars + B_KVGO + 8);
        if (i == KVGO && lane == 0) mbar_arrive(bars + B_KVGO);
        if (i == CVGO && lane == 0) mbar_arrive(bars + B_CVGO);
        src += 73728;
        r.next();
      }
      if (ro.kind != 2) {
        look = 0;
#pragma unroll 1
        for (int j = -1; j < 36; j++) {
          const uint8_t* su = gs->u + ((size_t)g2_block(ro.half, j) * D_ + ro.dt * 144) * 128;
          const int uc = j < 0 ? FL_U : FL_U + 1 + 2 * ro.half + (j > 16);
          if (j == -1 || j == 12 || j == 24) wait_counter(gs->flags, uc, 288u, look, 100);
          if (j == (ro.skip ? 4 : -1) || j == 3) mbar_wait_u(bars + B_UDONE + (j == 3 ? 8 : 0), 0);
          if (j >= ro.skip - 1) mbar_wait(bars + B_EMPTY + r.s * 8, r.ph ^ 1);
          if (j >= ro.skip - 1 && elect_one()) {
            bulk_g2s(sb + r.s * ro.pitch + ASZ, su + (ro.half ^ 1) * 9216, 9216, bars + B_FULL + r.s * 8);
            bulk_g2s(sb + r.s * ro.pitch + ASZ + 9216, su + ro.half * 9216, 9216, bars + B_FULL + r.s * 8);
          }
          if (j == 9 || j == 21) look = flag_ld(gs->flags, uc);
          r.next();
        }
#pragma unroll 1
        for (int o = lane; o < ST * 73728 / 16 / NG2; o += 32) ((uint4*)gs->h)[ro.cs * (ST * 73728 / 16 / NG2) + o] = make_uint4(0u, 0u, 0u, 0u);
      }
    } else if (warp == 8) {
      const uint64_t pol = stream_policy();
      Ring r{0, 0};
#pragma unroll 1
      for (int i = 0; i < 32; i++) {
        if (i < ST) spin_until(t_start, A0 + i * AD + (i >= AN ? AL : 0));
        if (i == ST) {
          asm volatile("barrier.cluster.wait.aligned;" ::: "memory");
          if (roles.by_sm) {
            uint32_t sm;
            asm volatile("mov.u32 %0, %%smid;" : "=r"(sm));
            if (elect_one()) { mbar_expect(bars + B_PEER, 8); st_async2(mapa(bars + B_END, ro.half ^ 1), sm, sm, mapa(bars + B_PEER, ro.half ^ 1)); }
            mbar_wait_u(bars + B_PEER, 0);
            if ((lds32(bars + B_END) ^ sm) != 1 || sm >= NCTA) asm volatile("trap;");
          }
        }
        if (i >= ST) mbar_wait(bars + B_EMPTY + r.s * 8, r.ph ^ 1);
        if (elect_one()) {
          mbar_expect(bars + B_FULL + r.s * 8, ro.pitch);
          tma_weights(sb + r.s * ro.pitch, &tm.m[M_W1], i * 64, ro.g1_mt * 2, bars + B_FULL + r.s * 8, pol);
        }
        r.next();
      }
      if (ro.kind != 2) {
#pragma unroll 1
        for (int j = -1; j < 36; j++) {
          if (j == 3 && ro.kind == 0) mbar_wait_u(bars + B_CEMPTY + 24, 0);
          if (j >= ro.skip - 1) mbar_wait(bars + B_EMPTY + r.s * 8, r.ph ^ 1);
          if (j >= ro.skip - 1 && elect_one()) {
            mbar_expect(bars + B_FULL + r.s * 8, PITCH_S);
            tma_weights(sb + r.s * ro.pitch, &tm.m[M_W2], g2_block(ro.half, j) * 64, ro.g2_m >> 6, bars + B_FULL + r.s * 8, pol);
            if (j == 26 + ro.dt) tma_weights_prefetch(&tm.m[M_W2], g2_block(ro.half, j + 6) * 64, ro.g2_m >> 6, pol);
          }
          r.next();
        }
        if (lane < 2) mbar_expect(bars + B_RFULL + lane * 8, 9216);
        __syncwarp();
        mbar_wait(bars + B_EMPTY + r.s * 8, r.ph ^ 1);
        if (lane == 0) mbar_arrive_cluster(mapa(bars + B_GO, ro.half ^ 1));
      }
    } else {
      const uint64_t pol = stream_policy();
      {
        const uint32_t hb = (ro.pitch - ASZ) >> 1, raw = bars + B_RAW + (warp - 9) * 40, dst = sb + ASZ + (warp - 9) * hb;
        const uint8_t* src = gs->h + (2 * ro.g1_nt + warp - 9) * hb;
        auto fetch_h = [&](int i) { if (elect_one()) { mbar_expect(raw + i * 8, hb); bulk_g2s(dst + i * ro.pitch, src + i * 73728, hb, raw + i * 8); } };
        int next = 0;
#pragma unroll 1
        for (int i = -1; i < ST; i++) {
          if (i >= 0) {
#pragma unroll 1
            for (uint32_t tries = 0;; tries++) {
              mbar_wait_u(raw + i * 8, tries & 1);
              const uint32_t pa = dst + i * ro.pitch + lane * 32 + (lane >> 2) * 4;
              uint32_t m = 1;
#pragma unroll
              for (int j = 0; j < 12; j++) m = min(m, lds32(pa + (j < 9 || ro.kind ? j : 0) * 1024));
              if (__all_sync(0xffffffffu, m)) break;
              fetch_h(i);
            }
            if (elect_one()) asm volatile("mbarrier.complete_tx.relaxed.cta.shared::cta.b64 [%0], %1;" ::"r"(bars + B_FULL + i * 8), "r"(hb) : "memory");
          }
#pragma unroll 1
          for (const int end = min(next + 2, ST); next < end; next++) {
            if (i < 0) spin_until(t_start, H0 + next * HD);
            fetch_h(next);
          }
          if (i < 0 && warp == 10) named_arrive(10, 64);
        }
      }
      const int chan = conv_chan(ro, lane < ro.nconv ? lane : 0);
      const uint32_t dskip = ldg16(ssmD + chan);
      uint4 shk;
      mbar_wait_u(bars + B_KVGO + (ro.kind ? 8 : (warp - 9) * 8), 0);
      if (ro.kind) shk = ldg128(ssmk + (size_t)chan * S_);
      else {
        const int cs = ro.cs, grp = (cs / 3) * 2 + warp - 9, cb0 = (cs % 3) * 3;
        const uint32_t kin_s = sb + ST * PITCH_S + (warp - 9) * KVW, kout = kin_s + 2 * KVIN, fb = bars + B_KFULL + (warp - 9) * 16;
        auto fetch = [&](int i) {
          if (elect_one()) {
            mbar_expect(fb + (i & 1) * 8, KVIN);
            tma2d_stream(kin_s + (i & 1) * KVIN, &tm.m[M_K], (cb0 + i) * 64, grp * 32 - 4, fb + (i & 1) * 8, pol);
            tma2d_stream(kin_s + (i & 1) * KVIN + 4608, &tm.m[M_V], (cb0 + i) * 64, grp * 32 - 1, fb + (i & 1) * 8, pol);
          }
        };
        fetch(0);
        shk = ldg128(shiftk + (cb0 * 64 + lane * 2) * 4);
#pragma unroll 1
        for (int i = 0; i < 3; i++) {
          const uint32_t w0 = __byte_perm(shk.x, shk.z, 0x5410), w1 = __byte_perm(shk.x, shk.z, 0x7632);
          const uint32_t w2 = __byte_perm(shk.y, shk.w, 0x5410), w3 = __byte_perm(shk.y, shk.w, 0x7632);
          const uint32_t ka = kin_s + (i & 1) * KVIN + lane * 4;
          mbar_wait_u(fb + (i & 1) * 8, i >> 1);
          if (i < 2) fetch(i + 1);
          shk = ldg128(i < 2 ? shiftk + ((cb0 + i + 1) * 64 + lane * 2) * 4 : ssmk + (size_t)chan * S_);
          uint32_t kr[8], vr[8], t1, t2, t3, xp;
          {
            const uint32_t k0 = lds32(ka), k1 = lds32(ka + 128), k2 = lds32(ka + 256), k3 = lds32(ka + 384), v0 = lds32(ka + 4608);
#pragma unroll
            for (int j = 0; j < 8; j++) { kr[j] = lds32(ka + 512 + j * 128); vr[j] = lds32(ka + 4736 + j * 128); }
            xp = hmul2(hfma2(k3, w0, hfma2(k2, w1, hfma2(k1, w2, hmul2(k0, w3)))), v0);
            t1 = hfma2(k3, w1, hfma2(k2, w2, hmul2(k1, w3)));
            t2 = hfma2(k3, w2, hmul2(k2, w3));
            t3 = hmul2(k3, w3);
          }
#pragma unroll 1
          for (int o = 0; o < 4; o++) {
            const uint32_t from = ka + o * 1024, to = kout + (o >> 1) * 5120 + lane * 80 + (o & 1) * 32;
#pragma unroll
            for (int m = 0; m < 8; m += 4) {
              uint32_t x[4];
#pragma unroll
              for (int j = 0; j < 4; j++) {
                x[j] = hmul2(hfma2(kr[m + j], w0, t1), vr[m + j]);
                t1 = hfma2(kr[m + j], w1, t2);
                t2 = hfma2(kr[m + j], w2, t3);
                t3 = hmul2(kr[m + j], w3);
              }
#pragma unroll
              for (int c = 0; c < 2; c++) {
                const uint32_t sel = c ? 0x7632 : 0x5410;
                sts128(to + c * 2560 + m * 4, __byte_perm(x[0], xp, sel), __byte_perm(x[1], x[0], sel), __byte_perm(x[2], x[1], sel), __byte_perm(x[3], x[2], sel));
              }
#pragma unroll
              for (int j = m; j < m + 4; j++) { kr[j] = lds32_if(from + 1536 + j * 128, o < 3); vr[j] = lds32_if(from + 5760 + j * 128, o < 3); }
              xp = x[3];
            }
            if (o & 1) {
              fence_async_smem();
              __syncwarp();
              if (elect_one()) {
                bulk_wait_all();
                if (o == 1 && i) flag_add(gs->flags, FL_KV + i - 1, 1);
                tma4d_store(&tm.m[M_KV], (cb0 + i) * 32, 0, 2 * grp + (o >> 1), kout + (o >> 1) * 5120);
                bulk_commit();
              }
              __syncwarp();
            }
          }
        }
        look = flag_ld(gs->flags, FL_KV + warp - 9);
        if (lane == 2 * (warp - 9)) bulk_prefetch(ssmk + (size_t)chan * S_, 2 * S_ * 2, pol);
        if (elect_one()) {
          bulk_wait_all();
          flag_add(gs->flags, FL_KV + 2, 1);
        }
        __syncwarp();
      }
      {
        shk.x = __byte_perm(pack_bf16(bf_lo(shk.x) + bf_lo(dskip), 0.f), shk.x, 0x7610);
        const int mid = ro.kind ? 1 : 2;
#pragma unroll 1
        for (int i = warp == 9 ? 0 : mid; i < (warp == 9 ? mid : ro.nconv); i++) {
          const int b = i & 3, d = __shfl_sync(0xffffffffu, chan, i);
          const uint32_t base = conv_buf(sb, ro.kind, b), cf = bars + B_CFULL + b * 8;
          if (ro.kind ? i < 2 : !(i & 1)) wait_counter(gs->flags, FL_KV + (ro.kind ? 2 : i >> 1), 192u, i < 4 ? look : 0u, 200);
          if (i == 2) { mbar_wait_u(bars + B_CVGO, 0); spin_until(clock_now(), 600); }
          if (i == 2 * mid - 1) {
            mbar_wait_u(bars + B_G1DONE, 0);
            if (lane == 4 || lane == 5) bulk_prefetch(ssmk + (size_t)chan * S_, S_ * 2, pol);
          }
          if (i >= 4) mbar_wait_u(bars + B_CEMPTY + b * 8, 0);
          if (lane == i) sts128(base + CH_OFF, shk.x, shk.y, shk.z, shk.w);
          if (lane >= 29) sts128(base + CH_OFF + (lane - 32) * 16, 0u, 0u, 0u, 0u);
          fence_async_smem();
          __syncwarp();
          if (elect_one()) mbar_expect(cf, 4080 + 64 * 160);
#pragma unroll 1
          for (int k = 0; k < 5; k++) {
            if (elect_one()) {
              if (k < 4) asm volatile("cp.async.bulk.tensor.3d.shared::cluster.global.mbarrier::complete_tx::bytes [%0], [%1, {%3, %4, %5}], [%2];"
                                      ::"r"(base + CT_OFF + k * 2560), "l"(&tm.m[M_KL]), "r"(cf), "r"(0), "r"(k * 16), "r"(d) : "memory");
              else bulk_g2s_stream(base + CH_OFF + 16, ssmk + (size_t)d * S_ + 8, 4080, cf, pol);
            }
          }
        }
      }
      if (warp == 9) {
        if (lane < 6) sts32(bars + B_END + 8 + lane * 4, chan_pos(chan));
        __syncwarp();
        if (elect_one()) {
          const uint32_t bsz = ro.pitch - ASZ;
          if (ro.kind) { mbar_wait_u(bars + B_G1DONE, 0); gate_arrive(gs->flags, GDELAY + BLK_NS - (ro.kind == 1 ? GBIG : 0)); }
#pragma unroll 1
          for (int w = 0; w < 2; w++) {
            const uint32_t src = u_stage(sb, ro.pitch, w);
            mbar_wait_u(bars + B_USTG + w * 8, 0);
            bulk_s2g(gs->u + (size_t)(2 * ro.g1_mt + w) * D_ * 128 + ro.g1_nt * bsz, src, bsz);
            bulk_commit();
#pragma unroll 1
            for (int k = 0; k < ro.skip * w; k++) {
              mbar_arrive(bars + B_FULL + (2 + k) * 8);
              mbar_arrive(bars + B_EMPTY + (2 + k) * 8);
              mbar_arrive(bars + B_EMPTY + (2 + k) * 8);
            }
            bulk_wait_read();
            mbar_arrive(bars + B_UDONE + w * 8);
            if (ro.kind && !w) continue;
            bulk_wait_all();
            flag_add(gs->flags, FL_U + (w ? 1 + 2 * ro.half + (ro.kind != 0) : 0), ro.kind ? 16 : 3 + 3 * w);
          }
#pragma unroll 1
          for (int i = 0; i < ro.nconv; i++) {
            mbar_wait_u(bars + B_SFULL + (i & 1) * 8, (i >> 1) & 1);
            bulk_s2g(gs->z + (size_t)lds32(bars + B_END + 8 + i * 4) * S_, conv_stage(sb, ro.kind) + (i & 1) * 4096, 4096);
            bulk_commit();
            if (ro.kind == 0 && i == ro.nconv - 4) gate_arrive(gs->flags, ro.skip * BLK_NS);
            bulk_wait_read();
            mbar_arrive(bars + B_SEMPTY + (i & 1) * 8);
          }
          bulk_wait_all();
          flag_add(gs->flags, FL_Z, 1);
        }
      } else if (ro.kind != 2) {
        mbar_wait_u(bars + B_G1DONE, 0);
        uint2 gate;
#pragma unroll 1
        for (uint32_t spins = 0;; spins++) {
          asm volatile("ld.relaxed.gpu.global.v2.u32 {%0, %1}, [%2];" : "=r"(gate.x), "=r"(gate.y) : "l"(gs->flags + FL_GATE * 32) : "memory");
          if (gate.x == NCTA) break;
          __nanosleep(100);
          if (spins > SPIN_LIMIT) asm volatile("trap;");
        }
#pragma unroll 1
        for (int w = 0; w < 2; w++) {
          while (time_now() - gate.y < GDELAY + ro.skip * BLK_NS + w * GDELAY1) {}
          if (lane == 0) mbar_arrive(bars + B_G2GO + (w ^ (ro.nconv & 1)) * 8);
        }
        wait_counter(gs->flags, FL_Z, NCTA, 0, 300);
        spin_until(clock_now(), ZRAMP * cta);
        if (elect_one()) {
          mbar_expect(bars + B_ZFULL, 18432);
          tma2d(sb + ST * ro.pitch, &tm.m[M_Z], ro.g2_m, ro.dt * 144 + ro.half * 72, bars + B_ZFULL);
          tma2d(sb + ST * ro.pitch + 9216, &tm.m[M_Z], ro.g2_m + 64, ro.dt * 144 + ro.half * 72, bars + B_ZFULL);
        }
      }
    }
    if (warp >= 10) polling_done(gs->flags, lane);
  } else {
    asm volatile("setmaxnreg.inc.sync.aligned.u32 224;");
    const int wi = warp & 3, g = lane >> 2, qd = lane & 3, wt = tid & 127;
    const bool leader = wt == 0;
    Pipe p{{0, 0}, 0, false};
    asm volatile("barrier.cluster.wait.aligned;" ::: "memory");
    int kind;
    {
      const Role ro = get_role(roles);
      kind = ro.kind;
      const int f0 = ro.g1_mt * 128 + wg * 64 + wi * 16 + g;
      uint32_t bias0 = ldg16(b1 + f0), bias1 = ldg16(b1 + f0 + 8);
      const uint32_t so = ((lane >> 4) * 8 + (lane & 7)) * 128 + (((2 * wi + ((lane >> 3) & 1)) ^ (lane & 7)) << 4);
      const int cB = (g >> 1) & 1, cA = g >> 2, b = 2 * wi + (g & 1), nconv = ro.nconv;
      const uint32_t toff = pin(CT_OFF + (40 * (2 * cA + cB) + 8 + b - 2 * qd) * 4);
      const int phi = 2 * cA + (qd >> 1) + cB, pp = cB ? (phi & 3) : ((phi + 3) & 3);
      const int srcB = shfl_ordered(((pp >> 1) << 4) | ((cB ^ 1) << 3) | ((g & 1) << 2) | ((pp & 1) << 1) | (qd & 1), lane);
      const bool pB1 = cB && phi < 4, pB2 = cB && phi == 4;
      const int word = (8 * cB + 2 * (phi & 3) + (qd & 1)) * 8 + b;
      const uint32_t sto = shfl_ordered(conv_stage(sb, kind) + wg * 4096 + (word ^ (((word >> 5) & 3) << 1)) * 4, lane);
      const uint32_t sa = shfl_ordered(u_stage(sb, ro.pitch, wg) + so, lane);
      uint32_t a[16][4];
      auto load_a = [&](uint32_t base, int t, uint32_t on) {
        const uint32_t pt = base + toff + (t >> 1) * 1280 + (t & 1) * 64;
        a[t][0] = lds32_if(pt + 32, on); a[t][1] = lds32_if(pt + 672, on); a[t][2] = lds32_if(pt, on); a[t][3] = lds32_if(pt + 640, on);
      };
      auto gemm1_done = [&]() {
        pipe_drain(p, bars, leader);
        if (leader) mbar_arrive(bars + B_G1DONE);
        mbar_wait_u(bars + B_EMPTY + (2 - wg) * 8, wg ^ 1);
      };
      {
        float acc[72];
        if (kind) {
          float big[96];
          gemm_run<1, LEAD_B>(big, 32, 0, p, sb, PITCH_B, wg, leader);
          if (wg == 1) named_arrive(6, 256);
          gemm1_done();
          if (wg < nconv) mbar_wait_u(bars + B_CFULL + wg * 8, 0);
#pragma unroll
          for (int t = 0; t < 8; t++) load_a(conv_buf(sb, 1, wg), t, 1);
          gelu_store<72, 96>(big, bias0, bias1, sa, 0u, [](int) { return 0u; });
#pragma unroll
          for (int i = 0; i < 72; i++) asm volatile("mov.b32 %0, %1;" : "=f"(acc[i]) : "f"(big[i]));
        } else {
          gemm_run<1, 0>(acc, 32 - LEAD_S - (wg ? 0 : PRE0), 0, p, sb, PITCH_S, wg, leader);
          if (wg == 1) pipe_drain(p, bars, leader);
          mbar_wait_u(bars + B_CFULL + wg * 8, 0);
#pragma unroll
          for (int t = 0; t < 8; t++) load_a(conv_buf(sb, 0, wg), t, 1);
          if (wg == 1) named_bar(8, 256);
          gemm_run<1, 0>(acc, LEAD_S + (wg ? 0 : PRE0), 1, p, sb, PITCH_S, wg, leader);
          named_arrive(8 - 2 * wg, 256);
          gemm1_done();
        }
        gelu_store<0, 72>(acc, bias0, bias1, sa, roles.by_sm >> 1, [&](int t) { return t + GLAG < 9 ? lds32(bars) : 0u; });
        fence_async_smem();
        __syncwarp();
        if (lane == 0) mbar_arrive(bars + B_USTG + wg * 8);
      }
      {
#pragma unroll 1
        for (int i = wg; i < nconv; i += 2) {
          const uint32_t base = conv_buf(sb, kind, i & 3), next = conv_buf(sb, kind, (i + 2) & 3);
          const uint64_t dH = mkdesc(base + CH_OFF, 16, 128, 0);
          float y[8][16];
          if (toff < CT_OFF + 32) a[0][2] = 0u;
          named_bar(6 + wg, 256);
          wg_fence();
#pragma unroll
          for (int t = 0; t < 16; t++) {
            if (t == 8) wg_fence();
            if (t == CTURN) named_arrive(7 - wg, 256);
#pragma unroll
            for (int cb = t >> 1; cb < 8; cb++) {
              wgmma_rs_n32(y[cb], a[t][0], a[t][1], a[t][2], a[t][3], dH + (32 * cb - 32 * (t >> 1) - 2 * (t & 1) - 1), t);
              const int n = 8 * t - (t >> 1) * ((t - 1) >> 1) - (t >> 1) + cb + 1;
              if (n % CPER == 0 && n / CPER <= 8) load_a(base, 7 + n / CPER, 1);
            }
          }
          wg_commit();
          const bool more = i + 2 < nconv;
          if (more) mbar_wait_u(bars + B_CFULL + ((i + 2) & 3) * 8, (i + 2) >> 2);
          mbar_wait_u(bars + B_SEMPTY + wg * 8, ((i >> 1) & 1) ^ 1);
          wg_wait<0>();
          if (lane == 0) mbar_arrive(bars + B_CEMPTY + (i & 3) * 8);
          uint32_t P[16], Q[16], R[16], o[8];
#pragma unroll
          for (int j = 0; j < 32; j++) {
            if ((j & 3) == 0) load_a(next, j >> 2, more);
            float v0 = y[j >> 2][4 * (j & 3)], v1 = y[j >> 2][4 * (j & 3) + 1];
            if (j >= 2) { v0 += y[(j - 2) >> 2][4 * ((j - 2) & 3) + 2]; v1 += y[(j - 2) >> 2][4 * ((j - 2) & 3) + 3]; }
            if (j & 1) R[j >> 1] = shfl_ordered(pack_bf16(v0, v1), lane ^ 16);
            else P[j >> 1] = pack_bf16(v0, v1);
          }
#pragma unroll
          for (int m = 0; m < 16; m++) Q[m] = hadd2(P[m], cA ? R[m] : (m ? R[m - 1] : 0u));
#pragma unroll
          for (int m = 0; m < 8; m++) o[m] = shfl_ordered(pB1 ? Q[2 * m] : (pB2 ? (m ? Q[2 * m - 1] : 0u) : Q[2 * m + 1]), srcB);
#pragma unroll
          for (int m = 0; m < 8; m++) sts32(sto + m * 512, hadd2(pB1 ? Q[2 * m + 1] : Q[2 * m], o[m]));
          fence_async_smem();
          __syncwarp();
          if (lane == 0) mbar_arrive(bars + B_SFULL + wg * 8);
        }
        if (wg == (nconv & 1)) named_bar(6 + wg, 256);
      }
    }
    if (kind != 2) {
      const Role ro = get_role(roles);
      const uint32_t pitch = ro.pitch;
      const int s0 = ro.g2_m + wg * 64 + wi * 16 + g;
      const size_t go = (size_t)s0 * D_ + ro.dt * 128 + ro.half * 64 + qd * 8, go8 = (size_t)s0 * D_ + 512 + ro.dt * 16 + ro.half * 8 + qd * 2;
      uint32_t x[2][9], sg[2][9];
      float acc[72];
      p.r = Ring{(uint32_t)(2 + ro.skip), 0};
      mbar_wait_u(bars + B_G2GO + wg * 8, 0);
      gemm_run<0, 0>(acc, XAT + 2 * wg + 1 - ro.skip, 0, p, sb, pitch, wg, leader);
#pragma unroll
      for (int J = 0; J < 4; J++) {
        const uint4 v = ldg128(q + go + (J & 1) * 8 * D_ + (J >> 1) * 32);
        x[J & 1][4 * (J >> 1)] = v.x; x[J & 1][4 * (J >> 1) + 1] = v.y; x[J & 1][4 * (J >> 1) + 2] = v.z; x[J & 1][4 * (J >> 1) + 3] = v.w;
      }
      x[0][8] = ldg32(q + go8); x[1][8] = ldg32(q + go8 + 8 * D_);
      const uint4 st0 = ld_l2(gs->stats + s0), st1 = ld_l2(gs->stats + s0 + 8);
      const uint32_t braw0 = ldg16(b2 + s0), braw1 = ldg16(b2 + s0 + 8);
      gemm_run<0, 0>(acc, ZAT - XAT, 1, p, sb, pitch, wg, leader);
      {
        const int zw = 8 * wi + (g ^ ((((ro.g2_m >> 6) + wg) & 3) << 1));
        const uint32_t za = sb + ST * pitch + wg * 9216 + qd * 256 + (zw & 3) * 4;
        mbar_wait_u(bars + B_ZFULL, 0);
#pragma unroll
        for (int j = 0; j < 9; j++) {
          sg[0][j] = lds32(za + j * 1024 + (((zw >> 2) ^ (2 * qd)) << 4));
          sg[1][j] = lds32(za + j * 1024 + 128 + (((zw >> 2) ^ (2 * qd + 1)) << 4));
        }
      }
      gemm_run<0, 0>(acc, 1, 1, p, sb, pitch, wg, leader);
#pragma unroll
      for (int j = 0; j < 9; j++) {
        const uint32_t z0 = __byte_perm(sg[0][j], sg[1][j], 0x5410), z1 = __byte_perm(sg[0][j], sg[1][j], 0x7632);
        sg[0][j] = hmul2(ln_apply(x[0][j], st0), z0);
        sg[1][j] = hmul2(ln_apply(x[1][j], st1), z1);
        asm volatile("" : "+r"(sg[0][j]), "+r"(sg[1][j]));
      }
      gemm_run<0, SKEW>(acc, 35 - ZAT - LAG - 2 * wg, 1, p, sb, pitch, wg, leader);
      const uint32_t rbuf = sb + (69 % ST) * pitch + warp * 2304;
      const uint32_t rdst = mapa(rbuf, ro.half ^ 1), rbar = mapa(bars + B_RFULL + wg * 8, ro.half ^ 1);
      pipe_drain(p, bars, leader);
      float cs[36], ck[36];
      split_acc(acc, cs, ck);
      gemm2_part<0, 0, 4 * LAG>(cs, sb, pitch, wg);
      if (KPRE) gemm2_part<72, 0, KPRE>(ck, sb, pitch, wg);
      const float hb0 = fmaf(bf_lo(braw0), 0.5f, __uint_as_float(st0.w)), hb1 = fmaf(bf_lo(braw1), 0.5f, __uint_as_float(st1.w));
      mbar_wait(bars + B_GO, 0);
      wg_wait<KPRE ? 1 : 0>();
#pragma unroll
      for (int i = 0; i < 5; i++) {
        const float* c = &cs[8 * i];
        const uint32_t v0 = pack_bf16(fmaf(c[0], 0.25f, hb0), fmaf(c[1], 0.25f, hb0)), v1 = pack_bf16(fmaf(c[2], 0.25f, hb1), fmaf(c[3], 0.25f, hb1));
        if (i < 4) st_async4(rdst + i * 512 + lane * 16, v0, v1, pack_bf16(fmaf(c[4], 0.25f, hb0), fmaf(c[5], 0.25f, hb0)), pack_bf16(fmaf(c[6], 0.25f, hb1), fmaf(c[7], 0.25f, hb1)), rbar);
        else st_async2(rdst + 2048 + lane * 8, v0, v1, rbar);
      }
      if (wg == 1) named_bar(7, 256);
      gemm2_part<72, KPRE, 4 * LAG>(ck, sb, pitch, wg);
      uint32_t rp[18];
      mbar_wait(bars + B_RFULL + wg * 8, 0);
#pragma unroll
      for (int m = 0; m < 4; m++) {
        const uint4 v = lds128(rbuf + m * 512 + lane * 16);
        rp[4 * m] = v.x; rp[4 * m + 1] = v.y; rp[4 * m + 2] = v.z; rp[4 * m + 3] = v.w;
      }
      { const uint2 v = lds64(rbuf + 2048 + lane * 8); rp[16] = v.x; rp[17] = v.y; }
      __nv_bfloat16* o = out + go;
      wg_wait<0>();
      float h[2][4], t[2][4], half = 0.25f;
#pragma unroll
      for (int j = 0; j <= 9; j++) {
        if (j < 9) {
          const uint32_t ra = rp[2 * j], rb = rp[2 * j + 1];
          if (j >= 2) half = fmaf(t[j & 1][3], 0.f, 0.25f);
          h[j & 1][0] = fmaf(ck[4 * j], half, bf_lo(ra)); h[j & 1][1] = fmaf(ck[4 * j + 1], half, bf_hi(ra));
          h[j & 1][2] = fmaf(ck[4 * j + 2], half, bf_lo(rb)); h[j & 1][3] = fmaf(ck[4 * j + 3], half, bf_hi(rb));
#pragma unroll
          for (int u = 0; u < 4; u++) t[j & 1][u] = tanh_ordered(h[j & 1][u]);
        }
        if (j > 0) {
          const int k = j - 1;
          const float* hh = h[k & 1];
          const float* tt = t[k & 1];
          x[0][k] = hfma2(sg[0][k], pack_bf16(fmaf(hh[0], tt[0], hh[0]), fmaf(hh[1], tt[1], hh[1])), x[0][k]);
          x[1][k] = hfma2(sg[1][k], pack_bf16(fmaf(hh[2], tt[2], hh[2]), fmaf(hh[3], tt[3], hh[3])), x[1][k]);
          if ((k & 3) == 3) {
            *(uint4*)(o + (k >> 2) * 32) = make_uint4(x[0][k - 3], x[0][k - 2], x[0][k - 1], x[0][k]);
            *(uint4*)(o + 8 * D_ + (k >> 2) * 32) = make_uint4(x[1][k - 3], x[1][k - 2], x[1][k - 1], x[1][k]);
          }
        }
      }
      *(uint32_t*)(out + go8) = x[0][8];
      *(uint32_t*)(out + go8 + 8 * D_) = x[1][8];
    }
  }
}

typedef CUresult (*EncodeFn)(CUtensorMap*, CUtensorMapDataType, cuuint32_t, void*, const cuuint64_t*, const cuuint64_t*, const cuuint32_t*,
                             const cuuint32_t*, CUtensorMapInterleave, CUtensorMapSwizzle, CUtensorMapL2promotion, CUtensorMapFloatOOBfill);

uint32_t role_of_pair(int t) {
  int grp, i;
  if (t < 32) { const int j = t & 7; i = t >> 3; grp = j < 6 ? 1 + j : 12 + 2 * (j - 6); }
  else if (t < 60) { const int j = (t - 32) % 7; i = (t - 32) / 7; grp = j < 5 ? 7 + j : 13 + 2 * (j - 5); }
  else if (t < 62) return 2u | (uint32_t)(t - 60) << 2 | (uint32_t)(14 + 3 * (t - 60)) << 8 | 2u << 16;
  else { grp = 0; i = t - 62; }
  if (grp < 12) return (uint32_t)(i << 2 | grp << 4 | grp << 8 | i << 16);
  const int u = (grp & 1) * 4 + i;
  return (uint32_t)(1 | i << 2 | grp << 4 | (12 + 3 * ((grp - 12) >> 1) + u / 3) << 8 | (u % 3) << 16);
}

}

extern "C" void kernel_launch(void* const* d_in, const int* in_sizes, int n_in, void* d_out, int out_size) {
  (void)in_sizes; (void)n_in; (void)out_size;
  EncodeFn enc = nullptr;
  cudaDriverEntryPointQueryResult qr;
  cudaGetDriverEntryPoint("cuTensorMapEncodeTiled", (void**)&enc, cudaEnableDefault, &qr);
  Scratch* gs = nullptr;
  cudaGetSymbolAddress((void**)&gs, g_scratch);
  void *zp = gs->z, *hp = gs->h, *kvp = gs->kv;
  Maps tm;
  for (int w = 0; w < 2; w++) {
    cuuint64_t gd[2] = {D_, S_};
    cuuint64_t st[1] = {D_ * 2};
    cuuint32_t bx[2] = {64, w ? 33u : 36u};
    cuuint32_t es[2] = {1, 1};
    enc(w ? &tm.m[M_V] : &tm.m[M_K], CU_TENSOR_MAP_DATA_TYPE_BFLOAT16, 2, d_in[1 + w], gd, st, bx, es, CU_TENSOR_MAP_INTERLEAVE_NONE, CU_TENSOR_MAP_SWIZZLE_NONE,
        CU_TENSOR_MAP_L2_PROMOTION_L2_128B, CU_TENSOR_MAP_FLOAT_OOB_FILL_NONE);
  }
  {
    cuuint64_t gd[4] = {16, D_ / 2, 2, 128};
    cuuint64_t st[3] = {2 * KVT, KVT, 64};
    cuuint32_t bx[4] = {20, 32, 2, 1};
    cuuint32_t es[4] = {1, 1, 1, 1};
    enc(&tm.m[M_KV], CU_TENSOR_MAP_DATA_TYPE_UINT32, 4, kvp, gd, st, bx, es, CU_TENSOR_MAP_INTERLEAVE_NONE, CU_TENSOR_MAP_SWIZZLE_NONE,
        CU_TENSOR_MAP_L2_PROMOTION_NONE, CU_TENSOR_MAP_FLOAT_OOB_FILL_NONE);
  }
  {
    cuuint64_t gd[3] = {40, 64, D_};
    cuuint64_t st[2] = {128, KVT};
    cuuint32_t bx[3] = {40, 16, 1};
    cuuint32_t es[3] = {1, 1, 1};
    enc(&tm.m[M_KL], CU_TENSOR_MAP_DATA_TYPE_UINT32, 3, (uint8_t*)kvp - 32, gd, st, bx, es, CU_TENSOR_MAP_INTERLEAVE_NONE, CU_TENSOR_MAP_SWIZZLE_NONE,
        CU_TENSOR_MAP_L2_PROMOTION_NONE, CU_TENSOR_MAP_FLOAT_OOB_FILL_NONE);
  }
  {
    cuuint64_t gd[3] = {64, 32 * 72, 8};
    cuuint64_t st[2] = {1024, 128};
    cuuint32_t bx[3] = {64, 72, 1};
    cuuint32_t es[3] = {1, 1, 1};
    enc(&tm.m[M_H], CU_TENSOR_MAP_DATA_TYPE_BFLOAT16, 3, hp, gd, st, bx, es, CU_TENSOR_MAP_INTERLEAVE_NONE, CU_TENSOR_MAP_SWIZZLE_128B,
        CU_TENSOR_MAP_L2_PROMOTION_NONE, CU_TENSOR_MAP_FLOAT_OOB_FILL_NONE);
  }
  for (int w = 0; w < 2; w++) {
    const cuuint64_t M = w ? S_ : F_, K = w ? F_ : S_;
    cuuint64_t gd[3] = {64, K, M / 64};
    cuuint64_t st[2] = {M * 2, 128};
    cuuint32_t bx[3] = {64, 64, 2};
    cuuint32_t es[3] = {1, 1, 1};
    enc(w ? &tm.m[M_W2] : &tm.m[M_W1], CU_TENSOR_MAP_DATA_TYPE_BFLOAT16, 3, d_in[w ? 9 : 7], gd, st, bx, es, CU_TENSOR_MAP_INTERLEAVE_NONE,
        CU_TENSOR_MAP_SWIZZLE_128B, CU_TENSOR_MAP_L2_PROMOTION_L2_256B, CU_TENSOR_MAP_FLOAT_OOB_FILL_NONE);
  }
  {
    cuuint64_t gd[2] = {S_, D_};
    cuuint64_t st[1] = {S_ * 2};
    cuuint32_t bx[2] = {64, 72};
    cuuint32_t es[2] = {1, 1};
    enc(&tm.m[M_Z], CU_TENSOR_MAP_DATA_TYPE_BFLOAT16, 2, zp, gd, st, bx, es, CU_TENSOR_MAP_INTERLEAVE_NONE, CU_TENSOR_MAP_SWIZZLE_128B,
        CU_TENSOR_MAP_L2_PROMOTION_L2_256B, CU_TENSOR_MAP_FLOAT_OOB_FILL_NONE);
  }
  RoleMap roles;
  int dev = 0, sms = 0;
  cudaGetDevice(&dev);
  cudaDeviceGetAttribute(&sms, cudaDevAttrMultiProcessorCount, dev);
  roles.by_sm = sms == NCTA;
  for (int k = 0; k < NCTA / 2; k++) roles.role[k] = role_of_pair(k);
  cudaFuncSetAttribute(fused_kernel, cudaFuncAttributeMaxDynamicSharedMemorySize, SMEM_BYTES);
  fused_kernel<<<NCTA, 384, SMEM_BYTES>>>((const __nv_bfloat16*)d_in[0], gs, (const __nv_bfloat16*)d_in[8], (const __nv_bfloat16*)d_in[3],
                                          (const __nv_bfloat16*)d_in[4], (const __nv_bfloat16*)d_in[5], tm,
                                          roles, (const __nv_bfloat16*)d_in[10], (__nv_bfloat16*)d_out);
}
```

```cpp
#include <cuda_runtime.h>
#include <cuda_bf16.h>
#include <cuda.h>
#include <stdint.h>

namespace {

constexpr int S_ = 2048, D_ = 576, F_ = 4608;
constexpr int NCTA = 132, NG2 = 128;
constexpr int ST = 5, ASZ = 16384, PITCH_S = ASZ + 144 * 128, PITCH_B = ASZ + 192 * 128;
constexpr int CBUF = 14464, CH_OFF = 128, CT_OFF = 4224, KVT = 8192;
constexpr int KVIN = (36 + 33) * 128, KVW = 2 * CBUF;
constexpr int BAR_OFF = ST * PITCH_S + 2 * KVW;
constexpr int SMEM_BYTES = BAR_OFF + 512;
constexpr int LEAD_S = 4, LEAD_B = 3;
constexpr int PRE0 = 1;
constexpr int GLAG = 4;
constexpr int CTURN = 14, CPER = 4;
constexpr int XAT = 12, ZAT = 25;
constexpr int SKEW = 1;
constexpr int LAG = 4;
constexpr int KPRE = 2, TURN = 4;
constexpr int LNROT = 120;
constexpr int QLATE = 40, QDELAY = 400, QRAMP = 5;
constexpr int W9 = 1200;
constexpr int A0 = 1200, AD = 300, AN = 2, AL = 1500;
constexpr int H0 = 3100, HD = 400, HW = 4200;
constexpr int HS2 = 5, LK1 = 7, LK2 = 14, KVGO = 6, KVGO1 = 12, CVGO = 31;
constexpr int BLK_NS = 336, GDELAY = 1280, GBIG = 960, GDELAY1 = 128, ZRAMP = 30;
constexpr uint32_t SPIN_LIMIT = 1u << 22;

constexpr int FL_H = 0, FL_U = 3, FL_KV = 8, FL_Z = 11, FL_GATE = 12, FL_DONE = 13, FL_N = 14;
struct Scratch {
  uint32_t flags[64 * 32];
  uint4 stats[S_];
  uint8_t h[32 * 72 * 1024];
  uint8_t u[72 * D_ * 128];
  uint8_t kv[D_ * KVT];
  __nv_bfloat16 z[D_ * S_];
};
__device__ __align__(1024) Scratch g_scratch;
extern __shared__ __align__(1024) uint8_t smem_raw[];
enum { M_W1, M_H, M_K, M_V, M_KV, M_KL, M_W2, M_Z, M_N };
struct Maps { CUtensorMap m[M_N]; };
struct RoleMap { uint32_t role[NCTA / 2]; uint32_t by_sm; };

template<int TB> __device__ __forceinline__ void wgmma_ss(float (&d)[96], uint32_t da, uint32_t db, int sd) {
  asm volatile("{\n.reg .pred p;\n.reg .b64 a, b;\nsetp.ne.b32 p, %98, 0;\nmov.b64 a, {%96, %100};\nmov.b64 b, {%97, %101};\n"
    "wgmma.mma_async.sync.aligned.m64n192k16.f32.bf16.bf16 {%0, %1, %2, %3, %4, %5, %6, %7, %8, %9, %10, %11, %12, %13, %14, %15, %16, %17, %18, %19, %20, %21, %22, %23, %24, %25, %26, %27, %28, %29, %30, %31, %32, %33, %34, %35, %36, %37, %38, %39, %40, %41, %42, %43, %44, %45, %46, %47, %48, %49, %50, %51, %52, %53, %54, %55, %56, %57, %58, %59, %60, %61, %62, %63, %64, %65, %66, %67, %68, %69, %70, %71, %72, %73, %74, %75, %76, %77, %78, %79, %80, %81, %82, %83, %84, %85, %86, %87, %88, %89, %90, %91, %92, %93, %94, %95}, a, b, p, 1, 1, 1, %99;\n}\n"
    : "+f"(d[0]), "+f"(d[1]), "+f"(d[2]), "+f"(d[3]), "+f"(d[4]), "+f"(d[5]), "+f"(d[6]), "+f"(d[7]), "+f"(d[8]), "+f"(d[9]), "+f"(d[10]), "+f"(d[11]), "+f"(d[12]), "+f"(d[13]), "+f"(d[14]), "+f"(d[15]), "+f"(d[16]), "+f"(d[17]), "+f"(d[18]), "+f"(d[19]), "+f"(d[20]), "+f"(d[21]), "+f"(d[22]), "+f"(d[23]), "+f"(d[24]), "+f"(d[25]), "+f"(d[26]), "+f"(d[27]), "+f"(d[28]), "+f"(d[29]), "+f"(d[30]), "+f"(d[31]), "+f"(d[32]), "+f"(d[33]), "+f"(d[34]), "+f"(d[35]), "+f"(d[36]), "+f"(d[37]), "+f"(d[38]), "+f"(d[39]), "+f"(d[40]), "+f"(d[41]), "+f"(d[42]), "+f"(d[43]), "+f"(d[44]), "+f"(d[45]), "+f"(d[46]), "+f"(d[47]), "+f"(d[48]), "+f"(d[49]), "+f"(d[50]), "+f"(d[51]), "+f"(d[52]), "+f"(d[53]), "+f"(d[54]), "+f"(d[55]), "+f"(d[56]), "+f"(d[57]), "+f"(d[58]), "+f"(d[59]), "+f"(d[60]), "+f"(d[61]), "+f"(d[62]), "+f"(d[63]), "+f"(d[64]), "+f"(d[65]), "+f"(d[66]), "+f"(d[67]), "+f"(d[68]), "+f"(d[69]), "+f"(d[70]), "+f"(d[71]), "+f"(d[72]), "+f"(d[73]), "+f"(d[74]), "+f"(d[75]), "+f"(d[76]), "+f"(d[77]), "+f"(d[78]), "+f"(d[79]), "+f"(d[80]), "+f"(d[81]), "+f"(d[82]), "+f"(d[83]), "+f"(d[84]), "+f"(d[85]), "+f"(d[86]), "+f"(d[87]), "+f"(d[88]), "+f"(d[89]), "+f"(d[90]), "+f"(d[91]), "+f"(d[92]), "+f"(d[93]), "+f"(d[94]), "+f"(d[95])
    : "r"(da), "r"(db), "r"(sd), "n"(TB), "r"(0x40000040u), "r"(TB ? 0x40u : 0x40000040u));
}
template<int TB> __device__ __forceinline__ void wgmma_ss(float (&d)[72], uint32_t da, uint32_t db, int sd) {
  asm volatile("{\n.reg .pred p;\n.reg .b64 a, b;\nsetp.ne.b32 p, %74, 0;\nmov.b64 a, {%72, %76};\nmov.b64 b, {%73, %77};\n"
    "wgmma.mma_async.sync.aligned.m64n144k16.f32.bf16.bf16 {%0, %1, %2, %3, %4, %5, %6, %7, %8, %9, %10, %11, %12, %13, %14, %15, %16, %17, %18, %19, %20, %21, %22, %23, %24, %25, %26, %27, %28, %29, %30, %31, %32, %33, %34, %35, %36, %37, %38, %39, %40, %41, %42, %43, %44, %45, %46, %47, %48, %49, %50, %51, %52, %53, %54, %55, %56, %57, %58, %59, %60, %61, %62, %63, %64, %65, %66, %67, %68, %69, %70, %71}, a, b, p, 1, 1, 1, %75;\n}\n"
    : "+f"(d[0]), "+f"(d[1]), "+f"(d[2]), "+f"(d[3]), "+f"(d[4]), "+f"(d[5]), "+f"(d[6]), "+f"(d[7]), "+f"(d[8]), "+f"(d[9]), "+f"(d[10]), "+f"(d[11]), "+f"(d[12]), "+f"(d[13]), "+f"(d[14]), "+f"(d[15]), "+f"(d[16]), "+f"(d[17]), "+f"(d[18]), "+f"(d[19]), "+f"(d[20]), "+f"(d[21]), "+f"(d[22]), "+f"(d[23]), "+f"(d[24]), "+f"(d[25]), "+f"(d[26]), "+f"(d[27]), "+f"(d[28]), "+f"(d[29]), "+f"(d[30]), "+f"(d[31]), "+f"(d[32]), "+f"(d[33]), "+f"(d[34]), "+f"(d[35]), "+f"(d[36]), "+f"(d[37]), "+f"(d[38]), "+f"(d[39]), "+f"(d[40]), "+f"(d[41]), "+f"(d[42]), "+f"(d[43]), "+f"(d[44]), "+f"(d[45]), "+f"(d[46]), "+f"(d[47]), "+f"(d[48]), "+f"(d[49]), "+f"(d[50]), "+f"(d[51]), "+f"(d[52]), "+f"(d[53]), "+f"(d[54]), "+f"(d[55]), "+f"(d[56]), "+f"(d[57]), "+f"(d[58]), "+f"(d[59]), "+f"(d[60]), "+f"(d[61]), "+f"(d[62]), "+f"(d[63]), "+f"(d[64]), "+f"(d[65]), "+f"(d[66]), "+f"(d[67]), "+f"(d[68]), "+f"(d[69]), "+f"(d[70]), "+f"(d[71])
    : "r"(da), "r"(db), "r"(sd), "n"(TB), "r"(0x40000040u), "r"(TB ? 0x40u : 0x40000040u));
}
template<int TB> __device__ __forceinline__ void wgmma_ss(float (&d)[36], uint32_t da, uint32_t db, int sd) {
  asm volatile("{\n.reg .pred p;\n.reg .b64 a, b;\nsetp.ne.b32 p, %38, 0;\nmov.b64 a, {%36, %40};\nmov.b64 b, {%37, %41};\n"
    "wgmma.mma_async.sync.aligned.m64n72k16.f32.bf16.bf16 {%0, %1, %2, %3, %4, %5, %6, %7, %8, %9, %10, %11, %12, %13, %14, %15, %16, %17, %18, %19, %20, %21, %22, %23, %24, %25, %26, %27, %28, %29, %30, %31, %32, %33, %34, %35}, a, b, p, 1, 1, 1, %39;\n}\n"
    : "+f"(d[0]), "+f"(d[1]), "+f"(d[2]), "+f"(d[3]), "+f"(d[4]), "+f"(d[5]), "+f"(d[6]), "+f"(d[7]), "+f"(d[8]), "+f"(d[9]), "+f"(d[10]), "+f"(d[11]), "+f"(d[12]), "+f"(d[13]), "+f"(d[14]), "+f"(d[15]), "+f"(d[16]), "+f"(d[17]), "+f"(d[18]), "+f"(d[19]), "+f"(d[20]), "+f"(d[21]), "+f"(d[22]), "+f"(d[23]), "+f"(d[24]), "+f"(d[25]), "+f"(d[26]), "+f"(d[27]), "+f"(d[28]), "+f"(d[29]), "+f"(d[30]), "+f"(d[31]), "+f"(d[32]), "+f"(d[33]), "+f"(d[34]), "+f"(d[35])
    : "r"(da), "r"(db), "r"(sd), "n"(TB), "r"(0x40000040u), "r"(TB ? 0x40u : 0x40000040u));
}
__device__ __forceinline__ void wgmma_rs_n32(float (&d)[16], uint32_t a0, uint32_t a1, uint32_t a2, uint32_t a3, uint64_t db, int sd) {
  asm volatile("{\n.reg .pred p;\nsetp.ne.b32 p, %21, 0;\n"
    "wgmma.mma_async.sync.aligned.m64n32k16.f32.bf16.bf16 {%0, %1, %2, %3, %4, %5, %6, %7, %8, %9, %10, %11, %12, %13, %14, %15}, {%16, %17, %18, %19}, %20, p, 1, 1, 0;\n}\n"
    : "+f"(d[0]), "+f"(d[1]), "+f"(d[2]), "+f"(d[3]), "+f"(d[4]), "+f"(d[5]), "+f"(d[6]), "+f"(d[7]), "+f"(d[8]), "+f"(d[9]), "+f"(d[10]), "+f"(d[11]), "+f"(d[12]), "+f"(d[13]), "+f"(d[14]), "+f"(d[15])
    : "r"(a0), "r"(a1), "r"(a2), "r"(a3), "l"(db), "r"(sd));
}

__device__ __forceinline__ void wg_fence() { asm volatile("wgmma.fence.sync.aligned;" ::: "memory"); }
__device__ __forceinline__ void wg_commit() { asm volatile("wgmma.commit_group.sync.aligned;" ::: "memory"); }
template <int n> __device__ __forceinline__ void wg_wait() { asm volatile("wgmma.wait_group.sync.aligned %0;" ::"n"(n) : "memory"); }
__device__ __forceinline__ uint64_t mkdesc(uint32_t addr, uint32_t lbo, uint32_t sbo, uint32_t sw) {
  return (uint64_t)((addr & 0x3FFFF) >> 4) | ((uint64_t)(lbo >> 4) << 16) | ((uint64_t)(sbo >> 4) << 32) | ((uint64_t)sw << 62);
}
__device__ __forceinline__ void mbar_init(uint32_t a, int c) { asm volatile("mbarrier.init.shared::cta.b64 [%0], %1;" ::"r"(a), "r"(c)); }
__device__ __forceinline__ void mbar_expect(uint32_t a, uint32_t b) { asm volatile("mbarrier.arrive.expect_tx.shared::cta.b64 _, [%0], %1;" ::"r"(a), "r"(b) : "memory"); }
__device__ __forceinline__ void mbar_arrive(uint32_t a) { asm volatile("mbarrier.arrive.shared::cta.b64 _, [%0];" ::"r"(a) : "memory"); }
__device__ __forceinline__ void mbar_arrive_cluster(uint32_t raddr) { asm volatile("mbarrier.arrive.shared::cluster.b64 _, [%0];" ::"r"(raddr) : "memory"); }
__device__ __forceinline__ uint32_t mapa(uint32_t a, uint32_t cta) { uint32_t r; asm("mapa.shared::cluster.u32 %0, %1, %2;" : "=r"(r) : "r"(a), "r"(cta)); return r; }
__device__ __forceinline__ void mbar_wait(uint32_t a, uint32_t ph) {
  asm volatile(
      "{\n.reg .pred p;\n.reg .u32 c;\nmov.u32 c, 0;\n"
      "WAIT_LOOP:\nmbarrier.try_wait.parity.shared::cta.b64 p, [%0], %1;\n@p bra WAIT_DONE;\n"
      "add.u32 c, c, 1;\nsetp.lt.u32 p, c, %2;\n@p bra WAIT_LOOP;\ntrap;\nWAIT_DONE:\n}" ::"r"(a), "r"(ph), "n"(SPIN_LIMIT) : "memory");
}
__device__ __forceinline__ void mbar_wait_u(uint32_t a, uint32_t ph) {
  asm volatile("{\n.reg .pred p;\nWAIT_LOOP:\nmbarrier.try_wait.parity.shared::cta.b64 p, [%0], %1;\n@!p bra WAIT_LOOP;\n}" ::"r"(a), "r"(ph) : "memory");
}
__device__ __forceinline__ uint32_t desc_lo(uint32_t addr, uint32_t lbo) { return ((addr & 0x3FFFF) >> 4) | ((lbo >> 4) << 16); }
__device__ __forceinline__ void tma2d(uint32_t dst, const CUtensorMap* m, int c0, int c1, uint32_t bar) {
  asm volatile("cp.async.bulk.tensor.2d.shared::cluster.global.mbarrier::complete_tx::bytes [%0], [%1, {%3, %4}], [%2];" ::"r"(dst), "l"(m), "r"(bar), "r"(c0), "r"(c1) : "memory");
}
__device__ __forceinline__ void bulk_g2s(uint32_t dst, const void* src, uint32_t sz, uint32_t bar) {
  asm volatile("cp.async.bulk.shared::cluster.global.mbarrier::complete_tx::bytes [%0], [%1], %2, [%3];" ::"r"(dst), "l"(src), "r"(sz), "r"(bar) : "memory");
}
__device__ __forceinline__ void bulk_s2g(void* dst, uint32_t src, uint32_t sz) {
  asm volatile("cp.async.bulk.global.shared::cta.bulk_group [%0], [%1], %2;" ::"l"(dst), "r"(src), "r"(sz) : "memory");
}
__device__ __forceinline__ uint64_t stream_policy() {
  uint64_t p;
  asm volatile("createpolicy.fractional.L2::evict_first.b64 %0, 1.0;" : "=l"(p));
  return p;
}
__device__ __forceinline__ void tma_weights(uint32_t dst, const CUtensorMap* m, int k0, int mchunk, uint32_t bar, uint64_t pol) {
  asm volatile("cp.async.bulk.tensor.3d.shared::cluster.global.mbarrier::complete_tx::bytes.L2::cache_hint [%0], [%1, {%6, %3, %4}], [%2], %5;"
               ::"r"(dst), "l"(m), "r"(bar), "r"(k0), "r"(mchunk), "l"(pol), "r"(0) : "memory");
}
__device__ __forceinline__ void tma_weights_prefetch(const CUtensorMap* m, int k0, int mchunk, uint64_t pol) {
  asm volatile("cp.async.bulk.prefetch.tensor.3d.L2.global.L2::cache_hint [%0, {%4, %1, %2}], %3;" ::"l"(m), "r"(k0), "r"(mchunk), "l"(pol), "r"(0) : "memory");
}
__device__ __forceinline__ bool elect_one() {
  uint32_t p;
  asm volatile("{\n.reg .pred P;\nelect.sync _|P, 0xffffffff;\nselp.u32 %0, 1, 0, P;\n}" : "=r"(p));
  return p;
}
__device__ __forceinline__ void bulk_g2s_stream(uint32_t dst, const void* src, uint32_t sz, uint32_t bar, uint64_t pol) {
  asm volatile("cp.async.bulk.shared::cluster.global.mbarrier::complete_tx::bytes.L2::cache_hint [%0], [%1], %2, [%3], %4;"
               ::"r"(dst), "l"(src), "r"(sz), "r"(bar), "l"(pol) : "memory");
}
__device__ __forceinline__ void tma3d_store(const CUtensorMap* m, int c1, int c2, uint32_t src) {
  asm volatile("cp.async.bulk.tensor.3d.global.shared::cta.bulk_group [%0, {%4, %2, %3}], [%1];" ::"l"(m), "r"(src), "r"(c1), "r"(c2), "r"(0) : "memory");
}
__device__ __forceinline__ void tma2d_stream(uint32_t dst, const CUtensorMap* m, int c0, int c1, uint32_t bar, uint64_t pol) {
  asm volatile("cp.async.bulk.tensor.2d.shared::cluster.global.mbarrier::complete_tx::bytes.L2::cache_hint [%0], [%1, {%3, %4}], [%2], %5;"
               ::"r"(dst), "l"(m), "r"(bar), "r"(c0), "r"(c1), "l"(pol) : "memory");
}
__device__ __forceinline__ void tma4d_store(const CUtensorMap* m, int c1, int c2, int c3, uint32_t src) {
  asm volatile("cp.async.bulk.tensor.4d.global.shared::cta.bulk_group [%0, {%5, %2, %3, %4}], [%1];" ::"l"(m), "r"(src), "r"(c1), "r"(c2), "r"(c3), "r"(0) : "memory");
}
__device__ __forceinline__ void bulk_commit() { asm volatile("cp.async.bulk.commit_group;" ::: "memory"); }
__device__ __forceinline__ void bulk_wait_all() { asm volatile("cp.async.bulk.wait_group 0;" ::: "memory"); }
__device__ __forceinline__ void fence_async_smem() { asm volatile("fence.proxy.async.shared::cta;" ::: "memory"); }
__device__ __forceinline__ void fence_async_global() { asm volatile("fence.proxy.async.global;" ::: "memory"); }
__device__ __forceinline__ void named_bar(int id, int n) { asm volatile("bar.sync %0, %1;" ::"r"(id), "r"(n) : "memory"); }
__device__ __forceinline__ void named_arrive(int id, int n) { asm volatile("bar.arrive %0, %1;" ::"r"(id), "r"(n) : "memory"); }
__device__ __forceinline__ void flag_add(uint32_t* f, int i, uint32_t v) { asm volatile("red.relaxed.gpu.global.add.u32 [%0], %1;" ::"l"(f + i * 32), "r"(v) : "memory"); }
__device__ __forceinline__ uint32_t flag_ld(uint32_t* f, int i) { uint32_t v; asm volatile("ld.relaxed.gpu.global.u32 %0, [%1];" : "=r"(v) : "l"(f + i * 32) : "memory"); return v; }
__device__ __forceinline__ void prefetch_map(const CUtensorMap* m) { asm volatile("prefetch.tensormap [%0];" ::"l"(m) : "memory"); }
__device__ __forceinline__ void stsm4_t(uint32_t a, uint32_t r0, uint32_t r1, uint32_t r2, uint32_t r3) {
  asm volatile("stmatrix.sync.aligned.m8n8.x4.trans.shared.b16 [%0], {%1, %2, %3, %4};" ::"r"(a), "r"(r0), "r"(r1), "r"(r2), "r"(r3) : "memory");
}
__device__ __forceinline__ uint32_t lds32(uint32_t a) { uint32_t v; asm volatile("ld.shared.u32 %0, [%1];" : "=r"(v) : "r"(a) : "memory"); return v; }
__device__ __forceinline__ void sts32(uint32_t a, uint32_t v) { asm volatile("st.shared.u32 [%0], %1;" ::"r"(a), "r"(v) : "memory"); }
__device__ __forceinline__ uint4 ld_l2(const uint4* p) { uint4 v; asm volatile("ld.relaxed.gpu.global.v4.u32 {%0, %1, %2, %3}, [%4];" : "=r"(v.x), "=r"(v.y), "=r"(v.z), "=r"(v.w) : "l"(p) : "memory"); return v; }
__device__ __forceinline__ void sts128(uint32_t a, uint32_t x, uint32_t y, uint32_t z, uint32_t w) { asm volatile("st.shared.v4.u32 [%0], {%1, %2, %3, %4};" ::"r"(a), "r"(x), "r"(y), "r"(z), "r"(w) : "memory"); }
__device__ __forceinline__ uint4 lds128(uint32_t a) { uint4 v; asm volatile("ld.shared.v4.u32 {%0, %1, %2, %3}, [%4];" : "=r"(v.x), "=r"(v.y), "=r"(v.z), "=r"(v.w) : "r"(a) : "memory"); return v; }
__device__ __forceinline__ void st_async4(uint32_t raddr, uint32_t a, uint32_t b, uint32_t c, uint32_t d, uint32_t rbar) {
  asm volatile("st.async.weak.shared::cluster.mbarrier::complete_tx::bytes.v4.b32 [%0], {%1, %2, %3, %4}, [%5];" ::"r"(raddr), "r"(a), "r"(b), "r"(c), "r"(d), "r"(rbar) : "memory");
}
__device__ __forceinline__ uint32_t pack_bf16(float lo, float hi) { uint32_t r; asm("cvt.rn.bf16x2.f32 %0, %1, %2;" : "=r"(r) : "f"(hi), "f"(lo)); return r; }
__device__ __forceinline__ float bf_lo(uint32_t v) { return __uint_as_float(v << 16); }
__device__ __forceinline__ float bf_hi(uint32_t v) { return __uint_as_float(v & 0xffff0000u); }
__device__ __forceinline__ float bf_round(float x) { return bf_lo(pack_bf16(x, 0.f)); }
__device__ __forceinline__ uint32_t hmul2(uint32_t a, uint32_t b) { uint32_t r; asm("mul.rn.bf16x2 %0, %1, %2;" : "=r"(r) : "r"(a), "r"(b)); return r; }
__device__ __forceinline__ uint32_t hsub2(uint32_t a, uint32_t b) { uint32_t r; asm("sub.rn.bf16x2 %0, %1, %2;" : "=r"(r) : "r"(a), "r"(b)); return r; }
__device__ __forceinline__ uint32_t hfma2(uint32_t a, uint32_t b, uint32_t c) { uint32_t r; asm("fma.rn.bf16x2 %0, %1, %2, %3;" : "=r"(r) : "r"(a), "r"(b), "r"(c)); return r; }
__device__ __forceinline__ uint4 ldg128(const void* p) { uint4 v; asm volatile("ld.global.nc.v4.u32 {%0, %1, %2, %3}, [%4];" : "=r"(v.x), "=r"(v.y), "=r"(v.z), "=r"(v.w) : "l"(p)); return v; }
__device__ __forceinline__ uint32_t ldg16(const void* p) { uint32_t v; asm volatile("ld.global.nc.u16 %0, [%1];" : "=r"(v) : "l"(p)); return v; }
__device__ __forceinline__ float tanh_ordered(float x) { float y; asm volatile("tanh.approx.f32 %0, %1;" : "=f"(y) : "f"(x)); return y; }
__device__ __forceinline__ uint32_t tanh2_ordered(uint32_t x) { uint32_t y; asm volatile("tanh.approx.bf16x2 %0, %1;" : "=r"(y) : "r"(x)); return y; }
__device__ __forceinline__ void mma16816(float (&d)[4], uint32_t a0, uint32_t a1, uint32_t a2, uint32_t a3, uint32_t b0, uint32_t b1) {
  asm("mma.sync.aligned.m16n8k16.row.col.f32.bf16.bf16.f32 {%0, %1, %2, %3}, {%4, %5, %6, %7}, {%8, %9}, {%0, %1, %2, %3};"
      : "+f"(d[0]), "+f"(d[1]), "+f"(d[2]), "+f"(d[3]) : "r"(a0), "r"(a1), "r"(a2), "r"(a3), "r"(b0), "r"(b1));
}
__device__ __forceinline__ uint32_t hadd2(uint32_t a, uint32_t b) { uint32_t r; asm("add.rn.bf16x2 %0, %1, %2;" : "=r"(r) : "r"(a), "r"(b)); return r; }
__device__ __forceinline__ uint32_t ldg32(const void* p) { uint32_t v; asm volatile("ld.global.nc.L1::no_allocate.u32 %0, [%1];" : "=r"(v) : "l"(p)); return v; }
__device__ __forceinline__ uint2 lds64(uint32_t a) { uint2 v; asm volatile("ld.shared.v2.u32 {%0, %1}, [%2];" : "=r"(v.x), "=r"(v.y) : "r"(a) : "memory"); return v; }
__device__ __forceinline__ uint32_t lds32_if(uint32_t a, uint32_t on) {
  uint32_t v;
  asm volatile("{\n.reg .pred p;\nsetp.ne.u32 p, %2, 0;\n@p ld.shared.u32 %0, [%1];\n}" : "=r"(v) : "r"(a), "r"(on) : "memory");
  return v;
}
__device__ __forceinline__ uint32_t clock_now() { uint32_t t; asm volatile("mov.u32 %0, %%clock;" : "=r"(t)); return t; }
__device__ __forceinline__ uint32_t time_now() { uint32_t t; asm volatile("mov.u32 %0, %%globaltimer_lo;" : "=r"(t)); return t; }
__device__ __forceinline__ void spin_until(uint32_t t0, uint32_t n) { while (clock_now() - t0 < n) {} }
__device__ __forceinline__ uint2 ldg64_if(const void* p, uint32_t on) {
  uint2 v;
  asm volatile("{\n.reg .pred p;\nsetp.ne.u32 p, %3, 0;\n@p ld.global.nc.v2.u32 {%0, %1}, [%2];\n}" : "=r"(v.x), "=r"(v.y) : "l"(p), "r"(on));
  return v;
}
template <class T> __device__ __forceinline__ T pin(T v) { asm volatile("" : "+r"(v)); return v; }
__device__ __forceinline__ void st_async2(uint32_t raddr, uint32_t a, uint32_t b, uint32_t rbar) {
  asm volatile("st.async.weak.shared::cluster.mbarrier::complete_tx::bytes.v2.b32 [%0], {%1, %2}, [%3];" ::"r"(raddr), "r"(a), "r"(b), "r"(rbar) : "memory");
}
__device__ __forceinline__ void bulk_prefetch(const void* src, uint32_t sz, uint64_t pol) {
  asm volatile("cp.async.bulk.prefetch.L2.global.L2::cache_hint [%0], %1, %2;" ::"l"(src), "r"(sz), "l"(pol) : "memory");
}
__device__ __forceinline__ void bulk_wait_read() { asm volatile("cp.async.bulk.wait_group.read 0;" ::: "memory"); }
__device__ __forceinline__ uint32_t shfl_ordered(uint32_t v, int src) { uint32_t r; asm volatile("shfl.sync.idx.b32 %0, %1, %2, 0x1f, 0xffffffff;" : "=r"(r) : "r"(v), "r"(src)); return r; }
__device__ __forceinline__ int chan_pos(int d) {
  return d < 512 ? 72 * (d >> 6) + ((d & 33) | ((d & 6) << 2) | ((d >> 2) & 6)) : 72 * ((d - 512) >> 3) + 64 + (d & 7);
}

struct Ring {
  uint32_t s, ph;
  __device__ __forceinline__ void next() { if (++s == ST) { s = 0; ph ^= 1; } }
};
constexpr int B_FULL = 0, B_GO = 40, B_CFULL = 48, B_SEMPTY = 80, B_ZFULL = 96, B_RFULL = 104, B_UDONE = 120, B_KFULL = 136, B_RAW = 168, B_CVGO = 248, B_PEER = 256, B_G2GO = 264, B_KVGO = 280,
              B_EMPTY = 296, B_G1DONE = 336,
              B_CEMPTY = 344, B_SFULL = 376, B_USTG = 392, B_END = 408;

static_assert((B_EMPTY - B_GO) % 16 == 0 && (B_CEMPTY - B_EMPTY) % 16 == 0 && (B_END - B_CEMPTY) % 16 == 0, "barrier groups");

__device__ __forceinline__ void wait_counter(uint32_t* f, int idx, uint32_t want, uint32_t first, uint32_t nap) {
#pragma unroll 1
  for (uint32_t spins = 0; first != want; spins++) {
    if (nap && spins) __nanosleep(nap);
    first = flag_ld(f, idx);
    if (spins > SPIN_LIMIT) asm volatile("trap;");
  }
  fence_async_global();
}

__device__ __forceinline__ void gate_arrive(uint32_t* f, uint32_t back) {
  asm volatile("red.relaxed.gpu.global.max.u32 [%0], %1;" ::"l"(f + FL_GATE * 32 + 1), "r"(time_now() - back) : "memory");
  flag_add(f, FL_GATE, 1);
}

__device__ __forceinline__ float ln_rinv(float var) {
  float rt, rinv;
  asm("sqrt.approx.ftz.f32 %0, %1;" : "=f"(rt) : "f"(bf_round(bf_round(var) + 1e-5f)));
  asm("rcp.approx.ftz.f32 %0, %1;" : "=f"(rinv) : "f"(bf_round(rt)));
  return rinv;
}
__device__ __forceinline__ uint32_t ln_apply(uint32_t x, const uint4& st) {
  const uint32_t d = hsub2(x, st.x);
  return hfma2(d, st.y, hmul2(d, st.z));
}

__device__ __forceinline__ void polling_done(uint32_t* f, int lane) {
  unsigned old = 0;
  if (elect_one()) asm volatile("atom.relaxed.gpu.global.inc.u32 %0, [%1], 0xffff;" : "=r"(old) : "l"(f + FL_DONE * 32) : "memory");
  if (__any_sync(0xffffffffu, old == 2 * NCTA - 1)) {
    if (lane < FL_N) *(uint2*)(f + lane * 32) = make_uint2(0u, 0u);
  }
}

struct Pipe { Ring r; uint32_t prev; bool pending; };
__device__ __forceinline__ void pipe_drain(Pipe& p, uint32_t bars, bool leader) {
  wg_wait<0>();
  if (leader) mbar_arrive(bars + B_EMPTY + p.prev * 8);
  p.pending = false;
}
template <int TB, int LEAD, int R>
__device__ __forceinline__ void gemm_run(float (&acc)[R], int n, int accumulate, Pipe& p, uint32_t sb, uint32_t pitch, int wg, bool leader) {
  const uint32_t bars = sb + BAR_OFF;
  const uint32_t dA0 = desc_lo(sb + wg * 8192, 8192), dB0 = desc_lo(sb + ASZ, TB ? 128 : 16);
  constexpr int KB_STEP = TB ? 16 : 2;
#pragma unroll 1
  for (int kb = 0; kb < n; kb++) {
    if (LEAD && kb == n - LEAD && wg == 1) { if (TB) pipe_drain(p, bars, leader); named_bar(8, 256); }
    mbar_wait(bars + B_FULL + p.r.s * 8, p.r.ph);
    const uint32_t dA = dA0 + p.r.s * (pitch >> 4), dB = dB0 + p.r.s * (pitch >> 4);
    wg_fence();
    wgmma_ss<TB>(acc, dA, dB, accumulate | kb);
#pragma unroll
    for (int k = 1; k < 4; k++) wgmma_ss<TB>(acc, dA + k * 128, dB + k * KB_STEP, 1);
    wg_commit();
    wg_wait<1>();
    if (p.pending && leader) mbar_arrive(bars + B_EMPTY + p.prev * 8);
    p.pending = true;
    p.prev = p.r.s;
    p.r.next();
  }
  if (LEAD && wg == 0) named_arrive(8, 256);
}

template <int BROW0, int I0, int I1>
__device__ __forceinline__ void gemm2_part(float (&c)[36], uint32_t sb, uint32_t pitch, int wg) {
  const uint32_t dA0 = desc_lo(sb + wg * 8192, 8192), dB0 = desc_lo(sb + ASZ + BROW0 * 128, 16);
  wg_fence();
#pragma unroll
  for (int i = I0; i < I1; i++) {
    const int step = 69 - LAG + (i >> 2);
    if ((i & 3) == 0 && BROW0 == 0) mbar_wait_u(sb + BAR_OFF + B_FULL + (step % ST) * 8, (step / ST) & 1);
    if (i == 4 * LAG - TURN && BROW0 && wg == 0) named_arrive(7, 256);
    wgmma_ss<0>(c, dA0 + (step % ST) * (pitch >> 4) + (i & 3) * 128, dB0 + (step % ST) * (pitch >> 4) + (i & 3) * 2, 1);
  }
  wg_commit();
}
__device__ __forceinline__ void split_acc(const float (&acc)[72], float (&a)[36], float (&b)[36]) {
#pragma unroll
  for (int i = 0; i < 36; i++) { asm volatile("mov.b32 %0, %1;" : "=f"(a[i]) : "f"(acc[i])); asm volatile("mov.b32 %0, %1;" : "=f"(b[i]) : "f"(acc[36 + i])); }
}
template <int V0, int V1, int R, class Slice>
__device__ __forceinline__ void gelu_store(const float (&acc)[R], uint32_t bias0, uint32_t bias1, uint32_t sa, uint32_t zero, Slice slice) {
  const uint32_t bb[2] = {pin(bias0) * 0x10001u, pin(bias1) * 0x10001u};
  uint32_t x[2][4], t[2][4], dep[V1 / 8], c3 = 0x3d123d12u;
#pragma unroll
  for (int j = V0 / 8; j <= V1 / 8; j++) {
    if (j < V1 / 8) {
      if (j >= V0 / 8 + GLAG) c3 = (dep[j - GLAG] & zero) | 0x3d123d12u;
#pragma unroll
      for (int u = 0; u < 4; u++) {
        x[j & 1][u] = hadd2(pack_bf16(acc[8 * j + 2 * u], acc[8 * j + 2 * u + 1]), bb[u & 1]);
        t[j & 1][u] = tanh2_ordered(hmul2(x[j & 1][u], hfma2(hmul2(x[j & 1][u], c3), x[j & 1][u], 0x3f4c3f4cu)));
      }
    }
    if (j > V0 / 8) {
      const uint32_t *xx = x[(j - 1) & 1], *tt = t[(j - 1) & 1];
      stsm4_t(sa + (j - 1) * 2048, hfma2(xx[0], tt[0], xx[0]), hfma2(xx[1], tt[1], xx[1]), hfma2(xx[2], tt[2], xx[2]), hfma2(xx[3], tt[3], xx[3]));
      dep[j - 1] = slice(j - 1);
    }
  }
}
struct Role { int half, kind, g2_m, dt, g1_mt, g1_nt, cs, nconv, skip; uint32_t pitch; };
__device__ __forceinline__ Role get_role(const RoleMap& roles) {
  uint32_t b, sm;
  asm volatile("mov.u32 %0, %%ctaid.x;" : "=r"(b));
  asm volatile("mov.u32 %0, %%smid;" : "=r"(sm));
  const uint32_t w = roles.role[(roles.by_sm ? sm : b) >> 1];
  const int half = b & 1, kind = w & 3, m = (w >> 4) & 15, dt = (w >> 2) & 3;
  return Role{half, kind, m * 128, dt, half * 18 + (int)((w >> 8) & 31), (int)(w >> 16), (m * 4 + dt) * 2 + half,
              kind ? kind * kind : 6 - half, kind ? 1 : 2 - 2 * half, kind ? (uint32_t)PITCH_B : (uint32_t)PITCH_S};
}
__device__ __forceinline__ int g2_block(int half, int j) { return j < 0 ? 0 : half * 36 + (j < 12 ? 2 * j : j < 24 ? 2 * j - 23 : j); }
__device__ __forceinline__ int conv_chan(const Role& ro, int i) {
  const bool early = ro.kind == 0 && i < 4;
  const int big = ro.kind == 2 ? 176 + 4 * ro.cs : 48 + ro.cs, late = ro.kind ? big + i : i == 4 ? ro.cs : 96 + (ro.cs >> 1);
  const int k = early ? 2 * ro.cs + (i & 1) : late;
  return (3 * (k >> 6) + (early ? i >> 1 : 2)) * 64 + (k & 63);
}
__device__ __forceinline__ uint32_t conv_buf(uint32_t sb, int kind, int b) {
  return sb + (kind ? (b ? b + 1 : ST) * PITCH_B : b == 3 ? (36 % ST) * PITCH_S : ST * PITCH_S + b * CBUF);
}
__device__ __forceinline__ uint32_t conv_stage(uint32_t sb, int kind) { return sb + (kind ? ST * PITCH_B + CBUF : ST * PITCH_S + 3 * CBUF); }
__device__ __forceinline__ uint32_t u_stage(uint32_t sb, uint32_t pitch, int w) { return sb + (2 - w) * pitch + ASZ; }

__global__ void __cluster_dims__(2, 1, 1) __launch_bounds__(384, 1)
fused_kernel(const __nv_bfloat16* __restrict__ q, Scratch* __restrict__ gs, const __nv_bfloat16* __restrict__ b1,
             const __nv_bfloat16* __restrict__ shiftk, const __nv_bfloat16* __restrict__ ssmk, const __nv_bfloat16* __restrict__ ssmD,
             const __grid_constant__ Maps tm, const __grid_constant__ RoleMap roles, const __nv_bfloat16* __restrict__ b2,
             __nv_bfloat16* __restrict__ out) {
  const int cta = blockIdx.x;
  const int tid = threadIdx.x;

  const uint32_t t_start = clock_now();
  const int lc = (cta + LNROT) & 127;
  const uint32_t do_ln = cta < 128 && tid < 256;
  const int oct = lc + (tid & 128), ln_row = oct * 8 + ((tid >> 4) & 7), l16 = tid & 15;
  uint2 xr[9];
  const __nv_bfloat16* qrow = q + (size_t)ln_row * D_ + l16 * 4;
  asm volatile("" : "+l"(qrow));
  const int warp = __shfl_sync(0xffffffffu, tid >> 5, 0);
  if (warp < 8 || warp == 11) asm volatile("barrier.cluster.arrive.relaxed.aligned;" ::: "memory");
  if (do_ln && oct >= QLATE) spin_until(t_start, QDELAY + QRAMP * oct / 2);
#pragma unroll
  for (int i = 0; i < 9; i++) xr[i] = ldg64_if(qrow + i * 64, do_ln);
  const uint32_t sb = __shfl_sync(0xffffffffu, (uint32_t)__cvta_generic_to_shared(smem_raw), 0);
  const uint32_t bars = sb + BAR_OFF;
  const int lane = tid & 31;
  const int wg = warp >> 2;
  constexpr int LN_OFF = ST * PITCH_B;

  uint32_t look = 0;
  if (warp < 8 || warp == 11) {
    const int hq = (lane & 16) >> 3, hb = (lane & 16) + hq;
    float da[3][4] = {};
#pragma unroll
    for (int i = 0; i < 9; i++) mma16816(da[i % 3], xr[i].x, 0x3f803f80u, xr[i].y, 0x3f803f80u, xr[i].x, xr[i].y);
    const float r1 = ((da[0][2] + da[0][3]) + (da[1][2] + da[1][3])) + (da[2][2] + da[2][3]);
    const float r2 = (lane & 4) ? (da[0][1] + da[1][1]) + da[2][1] : (da[0][0] + da[1][0]) + da[2][0];
    const float s1 = __shfl_sync(0xffffffffu, r1, hq) + __shfl_sync(0xffffffffu, r1, hq + 1);
    const float s2 = (__shfl_sync(0xffffffffu, r2, hb) + __shfl_sync(0xffffffffu, r2, hb + 4)) + (__shfl_sync(0xffffffffu, r2, hb + 9) + __shfl_sync(0xffffffffu, r2, hb + 13));
    const float mean = s1 * (1.f / D_), var = fmaxf(fmaf(-mean, mean, s2 * (1.f / D_)), 0.f);
    const float rinv = ln_rinv(var), rinv2 = ln_rinv(var * rinv * rinv), scale = rinv * rinv2, shift = -bf_round((mean - bf_round(mean)) * rinv) * rinv2;
    const uint32_t m2 = pack_bf16(mean, mean), hi2 = pack_bf16(scale, scale), lo2 = pack_bf16(scale - bf_lo(hi2), scale - bf_lo(hi2)), sh2 = pack_bf16(shift, shift);
    const uint32_t hi1 = pack_bf16(rinv, rinv);
    asm volatile("{\n.reg .pred p;\nsetp.eq.u32 p, %5, 0;\n@p st.shared.v4.u32 [%0], {%1, %2, %3, %4};\n}" ::"r"(sb + LN_OFF + 18432 + tid), "r"(m2), "r"(hi1),
                 "r"(pack_bf16(rinv - bf_lo(hi1), rinv - bf_lo(hi1))), "r"(0u), "r"(tid & 0x10f) : "memory");
    const uint32_t g0 = 4 * (l16 >> 3) + 2 * (l16 & 1), hrow = sb + LN_OFF + ((tid >> 7) & 1) * 9216 + (tid & 0x70);
    const uint32_t hs0 = hrow + g0 * 128 + ((l16 >> 1) & 3) * 4, hs8 = ((hrow + (l16 >> 1) * 1152) ^ ((l16 >> 1) << 4)) + 1024 + (l16 & 1) * 8;
    uint32_t w[18];
#pragma unroll
    for (int i = 0; i < 18; i++) {
      const uint32_t d = hsub2((i & 1) ? xr[i >> 1].y : xr[i >> 1].x, m2);
      asm("max.u32 %0, %1, 1;" : "=r"(w[i]) : "r"(hfma2(d, hi2, hfma2(d, lo2, sh2))));
    }
#pragma unroll
    for (int i = 0; i < 16; i++) {
      const int gi = 9 * (i >> 1) + (i & 1);
      asm volatile("{\n.reg .pred p;\nsetp.ne.u32 p, %2, 0;\n@p st.shared.u32 [%0], %1;\n}" ::"r"((hs0 ^ ((g0 * 16 + (gi & 7) * 16) & 0x70)) + gi * 128), "r"(w[i]), "r"(do_ln) : "memory");
    }
    asm volatile("{\n.reg .pred p;\nsetp.ne.u32 p, %3, 0;\n@p st.shared.v2.u32 [%0], {%1, %2};\n}" ::"r"(hs8), "r"(w[16]), "r"(w[17]), "r"(do_ln) : "memory");
    fence_async_smem();
    if (warp < 8) named_arrive(wg, 160);
  } else if (warp != 8) {
    spin_until(t_start, W9);
  }

  if (wg == 2) {
    asm volatile("setmaxnreg.dec.sync.aligned.u32 56;");
    auto store_h = [&](int w) {
      named_bar(w, 160);
      if (cta < 128 && elect_one()) {
        tma3d_store(&tm.m[M_H], ((lc >> 3) + 16 * w) * 72, lc & 7, sb + LN_OFF + w * 9216);
        bulk_s2g(gs->stats + (lc + 128 * w) * 8, sb + LN_OFF + 18432 + w * 128, 128);
        bulk_commit();
      }
    };
    auto publish_h = [&](int w) {
      if (cta < 128 && elect_one()) { bulk_wait_all(); flag_add(gs->flags, FL_H + (w ? 2 : lc >> 6), 2 - w); }
      __syncwarp();
    };
    if (warp == 11) {
      if (lc >= 64) spin_until(t_start, HW);
      store_h(0);
      look = flag_ld(gs->flags, FL_H);
      if (lc < 64) publish_h(0);
    } else {
      if (elect_one()) {
        if (warp == 8) {
#pragma unroll
          for (int o = 0; o < B_GO; o += 8) mbar_init(bars + o, 1);
        } else {
#pragma unroll
          for (int o = 0; o < (B_EMPTY - B_GO) / 2; o += 8) mbar_init(bars + B_GO + (warp - 9) * ((B_EMPTY - B_GO) / 2) + o, 1);
#pragma unroll
          for (int o = 0; o < (B_CEMPTY - B_EMPTY) / 2; o += 8) mbar_init(bars + B_EMPTY + (warp - 9) * ((B_CEMPTY - B_EMPTY) / 2) + o, 2);
#pragma unroll
          for (int o = 0; o < (B_END - B_CEMPTY) / 2; o += 8) mbar_init(bars + B_CEMPTY + (warp - 9) * ((B_END - B_CEMPTY) / 2) + o, 4);
        }
        asm volatile("fence.mbarrier_init.release.cluster;" ::: "memory");
      }
      __syncwarp();
      asm volatile("barrier.cluster.arrive.relaxed.aligned;" ::: "memory");
#pragma unroll
      for (int k = 0; k < 3; k++) prefetch_map(&tm.m[warp == 8 ? k : 3 * warp - 25 + k]);
    }
    const Role ro = get_role(roles);
    if (warp != 8) asm volatile("barrier.cluster.wait.aligned;" ::: "memory");
    if (warp == 11) {
      Ring r{0, 1};
      const uint32_t bsz = ro.pitch - ASZ;
      const uint8_t* src = gs->h + ro.g1_nt * bsz + ST * 73728;
      named_bar(10, 64);
#pragma unroll 1
      for (int i = ST; i < 32; i++) {
        if (i == ST || i == 8 || i == 16) wait_counter(gs->flags, FL_H + (i >> 3), 128u, look, 0);
        if (i == LK1 || i == LK2) look = flag_ld(gs->flags, FL_H + (i >> 3) + 1);
        mbar_wait(bars + B_EMPTY + r.s * 8, r.ph ^ 1);
        if (elect_one()) bulk_g2s(sb + r.s * ro.pitch + ASZ, src, bsz, bars + B_FULL + r.s * 8);
        if (i == HS2) store_h(1);
        if (i == HS2 + 2 || (i == ST && lc >= 64)) publish_h(i != ST);
        if (i == KVGO1 && lane == 0) mbar_arrive(bars + B_KVGO + 8);
        if (i == KVGO && lane == 0) mbar_arrive(bars + B_KVGO);
        if (i == CVGO && lane == 0) mbar_arrive(bars + B_CVGO);
        src += 73728;
        r.next();
      }
      if (ro.kind != 2) {
        look = 0;
#pragma unroll 1
        for (int j = -1; j < 36; j++) {
          const uint8_t* su = gs->u + ((size_t)g2_block(ro.half, j) * D_ + ro.dt * 144) * 128;
          const int uc = j < 0 ? FL_U : FL_U + 1 + 2 * ro.half + (j > 16);
          if (j == -1 || j == 12 || j == 24) wait_counter(gs->flags, uc, 288u, look, 100);
          if (j == (ro.skip ? 4 : -1) || j == 3) mbar_wait_u(bars + B_UDONE + (j == 3 ? 8 : 0), 0);
          if (j >= ro.skip - 1) mbar_wait(bars + B_EMPTY + r.s * 8, r.ph ^ 1);
          if (j >= ro.skip - 1 && elect_one()) {
            bulk_g2s(sb + r.s * ro.pitch + ASZ, su + (ro.half ^ 1) * 9216, 9216, bars + B_FULL + r.s * 8);
            bulk_g2s(sb + r.s * ro.pitch + ASZ + 9216, su + ro.half * 9216, 9216, bars + B_FULL + r.s * 8);
          }
          if (j == 9 || j == 21) look = flag_ld(gs->flags, uc);
          r.next();
        }
#pragma unroll 1
        for (int o = lane; o < ST * 73728 / 16 / NG2; o += 32) ((uint4*)gs->h)[ro.cs * (ST * 73728 / 16 / NG2) + o] = make_uint4(0u, 0u, 0u, 0u);
      }
    } else if (warp == 8) {
      const uint64_t pol = stream_policy();
      Ring r{0, 0};
#pragma unroll 1
      for (int i = 0; i < 32; i++) {
        if (i < ST) spin_until(t_start, A0 + i * AD + (i >= AN ? AL : 0));
        if (i == ST) {
          asm volatile("barrier.cluster.wait.aligned;" ::: "memory");
          if (roles.by_sm) {
            uint32_t sm;
            asm volatile("mov.u32 %0, %%smid;" : "=r"(sm));
            if (elect_one()) { mbar_expect(bars + B_PEER, 8); st_async2(mapa(bars + B_END, ro.half ^ 1), sm, sm, mapa(bars + B_PEER, ro.half ^ 1)); }
            mbar_wait_u(bars + B_PEER, 0);
            if ((lds32(bars + B_END) ^ sm) != 1 || sm >= NCTA) asm volatile("trap;");
          }
        }
        if (i >= ST) mbar_wait(bars + B_EMPTY + r.s * 8, r.ph ^ 1);
        if (elect_one()) {
          mbar_expect(bars + B_FULL + r.s * 8, ro.pitch);
          tma_weights(sb + r.s * ro.pitch, &tm.m[M_W1], i * 64, ro.g1_mt * 2, bars + B_FULL + r.s * 8, pol);
        }
        r.next();
      }
      if (ro.kind != 2) {
#pragma unroll 1
        for (int j = -1; j < 36; j++) {
          if (j == 3 && ro.kind == 0) mbar_wait_u(bars + B_CEMPTY + 24, 0);
          if (j >= ro.skip - 1) mbar_wait(bars + B_EMPTY + r.s * 8, r.ph ^ 1);
          if (j >= ro.skip - 1 && elect_one()) {
            mbar_expect(bars + B_FULL + r.s * 8, PITCH_S);
            tma_weights(sb + r.s * ro.pitch, &tm.m[M_W2], g2_block(ro.half, j) * 64, ro.g2_m >> 6, bars + B_FULL + r.s * 8, pol);
            if (j == 26 + ro.dt) tma_weights_prefetch(&tm.m[M_W2], g2_block(ro.half, j + 6) * 64, ro.g2_m >> 6, pol);
          }
          r.next();
        }
        if (lane < 2) mbar_expect(bars + B_RFULL + lane * 8, 9216);
        __syncwarp();
        mbar_wait(bars + B_EMPTY + r.s * 8, r.ph ^ 1);
        if (lane == 0) mbar_arrive_cluster(mapa(bars + B_GO, ro.half ^ 1));
      }
    } else {
      const uint64_t pol = stream_policy();
      {
        const uint32_t hb = (ro.pitch - ASZ) >> 1, raw = bars + B_RAW + (warp - 9) * 40, dst = sb + ASZ + (warp - 9) * hb;
        const uint8_t* src = gs->h + (2 * ro.g1_nt + warp - 9) * hb;
        auto fetch_h = [&](int i) { if (elect_one()) { mbar_expect(raw + i * 8, hb); bulk_g2s(dst + i * ro.pitch, src + i * 73728, hb, raw + i * 8); } };
        int next = 0;
#pragma unroll 1
        for (int i = -1; i < ST; i++) {
          if (i >= 0) {
#pragma unroll 1
            for (uint32_t tries = 0;; tries++) {
              mbar_wait_u(raw + i * 8, tries & 1);
              const uint32_t pa = dst + i * ro.pitch + lane * 32 + (lane >> 2) * 4;
              uint32_t m = 1;
#pragma unroll
              for (int j = 0; j < 12; j++) m = min(m, lds32(pa + (j < 9 || ro.kind ? j : 0) * 1024));
              if (__all_sync(0xffffffffu, m)) break;
              fetch_h(i);
            }
            if (elect_one()) asm volatile("mbarrier.complete_tx.relaxed.cta.shared::cta.b64 [%0], %1;" ::"r"(bars + B_FULL + i * 8), "r"(hb) : "memory");
          }
#pragma unroll 1
          for (const int end = min(next + (i == 0 ? 1 : 2), ST); next < end; next++) {
            if (i < 0) spin_until(t_start, H0 + next * HD);
            fetch_h(next);
          }
          if (i < 0 && warp == 10) named_arrive(10, 64);
        }
      }
      const int chan = conv_chan(ro, lane < ro.nconv ? lane : 0);
      const uint32_t dskip = ldg16(ssmD + chan);
      uint4 shk;
      mbar_wait_u(bars + B_KVGO + (ro.kind ? 8 : (warp - 9) * 8), 0);
      if (ro.kind) shk = ldg128(ssmk + (size_t)chan * S_);
      else {
        const int cs = ro.cs, grp = (cs / 3) * 2 + warp - 9, cb0 = (cs % 3) * 3;
        const uint32_t kin_s = sb + ST * PITCH_S + (warp - 9) * KVW, kout = kin_s + 2 * KVIN, fb = bars + B_KFULL + (warp - 9) * 16;
        auto fetch = [&](int i) {
          if (elect_one()) {
            mbar_expect(fb + (i & 1) * 8, KVIN);
            tma2d_stream(kin_s + (i & 1) * KVIN, &tm.m[M_K], (cb0 + i) * 64, grp * 32 - 4, fb + (i & 1) * 8, pol);
            tma2d_stream(kin_s + (i & 1) * KVIN + 4608, &tm.m[M_V], (cb0 + i) * 64, grp * 32 - 1, fb + (i & 1) * 8, pol);
          }
        };
        fetch(0);
        shk = ldg128(shiftk + (cb0 * 64 + lane * 2) * 4);
#pragma unroll 1
        for (int i = 0; i < 3; i++) {
          const uint32_t w0 = __byte_perm(shk.x, shk.z, 0x5410), w1 = __byte_perm(shk.x, shk.z, 0x7632);
          const uint32_t w2 = __byte_perm(shk.y, shk.w, 0x5410), w3 = __byte_perm(shk.y, shk.w, 0x7632);
          const uint32_t ka = kin_s + (i & 1) * KVIN + lane * 4;
          mbar_wait_u(fb + (i & 1) * 8, i >> 1);
          if (i < 2) fetch(i + 1);
          shk = ldg128(i < 2 ? shiftk + ((cb0 + i + 1) * 64 + lane * 2) * 4 : ssmk + (size_t)chan * S_);
          uint32_t kr[8], vr[8], t1, t2, t3, xp;
          {
            const uint32_t k0 = lds32(ka), k1 = lds32(ka + 128), k2 = lds32(ka + 256), k3 = lds32(ka + 384), v0 = lds32(ka + 4608);
#pragma unroll
            for (int j = 0; j < 8; j++) { kr[j] = lds32(ka + 512 + j * 128); vr[j] = lds32(ka + 4736 + j * 128); }
            xp = hmul2(hfma2(k3, w0, hfma2(k2, w1, hfma2(k1, w2, hmul2(k0, w3)))), v0);
            t1 = hfma2(k3, w1, hfma2(k2, w2, hmul2(k1, w3)));
            t2 = hfma2(k3, w2, hmul2(k2, w3));
            t3 = hmul2(k3, w3);
          }
#pragma unroll 1
          for (int o = 0; o < 4; o++) {
            const uint32_t from = ka + o * 1024, to = kout + (o >> 1) * 5120 + lane * 80 + (o & 1) * 32;
#pragma unroll
            for (int m = 0; m < 8; m += 4) {
              uint32_t x[4];
#pragma unroll
              for (int j = 0; j < 4; j++) {
                x[j] = hmul2(hfma2(kr[m + j], w0, t1), vr[m + j]);
                t1 = hfma2(kr[m + j], w1, t2);
                t2 = hfma2(kr[m + j], w2, t3);
                t3 = hmul2(kr[m + j], w3);
              }
#pragma unroll
              for (int c = 0; c < 2; c++) {
                const uint32_t sel = c ? 0x7632 : 0x5410;
                sts128(to + c * 2560 + m * 4, __byte_perm(x[0], xp, sel), __byte_perm(x[1], x[0], sel), __byte_perm(x[2], x[1], sel), __byte_perm(x[3], x[2], sel));
              }
#pragma unroll
              for (int j = m; j < m + 4; j++) { kr[j] = lds32_if(from + 1536 + j * 128, o < 3); vr[j] = lds32_if(from + 5760 + j * 128, o < 3); }
              xp = x[3];
            }
            if (o & 1) {
              fence_async_smem();
              __syncwarp();
              if (elect_one()) {
                bulk_wait_all();
                if (o == 1 && i) flag_add(gs->flags, FL_KV + i - 1, 1);
                tma4d_store(&tm.m[M_KV], (cb0 + i) * 32, 0, 2 * grp + (o >> 1), kout + (o >> 1) * 5120);
                bulk_commit();
              }
              __syncwarp();
            }
          }
        }
        look = flag_ld(gs->flags, FL_KV + warp - 9);
        if (lane == 2 * (warp - 9)) bulk_prefetch(ssmk + (size_t)chan * S_, 2 * S_ * 2, pol);
        if (elect_one()) {
          bulk_wait_all();
          flag_add(gs->flags, FL_KV + 2, 1);
        }
        __syncwarp();
      }
      {
        shk.x = __byte_perm(pack_bf16(bf_lo(shk.x) + bf_lo(dskip), 0.f), shk.x, 0x7610);
        const int mid = ro.kind ? 1 : 2;
#pragma unroll 1
        for (int i = warp == 9 ? 0 : mid; i < (warp == 9 ? mid : ro.nconv); i++) {
          const int b = i & 3, d = __shfl_sync(0xffffffffu, chan, i);
          const uint32_t base = conv_buf(sb, ro.kind, b), cf = bars + B_CFULL + b * 8;
          if (ro.kind ? i < 2 : !(i & 1)) wait_counter(gs->flags, FL_KV + (ro.kind ? 2 : i >> 1), 192u, i < 4 ? look : 0u, 200);
          if (i == mid) {
            mbar_wait_u(bars + B_CVGO, 0);
            if (ro.kind) mbar_wait_u(bars + B_EMPTY + (32 % ST) * 8, ((32 / ST) & 1) ^ 1);
            else spin_until(clock_now(), 600);
          }
          if (i == mid + 1) {
            mbar_wait_u(bars + B_G1DONE, 0);
            if (lane == 4 || lane == 5) bulk_prefetch(ssmk + (size_t)chan * S_, S_ * 2, pol);
          }
          if (i >= 4) mbar_wait_u(bars + B_CEMPTY + b * 8, 0);
          if (lane == i) sts128(base + CH_OFF, shk.x, shk.y, shk.z, shk.w);
          if (lane >= 29) sts128(base + CH_OFF + (lane - 32) * 16, 0u, 0u, 0u, 0u);
          fence_async_smem();
          __syncwarp();
          if (elect_one()) mbar_expect(cf, 4080 + 64 * 160);
#pragma unroll 1
          for (int k = 0; k < 5; k++) {
            if (elect_one()) {
              if (k < 4) asm volatile("cp.async.bulk.tensor.3d.shared::cluster.global.mbarrier::complete_tx::bytes [%0], [%1, {%3, %4, %5}], [%2];"
                                      ::"r"(base + CT_OFF + k * 2560), "l"(&tm.m[M_KL]), "r"(cf), "r"(0), "r"(k * 16), "r"(d) : "memory");
              else bulk_g2s_stream(base + CH_OFF + 16, ssmk + (size_t)d * S_ + 8, 4080, cf, pol);
            }
          }
        }
      }
      if (warp == 9) {
        if (lane < 6) sts32(bars + B_END + 8 + lane * 4, chan_pos(chan));
        __syncwarp();
        if (elect_one()) {
          const uint32_t bsz = ro.pitch - ASZ;
          if (ro.kind) { mbar_wait_u(bars + B_G1DONE, 0); gate_arrive(gs->flags, GDELAY + BLK_NS - (ro.kind == 1 ? GBIG : 0)); }
#pragma unroll 1
          for (int w = 0; w < 2; w++) {
            const uint32_t src = u_stage(sb, ro.pitch, w);
            mbar_wait_u(bars + B_USTG + w * 8, 0);
            bulk_s2g(gs->u + (size_t)(2 * ro.g1_mt + w) * D_ * 128 + ro.g1_nt * bsz, src, bsz);
            bulk_commit();
#pragma unroll 1
            for (int k = 0; k < ro.skip * w; k++) {
              mbar_arrive(bars + B_FULL + (2 + k) * 8);
              mbar_arrive(bars + B_EMPTY + (2 + k) * 8);
              mbar_arrive(bars + B_EMPTY + (2 + k) * 8);
            }
            bulk_wait_read();
            mbar_arrive(bars + B_UDONE + w * 8);
            if (ro.kind && !w) continue;
            bulk_wait_all();
            flag_add(gs->flags, FL_U + (w ? 1 + 2 * ro.half + (ro.kind != 0) : 0), ro.kind ? 16 : 3 + 3 * w);
          }
#pragma unroll 1
          for (int i = 0; i < ro.nconv; i++) {
            mbar_wait_u(bars + B_SFULL + (i & 1) * 8, (i >> 1) & 1);
            bulk_s2g(gs->z + (size_t)lds32(bars + B_END + 8 + i * 4) * S_, conv_stage(sb, ro.kind) + (i & 1) * 4096, 4096);
            bulk_commit();
            if (ro.kind == 0 && i == ro.nconv - 4) gate_arrive(gs->flags, ro.skip * BLK_NS);
            bulk_wait_read();
            mbar_arrive(bars + B_SEMPTY + (i & 1) * 8);
          }
          bulk_wait_all();
          flag_add(gs->flags, FL_Z, 1);
        }
      } else if (ro.kind != 2) {
        mbar_wait_u(bars + B_G1DONE, 0);
        uint2 gate;
#pragma unroll 1
        for (uint32_t spins = 0;; spins++) {
          asm volatile("ld.relaxed.gpu.global.v2.u32 {%0, %1}, [%2];" : "=r"(gate.x), "=r"(gate.y) : "l"(gs->flags + FL_GATE * 32) : "memory");
          if (gate.x == NCTA) break;
          __nanosleep(100);
          if (spins > SPIN_LIMIT) asm volatile("trap;");
        }
#pragma unroll 1
        for (int w = 0; w < 2; w++) {
          while (time_now() - gate.y < GDELAY + ro.skip * BLK_NS + w * GDELAY1) {}
          if (lane == 0) mbar_arrive(bars + B_G2GO + (w ^ (ro.nconv & 1)) * 8);
        }
        wait_counter(gs->flags, FL_Z, NCTA, 0, 300);
        spin_until(clock_now(), ZRAMP * cta);
        if (elect_one()) {
          mbar_expect(bars + B_ZFULL, 18432);
          tma2d(sb + ST * ro.pitch, &tm.m[M_Z], ro.g2_m, ro.dt * 144 + ro.half * 72, bars + B_ZFULL);
          tma2d(sb + ST * ro.pitch + 9216, &tm.m[M_Z], ro.g2_m + 64, ro.dt * 144 + ro.half * 72, bars + B_ZFULL);
        }
      }
    }
    if (warp >= 10) polling_done(gs->flags, lane);
  } else {
    asm volatile("setmaxnreg.inc.sync.aligned.u32 224;");
    const int wi = warp & 3, g = lane >> 2, qd = lane & 3, wt = tid & 127;
    const bool leader = wt == 0;
    Pipe p{{0, 0}, 0, false};
    asm volatile("barrier.cluster.wait.aligned;" ::: "memory");
    int kind;
    {
      const Role ro = get_role(roles);
      kind = ro.kind;
      const int f0 = ro.g1_mt * 128 + wg * 64 + wi * 16 + g;
      uint32_t bias0 = ldg16(b1 + f0), bias1 = ldg16(b1 + f0 + 8);
      const uint32_t so = ((lane >> 4) * 8 + (lane & 7)) * 128 + (((2 * wi + ((lane >> 3) & 1)) ^ (lane & 7)) << 4);
      const int cB = (g >> 1) & 1, cA = g >> 2, b = 2 * wi + (g & 1), nconv = ro.nconv;
      const uint32_t toff = pin(CT_OFF + (40 * (2 * cA + cB) + 8 + b - 2 * qd) * 4);
      const int phi = 2 * cA + (qd >> 1) + cB, pp = cB ? (phi & 3) : ((phi + 3) & 3);
      const int srcB = shfl_ordered(((pp >> 1) << 4) | ((cB ^ 1) << 3) | ((g & 1) << 2) | ((pp & 1) << 1) | (qd & 1), lane);
      const bool pB1 = cB && phi < 4, pB2 = cB && phi == 4;
      const int word = (8 * cB + 2 * (phi & 3) + (qd & 1)) * 8 + b;
      const uint32_t sto = shfl_ordered(conv_stage(sb, kind) + wg * 4096 + (word ^ (((word >> 5) & 3) << 1)) * 4, lane);
      const uint32_t sa = shfl_ordered(u_stage(sb, ro.pitch, wg) + so, lane);
      uint32_t a[16][4];
      auto load_a = [&](uint32_t base, int t, uint32_t on) {
        const uint32_t pt = base + toff + (t >> 1) * 1280 + (t & 1) * 64;
        a[t][0] = lds32_if(pt + 32, on); a[t][1] = lds32_if(pt + 672, on); a[t][2] = lds32_if(pt, on); a[t][3] = lds32_if(pt + 640, on);
      };
      auto gemm1_done = [&]() {
        pipe_drain(p, bars, leader);
        if (leader) mbar_arrive(bars + B_G1DONE);
        mbar_wait_u(bars + B_EMPTY + (2 - wg) * 8, wg ^ 1);
      };
      {
        float acc[72];
        if (kind) {
          float big[96];
          gemm_run<1, LEAD_B>(big, 32, 0, p, sb, PITCH_B, wg, leader);
          if (wg == 1) named_arrive(6, 256);
          if (wg < nconv) mbar_wait_u(bars + B_CFULL + wg * 8, 0);
#pragma unroll
          for (int t = 0; t < 8; t++) load_a(conv_buf(sb, 1, wg), t, wg < nconv);
          gemm1_done();
          gelu_store<72, 96>(big, bias0, bias1, sa, 0u, [](int) { return 0u; });
#pragma unroll
          for (int i = 0; i < 72; i++) asm volatile("mov.b32 %0, %1;" : "=f"(acc[i]) : "f"(big[i]));
        } else {
          gemm_run<1, 0>(acc, 32 - LEAD_S - (wg ? 0 : PRE0), 0, p, sb, PITCH_S, wg, leader);
          if (wg == 1) pipe_drain(p, bars, leader);
          mbar_wait_u(bars + B_CFULL + wg * 8, 0);
#pragma unroll
          for (int t = 0; t < 8; t++) load_a(conv_buf(sb, 0, wg), t, 1);
          if (wg == 1) named_bar(8, 256);
          gemm_run<1, 0>(acc, LEAD_S + (wg ? 0 : PRE0), 1, p, sb, PITCH_S, wg, leader);
          named_arrive(8 - 2 * wg, 256);
          gemm1_done();
        }
        gelu_store<0, 72>(acc, bias0, bias1, sa, roles.by_sm >> 1, [&](int t) { return t + GLAG < 9 ? lds32(bars) : 0u; });
        fence_async_smem();
        __syncwarp();
        if (lane == 0) mbar_arrive(bars + B_USTG + wg * 8);
      }
      {
#pragma unroll 1
        for (int i = wg; i < nconv; i += 2) {
          const uint32_t base = conv_buf(sb, kind, i & 3), next = conv_buf(sb, kind, (i + 2) & 3);
          const uint64_t dH = mkdesc(base + CH_OFF, 16, 128, 0);
          float y[8][16];
          if (toff < CT_OFF + 32) a[0][2] = 0u;
          named_bar(6 + wg, 256);
          wg_fence();
#pragma unroll
          for (int t = 0; t < 16; t++) {
            if (t == 8) wg_fence();
            if (t == CTURN) named_arrive(7 - wg, 256);
#pragma unroll
            for (int cb = t >> 1; cb < 8; cb++) {
              wgmma_rs_n32(y[cb], a[t][0], a[t][1], a[t][2], a[t][3], dH + (32 * cb - 32 * (t >> 1) - 2 * (t & 1) - 1), t);
              const int n = 8 * t - (t >> 1) * ((t - 1) >> 1) - (t >> 1) + cb + 1;
              if (n % CPER == 0 && n / CPER <= 8) load_a(base, 7 + n / CPER, 1);
            }
          }
          wg_commit();
          const bool more = i + 2 < nconv;
          if (more) mbar_wait_u(bars + B_CFULL + ((i + 2) & 3) * 8, (i + 2) >> 2);
          mbar_wait_u(bars + B_SEMPTY + wg * 8, ((i >> 1) & 1) ^ 1);
          wg_wait<0>();
          if (lane == 0) mbar_arrive(bars + B_CEMPTY + (i & 3) * 8);
          uint32_t P[16], Q[16], R[16], o[8];
#pragma unroll
          for (int j = 0; j < 32; j++) {
            if ((j & 3) == 0) load_a(next, j >> 2, more);
            float v0 = y[j >> 2][4 * (j & 3)], v1 = y[j >> 2][4 * (j & 3) + 1];
            if (j >= 2) { v0 += y[(j - 2) >> 2][4 * ((j - 2) & 3) + 2]; v1 += y[(j - 2) >> 2][4 * ((j - 2) & 3) + 3]; }
            if (j & 1) R[j >> 1] = shfl_ordered(pack_bf16(v0, v1), lane ^ 16);
            else P[j >> 1] = pack_bf16(v0, v1);
          }
#pragma unroll
          for (int m = 0; m < 16; m++) Q[m] = hadd2(P[m], cA ? R[m] : (m ? R[m - 1] : 0u));
#pragma unroll
          for (int m = 0; m < 8; m++) o[m] = shfl_ordered(pB1 ? Q[2 * m] : (pB2 ? (m ? Q[2 * m - 1] : 0u) : Q[2 * m + 1]), srcB);
#pragma unroll
          for (int m = 0; m < 8; m++) sts32(sto + m * 512, hadd2(pB1 ? Q[2 * m + 1] : Q[2 * m], o[m]));
          fence_async_smem();
          __syncwarp();
          if (lane == 0) mbar_arrive(bars + B_SFULL + wg * 8);
        }
        if (wg == (nconv & 1)) named_bar(6 + wg, 256);
      }
    }
    if (kind != 2) {
      const Role ro = get_role(roles);
      const uint32_t pitch = ro.pitch;
      const int s0 = ro.g2_m + wg * 64 + wi * 16 + g;
      const size_t go = (size_t)s0 * D_ + ro.dt * 128 + ro.half * 64 + qd * 8, go8 = (size_t)s0 * D_ + 512 + ro.dt * 16 + ro.half * 8 + qd * 2;
      uint32_t x[2][9], sg[2][9];
      float acc[72];
      p.r = Ring{(uint32_t)(2 + ro.skip), 0};
      mbar_wait_u(bars + B_G2GO + wg * 8, 0);
      gemm_run<0, 0>(acc, XAT + 2 * wg + 1 - ro.skip, 0, p, sb, pitch, wg, leader);
#pragma unroll
      for (int J = 0; J < 4; J++) {
        const uint4 v = ldg128(q + go + (J & 1) * 8 * D_ + (J >> 1) * 32);
        x[J & 1][4 * (J >> 1)] = v.x; x[J & 1][4 * (J >> 1) + 1] = v.y; x[J & 1][4 * (J >> 1) + 2] = v.z; x[J & 1][4 * (J >> 1) + 3] = v.w;
      }
      x[0][8] = ldg32(q + go8); x[1][8] = ldg32(q + go8 + 8 * D_);
      const uint4 st0 = ld_l2(gs->stats + s0), st1 = ld_l2(gs->stats + s0 + 8);
      const uint32_t braw0 = ldg16(b2 + s0), braw1 = ldg16(b2 + s0 + 8);
      gemm_run<0, 0>(acc, ZAT - XAT, 1, p, sb, pitch, wg, leader);
      {
        const int zw = 8 * wi + (g ^ ((((ro.g2_m >> 6) + wg) & 3) << 1));
        const uint32_t za = sb + ST * pitch + wg * 9216 + qd * 256 + (zw & 3) * 4;
        mbar_wait_u(bars + B_ZFULL, 0);
#pragma unroll
        for (int j = 0; j < 9; j++) {
          sg[0][j] = lds32(za + j * 1024 + (((zw >> 2) ^ (2 * qd)) << 4));
          sg[1][j] = lds32(za + j * 1024 + 128 + (((zw >> 2) ^ (2 * qd + 1)) << 4));
        }
      }
      gemm_run<0, 0>(acc, 1, 1, p, sb, pitch, wg, leader);
#pragma unroll
      for (int j = 0; j < 9; j++) {
        const uint32_t z0 = __byte_perm(sg[0][j], sg[1][j], 0x5410), z1 = __byte_perm(sg[0][j], sg[1][j], 0x7632);
        sg[0][j] = hmul2(ln_apply(x[0][j], st0), z0);
        sg[1][j] = hmul2(ln_apply(x[1][j], st1), z1);
        asm volatile("" : "+r"(sg[0][j]), "+r"(sg[1][j]));
      }
      gemm_run<0, SKEW>(acc, 35 - ZAT - LAG - 2 * wg, 1, p, sb, pitch, wg, leader);
      const uint32_t rbuf = sb + (69 % ST) * pitch + warp * 2304;
      const uint32_t rdst = mapa(rbuf, ro.half ^ 1), rbar = mapa(bars + B_RFULL + wg * 8, ro.half ^ 1);
      pipe_drain(p, bars, leader);
      float cs[36], ck[36];
      split_acc(acc, cs, ck);
      gemm2_part<0, 0, 4 * LAG>(cs, sb, pitch, wg);
      if (KPRE) gemm2_part<72, 0, KPRE>(ck, sb, pitch, wg);
      const float hb0 = fmaf(bf_lo(braw0), 0.5f, __uint_as_float(st0.w)), hb1 = fmaf(bf_lo(braw1), 0.5f, __uint_as_float(st1.w));
      mbar_wait(bars + B_GO, 0);
      wg_wait<KPRE ? 1 : 0>();
#pragma unroll
      for (int i = 0; i < 5; i++) {
        const float* c = &cs[8 * i];
        const uint32_t v0 = pack_bf16(fmaf(c[0], 0.25f, hb0), fmaf(c[1], 0.25f, hb0)), v1 = pack_bf16(fmaf(c[2], 0.25f, hb1), fmaf(c[3], 0.25f, hb1));
        if (i < 4) st_async4(rdst + i * 512 + lane * 16, v0, v1, pack_bf16(fmaf(c[4], 0.25f, hb0), fmaf(c[5], 0.25f, hb0)), pack_bf16(fmaf(c[6], 0.25f, hb1), fmaf(c[7], 0.25f, hb1)), rbar);
        else st_async2(rdst + 2048 + lane * 8, v0, v1, rbar);
      }
      if (wg == 1) named_bar(7, 256);
      gemm2_part<72, KPRE, 4 * LAG>(ck, sb, pitch, wg);
      uint32_t rp[18];
      mbar_wait(bars + B_RFULL + wg * 8, 0);
#pragma unroll
      for (int m = 0; m < 4; m++) {
        const uint4 v = lds128(rbuf + m * 512 + lane * 16);
        rp[4 * m] = v.x; rp[4 * m + 1] = v.y; rp[4 * m + 2] = v.z; rp[4 * m + 3] = v.w;
      }
      { const uint2 v = lds64(rbuf + 2048 + lane * 8); rp[16] = v.x; rp[17] = v.y; }
      __nv_bfloat16* o = out + go;
      wg_wait<0>();
      float h[2][4], t[2][4], half = 0.25f;
#pragma unroll
      for (int j = 0; j <= 9; j++) {
        if (j < 9) {
          const uint32_t ra = rp[2 * j], rb = rp[2 * j + 1];
          if (j >= 2) half = fmaf(t[j & 1][3], 0.f, 0.25f);
          h[j & 1][0] = fmaf(ck[4 * j], half, bf_lo(ra)); h[j & 1][1] = fmaf(ck[4 * j + 1], half, bf_hi(ra));
          h[j & 1][2] = fmaf(ck[4 * j + 2], half, bf_lo(rb)); h[j & 1][3] = fmaf(ck[4 * j + 3], half, bf_hi(rb));
#pragma unroll
          for (int u = 0; u < 4; u++) t[j & 1][u] = tanh_ordered(h[j & 1][u]);
        }
        if (j > 0) {
          const int k = j - 1;
          const float* hh = h[k & 1];
          const float* tt = t[k & 1];
          x[0][k] = hfma2(sg[0][k], pack_bf16(fmaf(hh[0], tt[0], hh[0]), fmaf(hh[1], tt[1], hh[1])), x[0][k]);
          x[1][k] = hfma2(sg[1][k], pack_bf16(fmaf(hh[2], tt[2], hh[2]), fmaf(hh[3], tt[3], hh[3])), x[1][k]);
          if ((k & 3) == 3) {
            *(uint4*)(o + (k >> 2) * 32) = make_uint4(x[0][k - 3], x[0][k - 2], x[0][k - 1], x[0][k]);
            *(uint4*)(o + 8 * D_ + (k >> 2) * 32) = make_uint4(x[1][k - 3], x[1][k - 2], x[1][k - 1], x[1][k]);
          }
        }
      }
      *(uint32_t*)(out + go8) = x[0][8];
      *(uint32_t*)(out + go8 + 8 * D_) = x[1][8];
    }
  }
}

typedef CUresult (*EncodeFn)(CUtensorMap*, CUtensorMapDataType, cuuint32_t, void*, const cuuint64_t*, const cuuint64_t*, const cuuint32_t*,
                             const cuuint32_t*, CUtensorMapInterleave, CUtensorMapSwizzle, CUtensorMapL2promotion, CUtensorMapFloatOOBfill);

uint32_t role_of_pair(int t) {
  int grp, i;
  if (t < 32) { const int j = t & 7; i = t >> 3; grp = j < 6 ? 1 + j : 12 + 2 * (j - 6); }
  else if (t < 60) { const int j = (t - 32) % 7; i = (t - 32) / 7; grp = j < 5 ? 7 + j : 13 + 2 * (j - 5); }
  else if (t < 62) return 2u | (uint32_t)(t - 60) << 2 | (uint32_t)(14 + 3 * (t - 60)) << 8 | 2u << 16;
  else { grp = 0; i = t - 62; }
  if (grp < 12) return (uint32_t)(i << 2 | grp << 4 | grp << 8 | i << 16);
  const int u = (grp & 1) * 4 + i;
  return (uint32_t)(1 | i << 2 | grp << 4 | (12 + 3 * ((grp - 12) >> 1) + u / 3) << 8 | (u % 3) << 16);
}

}

extern "C" void kernel_launch(void* const* d_in, const int* in_sizes, int n_in, void* d_out, int out_size) {
  (void)in_sizes; (void)n_in; (void)out_size;
  EncodeFn enc = nullptr;
  cudaDriverEntryPointQueryResult qr;
  cudaGetDriverEntryPoint("cuTensorMapEncodeTiled", (void**)&enc, cudaEnableDefault, &qr);
  Scratch* gs = nullptr;
  cudaGetSymbolAddress((void**)&gs, g_scratch);
  void *zp = gs->z, *hp = gs->h, *kvp = gs->kv;
  Maps tm;
  for (int w = 0; w < 2; w++) {
    cuuint64_t gd[2] = {D_, S_};
    cuuint64_t st[1] = {D_ * 2};
    cuuint32_t bx[2] = {64, w ? 33u : 36u};
    cuuint32_t es[2] = {1, 1};
    enc(w ? &tm.m[M_V] : &tm.m[M_K], CU_TENSOR_MAP_DATA_TYPE_BFLOAT16, 2, d_in[1 + w], gd, st, bx, es, CU_TENSOR_MAP_INTERLEAVE_NONE, CU_TENSOR_MAP_SWIZZLE_NONE,
        CU_TENSOR_MAP_L2_PROMOTION_L2_128B, CU_TENSOR_MAP_FLOAT_OOB_FILL_NONE);
  }
  {
    cuuint64_t gd[4] = {16, D_ / 2, 2, 128};
    cuuint64_t st[3] = {2 * KVT, KVT, 64};
    cuuint32_t bx[4] = {20, 32, 2, 1};
    cuuint32_t es[4] = {1, 1, 1, 1};
    enc(&tm.m[M_KV], CU_TENSOR_MAP_DATA_TYPE_UINT32, 4, kvp, gd, st, bx, es, CU_TENSOR_MAP_INTERLEAVE_NONE, CU_TENSOR_MAP_SWIZZLE_NONE,
        CU_TENSOR_MAP_L2_PROMOTION_NONE, CU_TENSOR_MAP_FLOAT_OOB_FILL_NONE);
  }
  {
    cuuint64_t gd[3] = {40, 64, D_};
    cuuint64_t st[2] = {128, KVT};
    cuuint32_t bx[3] = {40, 16, 1};
    cuuint32_t es[3] = {1, 1, 1};
    enc(&tm.m[M_KL], CU_TENSOR_MAP_DATA_TYPE_UINT32, 3, (uint8_t*)kvp - 32, gd, st, bx, es, CU_TENSOR_MAP_INTERLEAVE_NONE, CU_TENSOR_MAP_SWIZZLE_NONE,
        CU_TENSOR_MAP_L2_PROMOTION_NONE, CU_TENSOR_MAP_FLOAT_OOB_FILL_NONE);
  }
  {
    cuuint64_t gd[3] = {64, 32 * 72, 8};
    cuuint64_t st[2] = {1024, 128};
    cuuint32_t bx[3] = {64, 72, 1};
    cuuint32_t es[3] = {1, 1, 1};
    enc(&tm.m[M_H], CU_TENSOR_MAP_DATA_TYPE_BFLOAT16, 3, hp, gd, st, bx, es, CU_TENSOR_MAP_INTERLEAVE_NONE, CU_TENSOR_MAP_SWIZZLE_128B,
        CU_TENSOR_MAP_L2_PROMOTION_NONE, CU_TENSOR_MAP_FLOAT_OOB_FILL_NONE);
  }
  for (int w = 0; w < 2; w++) {
    const cuuint64_t M = w ? S_ : F_, K = w ? F_ : S_;
    cuuint64_t gd[3] = {64, K, M / 64};
    cuuint64_t st[2] = {M * 2, 128};
    cuuint32_t bx[3] = {64, 64, 2};
    cuuint32_t es[3] = {1, 1, 1};
    enc(w ? &tm.m[M_W2] : &tm.m[M_W1], CU_TENSOR_MAP_DATA_TYPE_BFLOAT16, 3, d_in[w ? 9 : 7], gd, st, bx, es, CU_TENSOR_MAP_INTERLEAVE_NONE,
        CU_TENSOR_MAP_SWIZZLE_128B, CU_TENSOR_MAP_L2_PROMOTION_L2_256B, CU_TENSOR_MAP_FLOAT_OOB_FILL_NONE);
  }
  {
    cuuint64_t gd[2] = {S_, D_};
    cuuint64_t st[1] = {S_ * 2};
    cuuint32_t bx[2] = {64, 72};
    cuuint32_t es[2] = {1, 1};
    enc(&tm.m[M_Z], CU_TENSOR_MAP_DATA_TYPE_BFLOAT16, 2, zp, gd, st, bx, es, CU_TENSOR_MAP_INTERLEAVE_NONE, CU_TENSOR_MAP_SWIZZLE_128B,
        CU_TENSOR_MAP_L2_PROMOTION_L2_256B, CU_TENSOR_MAP_FLOAT_OOB_FILL_NONE);
  }
  RoleMap roles;
  int dev = 0, sms = 0;
  cudaGetDevice(&dev);
  cudaDeviceGetAttribute(&sms, cudaDevAttrMultiProcessorCount, dev);
  roles.by_sm = sms == NCTA;
  for (int k = 0; k < NCTA / 2; k++) roles.role[k] = role_of_pair(k);
  cudaFuncSetAttribute(fused_kernel, cudaFuncAttributeMaxDynamicSharedMemorySize, SMEM_BYTES);
  fused_kernel<<<NCTA, 384, SMEM_BYTES>>>((const __nv_bfloat16*)d_in[0], gs, (const __nv_bfloat16*)d_in[8], (const __nv_bfloat16*)d_in[3],
                                          (const __nv_bfloat16*)d_in[4], (const __nv_bfloat16*)d_in[5], tm,
                                          roles, (const __nv_bfloat16*)d_in[10], (__nv_bfloat16*)d_out);
}
```

```cpp
#include <cuda_runtime.h>
#include <cuda_bf16.h>
#include <cuda.h>
#include <stdint.h>

namespace {

constexpr int S_ = 2048, D_ = 576, F_ = 4608;
constexpr int NCTA = 132, NG2 = 128;
constexpr int ST = 5, ASZ = 16384, PITCH_S = ASZ + 144 * 128, PITCH_B = ASZ + 192 * 128;
constexpr int CBUF = 14464, CH_OFF = 128, CT_OFF = 4224, KVT = 8192;
constexpr int KVIN = (36 + 33) * 128, KVW = 2 * CBUF;
constexpr int BAR_OFF = ST * PITCH_S + 2 * KVW;
constexpr int SMEM_BYTES = BAR_OFF + 512;
constexpr int LEAD_S = 4, LEAD_B = 3;
constexpr int PREN = 3;
constexpr int GLAG = 4;
constexpr int CTURN = 14, CPER = 4;
constexpr int XAT = 12, ZAT = 25;
constexpr int SKEW = 1;
constexpr int LAG = 4;
constexpr int KPRE = 2, TURN = 4;
constexpr int LNROT = 120;
constexpr int QLATE = 40, QDELAY = 400, QRAMP = 5;
constexpr int W9 = 1200;
constexpr int A0 = 1200, AD = 300, AN = 2, AL = 1500;
constexpr int H0 = 3100, HD = 400, HW = 4200;
constexpr int HS2 = 5, LK1 = 7, LK2 = 14, KVGO = 6, KVGO1 = 12, CVGO = 31;
constexpr int BLK_NS = 336, GDELAY = 1280, GBIG = 960, GDELAY1 = 128, ZRAMP = 30;
constexpr uint32_t SPIN_LIMIT = 1u << 22;

constexpr int FL_H = 0, FL_U = 3, FL_KV = 8, FL_Z = 11, FL_GATE = 12, FL_DONE = 13, FL_N = 14;
struct Scratch {
  uint32_t flags[64 * 32];
  uint4 stats[S_];
  uint8_t h[32 * 72 * 1024];
  uint8_t u[72 * D_ * 128];
  uint8_t kv[D_ * KVT];
  __nv_bfloat16 z[D_ * S_];
};
__device__ __align__(1024) Scratch g_scratch;
extern __shared__ __align__(1024) uint8_t smem_raw[];
enum { M_W1, M_H, M_K, M_V, M_KV, M_KL, M_W2, M_Z, M_N };
struct Maps { CUtensorMap m[M_N]; };
struct RoleMap { uint32_t role[NCTA / 2]; uint32_t by_sm; };

template<int TB> __device__ __forceinline__ void wgmma_ss(float (&d)[96], uint32_t da, uint32_t db, int sd) {
  asm volatile("{\n.reg .pred p;\n.reg .b64 a, b;\nsetp.ne.b32 p, %98, 0;\nmov.b64 a, {%96, %100};\nmov.b64 b, {%97, %101};\n"
    "wgmma.mma_async.sync.aligned.m64n192k16.f32.bf16.bf16 {%0, %1, %2, %3, %4, %5, %6, %7, %8, %9, %10, %11, %12, %13, %14, %15, %16, %17, %18, %19, %20, %21, %22, %23, %24, %25, %26, %27, %28, %29, %30, %31, %32, %33, %34, %35, %36, %37, %38, %39, %40, %41, %42, %43, %44, %45, %46, %47, %48, %49, %50, %51, %52, %53, %54, %55, %56, %57, %58, %59, %60, %61, %62, %63, %64, %65, %66, %67, %68, %69, %70, %71, %72, %73, %74, %75, %76, %77, %78, %79, %80, %81, %82, %83, %84, %85, %86, %87, %88, %89, %90, %91, %92, %93, %94, %95}, a, b, p, 1, 1, 1, %99;\n}\n"
    : "+f"(d[0]), "+f"(d[1]), "+f"(d[2]), "+f"(d[3]), "+f"(d[4]), "+f"(d[5]), "+f"(d[6]), "+f"(d[7]), "+f"(d[8]), "+f"(d[9]), "+f"(d[10]), "+f"(d[11]), "+f"(d[12]), "+f"(d[13]), "+f"(d[14]), "+f"(d[15]), "+f"(d[16]), "+f"(d[17]), "+f"(d[18]), "+f"(d[19]), "+f"(d[20]), "+f"(d[21]), "+f"(d[22]), "+f"(d[23]), "+f"(d[24]), "+f"(d[25]), "+f"(d[26]), "+f"(d[27]), "+f"(d[28]), "+f"(d[29]), "+f"(d[30]), "+f"(d[31]), "+f"(d[32]), "+f"(d[33]), "+f"(d[34]), "+f"(d[35]), "+f"(d[36]), "+f"(d[37]), "+f"(d[38]), "+f"(d[39]), "+f"(d[40]), "+f"(d[41]), "+f"(d[42]), "+f"(d[43]), "+f"(d[44]), "+f"(d[45]), "+f"(d[46]), "+f"(d[47]), "+f"(d[48]), "+f"(d[49]), "+f"(d[50]), "+f"(d[51]), "+f"(d[52]), "+f"(d[53]), "+f"(d[54]), "+f"(d[55]), "+f"(d[56]), "+f"(d[57]), "+f"(d[58]), "+f"(d[59]), "+f"(d[60]), "+f"(d[61]), "+f"(d[62]), "+f"(d[63]), "+f"(d[64]), "+f"(d[65]), "+f"(d[66]), "+f"(d[67]), "+f"(d[68]), "+f"(d[69]), "+f"(d[70]), "+f"(d[71]), "+f"(d[72]), "+f"(d[73]), "+f"(d[74]), "+f"(d[75]), "+f"(d[76]), "+f"(d[77]), "+f"(d[78]), "+f"(d[79]), "+f"(d[80]), "+f"(d[81]), "+f"(d[82]), "+f"(d[83]), "+f"(d[84]), "+f"(d[85]), "+f"(d[86]), "+f"(d[87]), "+f"(d[88]), "+f"(d[89]), "+f"(d[90]), "+f"(d[91]), "+f"(d[92]), "+f"(d[93]), "+f"(d[94]), "+f"(d[95])
    : "r"(da), "r"(db), "r"(sd), "n"(TB), "r"(0x40000040u), "r"(TB ? 0x40u : 0x40000040u));
}
template<int TB> __device__ __forceinline__ void wgmma_ss(float (&d)[72], uint32_t da, uint32_t db, int sd) {
  asm volatile("{\n.reg .pred p;\n.reg .b64 a, b;\nsetp.ne.b32 p, %74, 0;\nmov.b64 a, {%72, %76};\nmov.b64 b, {%73, %77};\n"
    "wgmma.mma_async.sync.aligned.m64n144k16.f32.bf16.bf16 {%0, %1, %2, %3, %4, %5, %6, %7, %8, %9, %10, %11, %12, %13, %14, %15, %16, %17, %18, %19, %20, %21, %22, %23, %24, %25, %26, %27, %28, %29, %30, %31, %32, %33, %34, %35, %36, %37, %38, %39, %40, %41, %42, %43, %44, %45, %46, %47, %48, %49, %50, %51, %52, %53, %54, %55, %56, %57, %58, %59, %60, %61, %62, %63, %64, %65, %66, %67, %68, %69, %70, %71}, a, b, p, 1, 1, 1, %75;\n}\n"
    : "+f"(d[0]), "+f"(d[1]), "+f"(d[2]), "+f"(d[3]), "+f"(d[4]), "+f"(d[5]), "+f"(d[6]), "+f"(d[7]), "+f"(d[8]), "+f"(d[9]), "+f"(d[10]), "+f"(d[11]), "+f"(d[12]), "+f"(d[13]), "+f"(d[14]), "+f"(d[15]), "+f"(d[16]), "+f"(d[17]), "+f"(d[18]), "+f"(d[19]), "+f"(d[20]), "+f"(d[21]), "+f"(d[22]), "+f"(d[23]), "+f"(d[24]), "+f"(d[25]), "+f"(d[26]), "+f"(d[27]), "+f"(d[28]), "+f"(d[29]), "+f"(d[30]), "+f"(d[31]), "+f"(d[32]), "+f"(d[33]), "+f"(d[34]), "+f"(d[35]), "+f"(d[36]), "+f"(d[37]), "+f"(d[38]), "+f"(d[39]), "+f"(d[40]), "+f"(d[41]), "+f"(d[42]), "+f"(d[43]), "+f"(d[44]), "+f"(d[45]), "+f"(d[46]), "+f"(d[47]), "+f"(d[48]), "+f"(d[49]), "+f"(d[50]), "+f"(d[51]), "+f"(d[52]), "+f"(d[53]), "+f"(d[54]), "+f"(d[55]), "+f"(d[56]), "+f"(d[57]), "+f"(d[58]), "+f"(d[59]), "+f"(d[60]), "+f"(d[61]), "+f"(d[62]), "+f"(d[63]), "+f"(d[64]), "+f"(d[65]), "+f"(d[66]), "+f"(d[67]), "+f"(d[68]), "+f"(d[69]), "+f"(d[70]), "+f"(d[71])
    : "r"(da), "r"(db), "r"(sd), "n"(TB), "r"(0x40000040u), "r"(TB ? 0x40u : 0x40000040u));
}
template<int TB> __device__ __forceinline__ void wgmma_ss(float (&d)[36], uint32_t da, uint32_t db, int sd) {
  asm volatile("{\n.reg .pred p;\n.reg .b64 a, b;\nsetp.ne.b32 p, %38, 0;\nmov.b64 a, {%36, %40};\nmov.b64 b, {%37, %41};\n"
    "wgmma.mma_async.sync.aligned.m64n72k16.f32.bf16.bf16 {%0, %1, %2, %3, %4, %5, %6, %7, %8, %9, %10, %11, %12, %13, %14, %15, %16, %17, %18, %19, %20, %21, %22, %23, %24, %25, %26, %27, %28, %29, %30, %31, %32, %33, %34, %35}, a, b, p, 1, 1, 1, %39;\n}\n"
    : "+f"(d[0]), "+f"(d[1]), "+f"(d[2]), "+f"(d[3]), "+f"(d[4]), "+f"(d[5]), "+f"(d[6]), "+f"(d[7]), "+f"(d[8]), "+f"(d[9]), "+f"(d[10]), "+f"(d[11]), "+f"(d[12]), "+f"(d[13]), "+f"(d[14]), "+f"(d[15]), "+f"(d[16]), "+f"(d[17]), "+f"(d[18]), "+f"(d[19]), "+f"(d[20]), "+f"(d[21]), "+f"(d[22]), "+f"(d[23]), "+f"(d[24]), "+f"(d[25]), "+f"(d[26]), "+f"(d[27]), "+f"(d[28]), "+f"(d[29]), "+f"(d[30]), "+f"(d[31]), "+f"(d[32]), "+f"(d[33]), "+f"(d[34]), "+f"(d[35])
    : "r"(da), "r"(db), "r"(sd), "n"(TB), "r"(0x40000040u), "r"(TB ? 0x40u : 0x40000040u));
}
__device__ __forceinline__ void wgmma_rs_n32(float (&d)[16], uint32_t a0, uint32_t a1, uint32_t a2, uint32_t a3, uint64_t db, int sd) {
  asm volatile("{\n.reg .pred p;\nsetp.ne.b32 p, %21, 0;\n"
    "wgmma.mma_async.sync.aligned.m64n32k16.f32.bf16.bf16 {%0, %1, %2, %3, %4, %5, %6, %7, %8, %9, %10, %11, %12, %13, %14, %15}, {%16, %17, %18, %19}, %20, p, 1, 1, 0;\n}\n"
    : "+f"(d[0]), "+f"(d[1]), "+f"(d[2]), "+f"(d[3]), "+f"(d[4]), "+f"(d[5]), "+f"(d[6]), "+f"(d[7]), "+f"(d[8]), "+f"(d[9]), "+f"(d[10]), "+f"(d[11]), "+f"(d[12]), "+f"(d[13]), "+f"(d[14]), "+f"(d[15])
    : "r"(a0), "r"(a1), "r"(a2), "r"(a3), "l"(db), "r"(sd));
}

__device__ __forceinline__ void wg_fence() { asm volatile("wgmma.fence.sync.aligned;" ::: "memory"); }
__device__ __forceinline__ void wg_commit() { asm volatile("wgmma.commit_group.sync.aligned;" ::: "memory"); }
template <int n> __device__ __forceinline__ void wg_wait() { asm volatile("wgmma.wait_group.sync.aligned %0;" ::"n"(n) : "memory"); }
__device__ __forceinline__ uint64_t mkdesc(uint32_t addr, uint32_t lbo, uint32_t sbo, uint32_t sw) {
  return (uint64_t)((addr & 0x3FFFF) >> 4) | ((uint64_t)(lbo >> 4) << 16) | ((uint64_t)(sbo >> 4) << 32) | ((uint64_t)sw << 62);
}
__device__ __forceinline__ void mbar_init(uint32_t a, int c) { asm volatile("mbarrier.init.shared::cta.b64 [%0], %1;" ::"r"(a), "r"(c)); }
__device__ __forceinline__ void mbar_expect(uint32_t a, uint32_t b) { asm volatile("mbarrier.arrive.expect_tx.shared::cta.b64 _, [%0], %1;" ::"r"(a), "r"(b) : "memory"); }
__device__ __forceinline__ void mbar_arrive(uint32_t a) { asm volatile("mbarrier.arrive.shared::cta.b64 _, [%0];" ::"r"(a) : "memory"); }
__device__ __forceinline__ void mbar_arrive_cluster(uint32_t raddr) { asm volatile("mbarrier.arrive.shared::cluster.b64 _, [%0];" ::"r"(raddr) : "memory"); }
__device__ __forceinline__ uint32_t mapa(uint32_t a, uint32_t cta) { uint32_t r; asm("mapa.shared::cluster.u32 %0, %1, %2;" : "=r"(r) : "r"(a), "r"(cta)); return r; }
__device__ __forceinline__ void mbar_wait(uint32_t a, uint32_t ph) {
  asm volatile(
      "{\n.reg .pred p;\n.reg .u32 c;\nmov.u32 c, 0;\n"
      "WAIT_LOOP:\nmbarrier.try_wait.parity.shared::cta.b64 p, [%0], %1;\n@p bra WAIT_DONE;\n"
      "add.u32 c, c, 1;\nsetp.lt.u32 p, c, %2;\n@p bra WAIT_LOOP;\ntrap;\nWAIT_DONE:\n}" ::"r"(a), "r"(ph), "n"(SPIN_LIMIT) : "memory");
}
__device__ __forceinline__ void mbar_wait_u(uint32_t a, uint32_t ph) {
  asm volatile("{\n.reg .pred p;\nWAIT_LOOP:\nmbarrier.try_wait.parity.shared::cta.b64 p, [%0], %1;\n@!p bra WAIT_LOOP;\n}" ::"r"(a), "r"(ph) : "memory");
}
__device__ __forceinline__ uint32_t desc_lo(uint32_t addr, uint32_t lbo) { return ((addr & 0x3FFFF) >> 4) | ((lbo >> 4) << 16); }
__device__ __forceinline__ void tma2d(uint32_t dst, const CUtensorMap* m, int c0, int c1, uint32_t bar) {
  asm volatile("cp.async.bulk.tensor.2d.shared::cluster.global.mbarrier::complete_tx::bytes [%0], [%1, {%3, %4}], [%2];" ::"r"(dst), "l"(m), "r"(bar), "r"(c0), "r"(c1) : "memory");
}
__device__ __forceinline__ void bulk_g2s(uint32_t dst, const void* src, uint32_t sz, uint32_t bar) {
  asm volatile("cp.async.bulk.shared::cluster.global.mbarrier::complete_tx::bytes [%0], [%1], %2, [%3];" ::"r"(dst), "l"(src), "r"(sz), "r"(bar) : "memory");
}
__device__ __forceinline__ void bulk_s2g(void* dst, uint32_t src, uint32_t sz) {
  asm volatile("cp.async.bulk.global.shared::cta.bulk_group [%0], [%1], %2;" ::"l"(dst), "r"(src), "r"(sz) : "memory");
}
__device__ __forceinline__ uint64_t stream_policy() {
  uint64_t p;
  asm volatile("createpolicy.fractional.L2::evict_first.b64 %0, 1.0;" : "=l"(p));
  return p;
}
__device__ __forceinline__ void tma_weights(uint32_t dst, const CUtensorMap* m, int k0, int mchunk, uint32_t bar, uint64_t pol) {
  asm volatile("cp.async.bulk.tensor.3d.shared::cluster.global.mbarrier::complete_tx::bytes.L2::cache_hint [%0], [%1, {%6, %3, %4}], [%2], %5;"
               ::"r"(dst), "l"(m), "r"(bar), "r"(k0), "r"(mchunk), "l"(pol), "r"(0) : "memory");
}
__device__ __forceinline__ void tma_weights_prefetch(const CUtensorMap* m, int k0, int mchunk, uint64_t pol) {
  asm volatile("cp.async.bulk.prefetch.tensor.3d.L2.global.L2::cache_hint [%0, {%4, %1, %2}], %3;" ::"l"(m), "r"(k0), "r"(mchunk), "l"(pol), "r"(0) : "memory");
}
__device__ __forceinline__ bool elect_one() {
  uint32_t p;
  asm volatile("{\n.reg .pred P;\nelect.sync _|P, 0xffffffff;\nselp.u32 %0, 1, 0, P;\n}" : "=r"(p));
  return p;
}
__device__ __forceinline__ void bulk_g2s_stream(uint32_t dst, const void* src, uint32_t sz, uint32_t bar, uint64_t pol) {
  asm volatile("cp.async.bulk.shared::cluster.global.mbarrier::complete_tx::bytes.L2::cache_hint [%0], [%1], %2, [%3], %4;"
               ::"r"(dst), "l"(src), "r"(sz), "r"(bar), "l"(pol) : "memory");
}
__device__ __forceinline__ void tma3d_store(const CUtensorMap* m, int c1, int c2, uint32_t src) {
  asm volatile("cp.async.bulk.tensor.3d.global.shared::cta.bulk_group [%0, {%4, %2, %3}], [%1];" ::"l"(m), "r"(src), "r"(c1), "r"(c2), "r"(0) : "memory");
}
__device__ __forceinline__ void tma2d_stream(uint32_t dst, const CUtensorMap* m, int c0, int c1, uint32_t bar, uint64_t pol) {
  asm volatile("cp.async.bulk.tensor.2d.shared::cluster.global.mbarrier::complete_tx::bytes.L2::cache_hint [%0], [%1, {%3, %4}], [%2], %5;"
               ::"r"(dst), "l"(m), "r"(bar), "r"(c0), "r"(c1), "l"(pol) : "memory");
}
__device__ __forceinline__ void tma4d_store(const CUtensorMap* m, int c1, int c2, int c3, uint32_t src) {
  asm volatile("cp.async.bulk.tensor.4d.global.shared::cta.bulk_group [%0, {%5, %2, %3, %4}], [%1];" ::"l"(m), "r"(src), "r"(c1), "r"(c2), "r"(c3), "r"(0) : "memory");
}
__device__ __forceinline__ void bulk_commit() { asm volatile("cp.async.bulk.commit_group;" ::: "memory"); }
__device__ __forceinline__ void bulk_wait_all() { asm volatile("cp.async.bulk.wait_group 0;" ::: "memory"); }
__device__ __forceinline__ void fence_async_smem() { asm volatile("fence.proxy.async.shared::cta;" ::: "memory"); }
__device__ __forceinline__ void fence_async_global() { asm volatile("fence.proxy.async.global;" ::: "memory"); }
__device__ __forceinline__ void named_bar(int id, int n) { asm volatile("bar.sync %0, %1;" ::"r"(id), "r"(n) : "memory"); }
__device__ __forceinline__ void named_arrive(int id, int n) { asm volatile("bar.arrive %0, %1;" ::"r"(id), "r"(n) : "memory"); }
__device__ __forceinline__ void flag_add(uint32_t* f, int i, uint32_t v) { asm volatile("red.relaxed.gpu.global.add.u32 [%0], %1;" ::"l"(f + i * 32), "r"(v) : "memory"); }
__device__ __forceinline__ uint32_t flag_ld(uint32_t* f, int i) { uint32_t v; asm volatile("ld.relaxed.gpu.global.u32 %0, [%1];" : "=r"(v) : "l"(f + i * 32) : "memory"); return v; }
__device__ __forceinline__ void prefetch_map(const CUtensorMap* m) { asm volatile("prefetch.tensormap [%0];" ::"l"(m) : "memory"); }
__device__ __forceinline__ void stsm4_t(uint32_t a, uint32_t r0, uint32_t r1, uint32_t r2, uint32_t r3) {
  asm volatile("stmatrix.sync.aligned.m8n8.x4.trans.shared.b16 [%0], {%1, %2, %3, %4};" ::"r"(a), "r"(r0), "r"(r1), "r"(r2), "r"(r3) : "memory");
}
__device__ __forceinline__ uint32_t lds32(uint32_t a) { uint32_t v; asm volatile("ld.shared.u32 %0, [%1];" : "=r"(v) : "r"(a) : "memory"); return v; }
__device__ __forceinline__ void sts32(uint32_t a, uint32_t v) { asm volatile("st.shared.u32 [%0], %1;" ::"r"(a), "r"(v) : "memory"); }
__device__ __forceinline__ uint4 ld_l2(const uint4* p) { uint4 v; asm volatile("ld.relaxed.gpu.global.v4.u32 {%0, %1, %2, %3}, [%4];" : "=r"(v.x), "=r"(v.y), "=r"(v.z), "=r"(v.w) : "l"(p) : "memory"); return v; }
__device__ __forceinline__ void sts128(uint32_t a, uint32_t x, uint32_t y, uint32_t z, uint32_t w) { asm volatile("st.shared.v4.u32 [%0], {%1, %2, %3, %4};" ::"r"(a), "r"(x), "r"(y), "r"(z), "r"(w) : "memory"); }
__device__ __forceinline__ uint4 lds128(uint32_t a) { uint4 v; asm volatile("ld.shared.v4.u32 {%0, %1, %2, %3}, [%4];" : "=r"(v.x), "=r"(v.y), "=r"(v.z), "=r"(v.w) : "r"(a) : "memory"); return v; }
__device__ __forceinline__ void st_async4(uint32_t raddr, uint32_t a, uint32_t b, uint32_t c, uint32_t d, uint32_t rbar) {
  asm volatile("st.async.weak.shared::cluster.mbarrier::complete_tx::bytes.v4.b32 [%0], {%1, %2, %3, %4}, [%5];" ::"r"(raddr), "r"(a), "r"(b), "r"(c), "r"(d), "r"(rbar) : "memory");
}
__device__ __forceinline__ uint32_t pack_bf16(float lo, float hi) { uint32_t r; asm("cvt.rn.bf16x2.f32 %0, %1, %2;" : "=r"(r) : "f"(hi), "f"(lo)); return r; }
__device__ __forceinline__ float bf_lo(uint32_t v) { return __uint_as_float(v << 16); }
__device__ __forceinline__ float bf_hi(uint32_t v) { return __uint_as_float(v & 0xffff0000u); }
__device__ __forceinline__ float bf_round(float x) { return bf_lo(pack_bf16(x, 0.f)); }
__device__ __forceinline__ uint32_t hmul2(uint32_t a, uint32_t b) { uint32_t r; asm("mul.rn.bf16x2 %0, %1, %2;" : "=r"(r) : "r"(a), "r"(b)); return r; }
__device__ __forceinline__ uint32_t hsub2(uint32_t a, uint32_t b) { uint32_t r; asm("sub.rn.bf16x2 %0, %1, %2;" : "=r"(r) : "r"(a), "r"(b)); return r; }
__device__ __forceinline__ uint32_t hfma2(uint32_t a, uint32_t b, uint32_t c) { uint32_t r; asm("fma.rn.bf16x2 %0, %1, %2, %3;" : "=r"(r) : "r"(a), "r"(b), "r"(c)); return r; }
__device__ __forceinline__ uint4 ldg128(const void* p) { uint4 v; asm volatile("ld.global.nc.v4.u32 {%0, %1, %2, %3}, [%4];" : "=r"(v.x), "=r"(v.y), "=r"(v.z), "=r"(v.w) : "l"(p)); return v; }
__device__ __forceinline__ uint32_t ldg16(const void* p) { uint32_t v; asm volatile("ld.global.nc.u16 %0, [%1];" : "=r"(v) : "l"(p)); return v; }
__device__ __forceinline__ float tanh_ordered(float x) { float y; asm volatile("tanh.approx.f32 %0, %1;" : "=f"(y) : "f"(x)); return y; }
__device__ __forceinline__ uint32_t tanh2_ordered(uint32_t x) { uint32_t y; asm volatile("tanh.approx.bf16x2 %0, %1;" : "=r"(y) : "r"(x)); return y; }
__device__ __forceinline__ void mma16816(float (&d)[4], uint32_t a0, uint32_t a1, uint32_t a2, uint32_t a3, uint32_t b0, uint32_t b1) {
  asm("mma.sync.aligned.m16n8k16.row.col.f32.bf16.bf16.f32 {%0, %1, %2, %3}, {%4, %5, %6, %7}, {%8, %9}, {%0, %1, %2, %3};"
      : "+f"(d[0]), "+f"(d[1]), "+f"(d[2]), "+f"(d[3]) : "r"(a0), "r"(a1), "r"(a2), "r"(a3), "r"(b0), "r"(b1));
}
__device__ __forceinline__ uint32_t hadd2(uint32_t a, uint32_t b) { uint32_t r; asm("add.rn.bf16x2 %0, %1, %2;" : "=r"(r) : "r"(a), "r"(b)); return r; }
__device__ __forceinline__ uint32_t ldg32(const void* p) { uint32_t v; asm volatile("ld.global.nc.L1::no_allocate.u32 %0, [%1];" : "=r"(v) : "l"(p)); return v; }
__device__ __forceinline__ uint2 lds64(uint32_t a) { uint2 v; asm volatile("ld.shared.v2.u32 {%0, %1}, [%2];" : "=r"(v.x), "=r"(v.y) : "r"(a) : "memory"); return v; }
__device__ __forceinline__ uint32_t lds32_if(uint32_t a, uint32_t on) {
  uint32_t v;
  asm volatile("{\n.reg .pred p;\nsetp.ne.u32 p, %2, 0;\n@p ld.shared.u32 %0, [%1];\n}" : "=r"(v) : "r"(a), "r"(on) : "memory");
  return v;
}
__device__ __forceinline__ uint32_t clock_now() { uint32_t t; asm volatile("mov.u32 %0, %%clock;" : "=r"(t)); return t; }
__device__ __forceinline__ uint32_t time_now() { uint32_t t; asm volatile("mov.u32 %0, %%globaltimer_lo;" : "=r"(t)); return t; }
__device__ __forceinline__ void spin_until(uint32_t t0, uint32_t n) { while (clock_now() - t0 < n) {} }
__device__ __forceinline__ uint2 ldg64_if(const void* p, uint32_t on) {
  uint2 v;
  asm volatile("{\n.reg .pred p;\nsetp.ne.u32 p, %3, 0;\n@p ld.global.nc.v2.u32 {%0, %1}, [%2];\n}" : "=r"(v.x), "=r"(v.y) : "l"(p), "r"(on));
  return v;
}
template <class T> __device__ __forceinline__ T pin(T v) { asm volatile("" : "+r"(v)); return v; }
__device__ __forceinline__ void st_async2(uint32_t raddr, uint32_t a, uint32_t b, uint32_t rbar) {
  asm volatile("st.async.weak.shared::cluster.mbarrier::complete_tx::bytes.v2.b32 [%0], {%1, %2}, [%3];" ::"r"(raddr), "r"(a), "r"(b), "r"(rbar) : "memory");
}
__device__ __forceinline__ void bulk_prefetch(const void* src, uint32_t sz, uint64_t pol) {
  asm volatile("cp.async.bulk.prefetch.L2.global.L2::cache_hint [%0], %1, %2;" ::"l"(src), "r"(sz), "l"(pol) : "memory");
}
__device__ __forceinline__ void bulk_wait_read() { asm volatile("cp.async.bulk.wait_group.read 0;" ::: "memory"); }
__device__ __forceinline__ uint32_t shfl_ordered(uint32_t v, int src) { uint32_t r; asm volatile("shfl.sync.idx.b32 %0, %1, %2, 0x1f, 0xffffffff;" : "=r"(r) : "r"(v), "r"(src)); return r; }
__device__ __forceinline__ int chan_pos(int d) {
  return d < 512 ? 72 * (d >> 6) + ((d & 33) | ((d & 6) << 2) | ((d >> 2) & 6)) : 72 * ((d - 512) >> 3) + 64 + (d & 7);
}

struct Ring {
  uint32_t s, ph;
  __device__ __forceinline__ void next() { if (++s == ST) { s = 0; ph ^= 1; } }
};
constexpr int B_FULL = 0, B_GO = 40, B_CFULL = 48, B_SEMPTY = 80, B_ZFULL = 96, B_RFULL = 104, B_UDONE = 120, B_KFULL = 136, B_RAW = 168, B_CVGO = 248, B_PEER = 256, B_G2GO = 264, B_KVGO = 280,
              B_EMPTY = 296, B_G1DONE = 336,
              B_CEMPTY = 344, B_SFULL = 376, B_USTG = 392, B_END = 408;

static_assert((B_EMPTY - B_GO) % 16 == 0 && (B_CEMPTY - B_EMPTY) % 16 == 0 && (B_END - B_CEMPTY) % 16 == 0, "barrier groups");

__device__ __forceinline__ void wait_counter(uint32_t* f, int idx, uint32_t want, uint32_t first, uint32_t nap) {
#pragma unroll 1
  for (uint32_t spins = 0; first != want; spins++) {
    if (nap && spins) __nanosleep(nap);
    first = flag_ld(f, idx);
    if (spins > SPIN_LIMIT) asm volatile("trap;");
  }
  fence_async_global();
}

__device__ __forceinline__ void gate_arrive(uint32_t* f, uint32_t back) {
  asm volatile("red.relaxed.gpu.global.max.u32 [%0], %1;" ::"l"(f + FL_GATE * 32 + 1), "r"(time_now() - back) : "memory");
  flag_add(f, FL_GATE, 1);
}

__device__ __forceinline__ float ln_rinv(float var) {
  float rt, rinv;
  asm("sqrt.approx.ftz.f32 %0, %1;" : "=f"(rt) : "f"(bf_round(bf_round(var) + 1e-5f)));
  asm("rcp.approx.ftz.f32 %0, %1;" : "=f"(rinv) : "f"(bf_round(rt)));
  return rinv;
}
__device__ __forceinline__ uint32_t ln_apply(uint32_t x, const uint4& st) {
  const uint32_t d = hsub2(x, st.x);
  return hfma2(d, st.y, hmul2(d, st.z));
}

__device__ __forceinline__ void polling_done(uint32_t* f, int lane) {
  unsigned old = 0;
  if (elect_one()) asm volatile("atom.relaxed.gpu.global.inc.u32 %0, [%1], 0xffff;" : "=r"(old) : "l"(f + FL_DONE * 32) : "memory");
  if (__any_sync(0xffffffffu, old == 2 * NCTA - 1)) {
    if (lane < FL_N) *(uint2*)(f + lane * 32) = make_uint2(0u, 0u);
  }
}

struct Pipe { Ring r; uint32_t prev; bool pending; };
__device__ __forceinline__ void pipe_drain(Pipe& p, uint32_t bars, bool leader) {
  wg_wait<0>();
  if (leader) mbar_arrive(bars + B_EMPTY + p.prev * 8);
  p.pending = false;
}
template <int TB, int LEAD, int R>
__device__ __forceinline__ void gemm_run(float (&acc)[R], int n, int accumulate, Pipe& p, uint32_t sb, uint32_t pitch, int wg, bool leader) {
  const uint32_t bars = sb + BAR_OFF;
  const uint32_t dA0 = desc_lo(sb + wg * 8192, 8192), dB0 = desc_lo(sb + ASZ, TB ? 128 : 16);
  constexpr int KB_STEP = TB ? 16 : 2;
#pragma unroll 1
  for (int kb = 0; kb < n; kb++) {
    if (LEAD && kb == n - LEAD && wg == 1) { if (TB) pipe_drain(p, bars, leader); named_bar(8, 256); }
    mbar_wait(bars + B_FULL + p.r.s * 8, p.r.ph);
    const uint32_t dA = dA0 + p.r.s * (pitch >> 4), dB = dB0 + p.r.s * (pitch >> 4);
    wg_fence();
    wgmma_ss<TB>(acc, dA, dB, accumulate | kb);
#pragma unroll
    for (int k = 1; k < 4; k++) wgmma_ss<TB>(acc, dA + k * 128, dB + k * KB_STEP, 1);
    wg_commit();
    wg_wait<1>();
    if (p.pending && leader) mbar_arrive(bars + B_EMPTY + p.prev * 8);
    p.pending = true;
    p.prev = p.r.s;
    p.r.next();
  }
  if (LEAD && wg == 0) named_arrive(8, 256);
}

template <int BROW0, int I0, int I1>
__device__ __forceinline__ void gemm2_part(float (&c)[36], uint32_t sb, uint32_t pitch, int wg) {
  const uint32_t dA0 = desc_lo(sb + wg * 8192, 8192), dB0 = desc_lo(sb + ASZ + BROW0 * 128, 16);
  wg_fence();
#pragma unroll
  for (int i = I0; i < I1; i++) {
    const int step = 69 - LAG + (i >> 2);
    if ((i & 3) == 0 && BROW0 == 0) mbar_wait_u(sb + BAR_OFF + B_FULL + (step % ST) * 8, (step / ST) & 1);
    if (i == 4 * LAG - TURN && BROW0 && wg == 0) named_arrive(7, 256);
    wgmma_ss<0>(c, dA0 + (step % ST) * (pitch >> 4) + (i & 3) * 128, dB0 + (step % ST) * (pitch >> 4) + (i & 3) * 2, 1);
  }
  wg_commit();
}
__device__ __forceinline__ void split_acc(const float (&acc)[72], float (&a)[36], float (&b)[36]) {
#pragma unroll
  for (int i = 0; i < 36; i++) { asm volatile("mov.b32 %0, %1;" : "=f"(a[i]) : "f"(acc[i])); asm volatile("mov.b32 %0, %1;" : "=f"(b[i]) : "f"(acc[36 + i])); }
}
template <int V0, int V1, int R, class Slice>
__device__ __forceinline__ void gelu_store(const float (&acc)[R], uint32_t bias0, uint32_t bias1, uint32_t sa, uint32_t zero, Slice slice) {
  const uint32_t bb[2] = {pin(bias0) * 0x10001u, pin(bias1) * 0x10001u};
  uint32_t x[2][4], t[2][4], dep[V1 / 8], c3 = 0x3d123d12u;
#pragma unroll
  for (int j = V0 / 8; j <= V1 / 8; j++) {
    if (j < V1 / 8) {
      if (j >= V0 / 8 + GLAG) c3 = (dep[j - GLAG] & zero) | 0x3d123d12u;
#pragma unroll
      for (int u = 0; u < 4; u++) {
        x[j & 1][u] = hadd2(pack_bf16(acc[8 * j + 2 * u], acc[8 * j + 2 * u + 1]), bb[u & 1]);
        t[j & 1][u] = tanh2_ordered(hmul2(x[j & 1][u], hfma2(hmul2(x[j & 1][u], c3), x[j & 1][u], 0x3f4c3f4cu)));
      }
    }
    if (j > V0 / 8) {
      const uint32_t *xx = x[(j - 1) & 1], *tt = t[(j - 1) & 1];
      stsm4_t(sa + (j - 1) * 2048, hfma2(xx[0], tt[0], xx[0]), hfma2(xx[1], tt[1], xx[1]), hfma2(xx[2], tt[2], xx[2]), hfma2(xx[3], tt[3], xx[3]));
      dep[j - 1] = slice(j - 1);
    }
  }
}
struct Role { int half, kind, g2_m, dt, g1_mt, g1_nt, cs, nconv, skip; uint32_t pitch; };
__device__ __forceinline__ Role get_role(const RoleMap& roles) {
  uint32_t b, sm;
  asm volatile("mov.u32 %0, %%ctaid.x;" : "=r"(b));
  asm volatile("mov.u32 %0, %%smid;" : "=r"(sm));
  const uint32_t w = roles.role[(roles.by_sm ? sm : b) >> 1];
  const int half = b & 1, kind = w & 3, m = (w >> 4) & 15, dt = (w >> 2) & 3;
  return Role{half, kind, m * 128, dt, half * 18 + (int)((w >> 8) & 31), (int)(w >> 16), (m * 4 + dt) * 2 + half,
              kind ? kind * kind : 6 - half, kind ? 1 : 2 - 2 * half, kind ? (uint32_t)PITCH_B : (uint32_t)PITCH_S};
}
__device__ __forceinline__ int g2_block(int half, int j) { return j < 0 ? 0 : half * 36 + (j < 12 ? 2 * j : j < 24 ? 2 * j - 23 : j); }
__device__ __forceinline__ int conv_chan(const Role& ro, int i) {
  const bool early = ro.kind == 0 && i < 4;
  const int big = ro.kind == 2 ? 176 + 4 * ro.cs : 48 + ro.cs, late = ro.kind ? big + i : i == 4 ? ro.cs : 96 + (ro.cs >> 1);
  const int k = early ? 2 * ro.cs + (i & 1) : late;
  return (3 * (k >> 6) + (early ? i >> 1 : 2)) * 64 + (k & 63);
}
__device__ __forceinline__ uint32_t conv_buf(uint32_t sb, int kind, int b) {
  return sb + (kind ? (b ? b + 1 : ST) * PITCH_B : b == 3 ? (36 % ST) * PITCH_S : ST * PITCH_S + b * CBUF);
}
__device__ __forceinline__ uint32_t conv_stage(uint32_t sb, int kind) { return sb + (kind ? ST * PITCH_B + CBUF : ST * PITCH_S + 3 * CBUF); }
__device__ __forceinline__ uint32_t u_stage(uint32_t sb, uint32_t pitch, int w) { return sb + (2 - w) * pitch + ASZ; }

__global__ void __cluster_dims__(2, 1, 1) __launch_bounds__(384, 1)
fused_kernel(const __nv_bfloat16* __restrict__ q, Scratch* __restrict__ gs, const __nv_bfloat16* __restrict__ b1,
             const __nv_bfloat16* __restrict__ shiftk, const __nv_bfloat16* __restrict__ ssmk, const __nv_bfloat16* __restrict__ ssmD,
             const __grid_constant__ Maps tm, const __grid_constant__ RoleMap roles, const __nv_bfloat16* __restrict__ b2,
             __nv_bfloat16* __restrict__ out) {
  const int cta = blockIdx.x;
  const int tid = threadIdx.x;

  const uint32_t t_start = clock_now();
  const int lc = (cta + LNROT) & 127;
  const uint32_t do_ln = cta < 128 && tid < 256;
  const int oct = lc + (tid & 128), ln_row = oct * 8 + ((tid >> 4) & 7), l16 = tid & 15;
  uint2 xr[9];
  const __nv_bfloat16* qrow = q + (size_t)ln_row * D_ + l16 * 4;
  asm volatile("" : "+l"(qrow));
  const int warp = __shfl_sync(0xffffffffu, tid >> 5, 0);
  if (warp < 8 || warp == 11) asm volatile("barrier.cluster.arrive.relaxed.aligned;" ::: "memory");
  if (do_ln && oct >= QLATE) spin_until(t_start, QDELAY + QRAMP * oct / 2);
#pragma unroll
  for (int i = 0; i < 9; i++) xr[i] = ldg64_if(qrow + i * 64, do_ln);
  const uint32_t sb = __shfl_sync(0xffffffffu, (uint32_t)__cvta_generic_to_shared(smem_raw), 0);
  const uint32_t bars = sb + BAR_OFF;
  const int lane = tid & 31;
  const int wg = warp >> 2;
  constexpr int LN_OFF = ST * PITCH_B;

  uint32_t look = 0;
  if (warp < 8 || warp == 11) {
    const int hq = (lane & 16) >> 3, hb = (lane & 16) + hq;
    float da[3][4] = {};
#pragma unroll
    for (int i = 0; i < 9; i++) mma16816(da[i % 3], xr[i].x, 0x3f803f80u, xr[i].y, 0x3f803f80u, xr[i].x, xr[i].y);
    const float r1 = ((da[0][2] + da[0][3]) + (da[1][2] + da[1][3])) + (da[2][2] + da[2][3]);
    const float r2 = (lane & 4) ? (da[0][1] + da[1][1]) + da[2][1] : (da[0][0] + da[1][0]) + da[2][0];
    const float s1 = __shfl_sync(0xffffffffu, r1, hq) + __shfl_sync(0xffffffffu, r1, hq + 1);
    const float s2 = (__shfl_sync(0xffffffffu, r2, hb) + __shfl_sync(0xffffffffu, r2, hb + 4)) + (__shfl_sync(0xffffffffu, r2, hb + 9) + __shfl_sync(0xffffffffu, r2, hb + 13));
    const float mean = s1 * (1.f / D_), var = fmaxf(fmaf(-mean, mean, s2 * (1.f / D_)), 0.f);
    const float rinv = ln_rinv(var), rinv2 = ln_rinv(var * rinv * rinv), scale = rinv * rinv2, shift = -bf_round((mean - bf_round(mean)) * rinv) * rinv2;
    const uint32_t m2 = pack_bf16(mean, mean), hi2 = pack_bf16(scale, scale), lo2 = pack_bf16(scale - bf_lo(hi2), scale - bf_lo(hi2)), sh2 = pack_bf16(shift, shift);
    const uint32_t hi1 = pack_bf16(rinv, rinv);
    asm volatile("{\n.reg .pred p;\nsetp.eq.u32 p, %5, 0;\n@p st.shared.v4.u32 [%0], {%1, %2, %3, %4};\n}" ::"r"(sb + LN_OFF + 18432 + tid), "r"(m2), "r"(hi1),
                 "r"(pack_bf16(rinv - bf_lo(hi1), rinv - bf_lo(hi1))), "r"(0u), "r"(tid & 0x10f) : "memory");
    const uint32_t g0 = 4 * (l16 >> 3) + 2 * (l16 & 1), hrow = sb + LN_OFF + ((tid >> 7) & 1) * 9216 + (tid & 0x70);
    const uint32_t hs0 = hrow + g0 * 128 + ((l16 >> 1) & 3) * 4, hs8 = ((hrow + (l16 >> 1) * 1152) ^ ((l16 >> 1) << 4)) + 1024 + (l16 & 1) * 8;
    uint32_t w[18];
#pragma unroll
    for (int i = 0; i < 18; i++) {
      const uint32_t d = hsub2((i & 1) ? xr[i >> 1].y : xr[i >> 1].x, m2);
      asm("max.u32 %0, %1, 1;" : "=r"(w[i]) : "r"(hfma2(d, hi2, hfma2(d, lo2, sh2))));
    }
#pragma unroll
    for (int i = 0; i < 16; i++) {
      const int gi = 9 * (i >> 1) + (i & 1);
      asm volatile("{\n.reg .pred p;\nsetp.ne.u32 p, %2, 0;\n@p st.shared.u32 [%0], %1;\n}" ::"r"((hs0 ^ ((g0 * 16 + (gi & 7) * 16) & 0x70)) + gi * 128), "r"(w[i]), "r"(do_ln) : "memory");
    }
    asm volatile("{\n.reg .pred p;\nsetp.ne.u32 p, %3, 0;\n@p st.shared.v2.u32 [%0], {%1, %2};\n}" ::"r"(hs8), "r"(w[16]), "r"(w[17]), "r"(do_ln) : "memory");
    fence_async_smem();
    if (warp < 8) named_arrive(wg, 160);
  } else if (warp != 8) {
    spin_until(t_start, W9);
  }

  if (wg == 2) {
    asm volatile("setmaxnreg.dec.sync.aligned.u32 56;");
    auto store_h = [&](int w) {
      named_bar(w, 160);
      if (cta < 128 && elect_one()) {
        tma3d_store(&tm.m[M_H], ((lc >> 3) + 16 * w) * 72, lc & 7, sb + LN_OFF + w * 9216);
        bulk_s2g(gs->stats + (lc + 128 * w) * 8, sb + LN_OFF + 18432 + w * 128, 128);
        bulk_commit();
      }
    };
    auto publish_h = [&](int w) {
      if (cta < 128 && elect_one()) { bulk_wait_all(); flag_add(gs->flags, FL_H + (w ? 2 : lc >> 6), 2 - w); }
      __syncwarp();
    };
    if (warp == 11) {
      if (lc >= 64) spin_until(t_start, HW);
      store_h(0);
      look = flag_ld(gs->flags, FL_H);
      if (lc < 64) publish_h(0);
    } else {
      if (elect_one()) {
        if (warp == 8) {
#pragma unroll
          for (int o = 0; o < B_GO; o += 8) mbar_init(bars + o, 1);
        } else {
#pragma unroll
          for (int o = 0; o < (B_EMPTY - B_GO) / 2; o += 8) mbar_init(bars + B_GO + (warp - 9) * ((B_EMPTY - B_GO) / 2) + o, 1);
#pragma unroll
          for (int o = 0; o < (B_CEMPTY - B_EMPTY) / 2; o += 8) mbar_init(bars + B_EMPTY + (warp - 9) * ((B_CEMPTY - B_EMPTY) / 2) + o, 2);
#pragma unroll
          for (int o = 0; o < (B_END - B_CEMPTY) / 2; o += 8) mbar_init(bars + B_CEMPTY + (warp - 9) * ((B_END - B_CEMPTY) / 2) + o, 4);
        }
        asm volatile("fence.mbarrier_init.release.cluster;" ::: "memory");
      }
      __syncwarp();
      asm volatile("barrier.cluster.arrive.relaxed.aligned;" ::: "memory");
#pragma unroll
      for (int k = 0; k < 3; k++) prefetch_map(&tm.m[warp == 8 ? k : 3 * warp - 25 + k]);
    }
    const Role ro = get_role(roles);
    if (warp != 8) asm volatile("barrier.cluster.wait.aligned;" ::: "memory");
    if (warp == 11) {
      Ring r{0, 1};
      const uint32_t bsz = ro.pitch - ASZ;
      const uint8_t* src = gs->h + ro.g1_nt * bsz + ST * 73728;
      named_bar(10, 64);
#pragma unroll 1
      for (int i = ST; i < 32; i++) {
        if (i == ST || i == 8 || i == 16) wait_counter(gs->flags, FL_H + (i >> 3), 128u, look, 0);
        if (i == LK1 || i == LK2) look = flag_ld(gs->flags, FL_H + (i >> 3) + 1);
        mbar_wait(bars + B_EMPTY + r.s * 8, r.ph ^ 1);
        if (elect_one()) bulk_g2s(sb + r.s * ro.pitch + ASZ, src, bsz, bars + B_FULL + r.s * 8);
        if (i == HS2) store_h(1);
        if (i == HS2 + 2 || (i == ST && lc >= 64)) publish_h(i != ST);
        if (i == KVGO1 && lane == 0) mbar_arrive(bars + B_KVGO + 8);
        if (i == KVGO && lane == 0) mbar_arrive(bars + B_KVGO);
        if (i == CVGO && lane == 0) mbar_arrive(bars + B_CVGO);
        src += 73728;
        r.next();
      }
      if (ro.kind != 2) {
        look = 0;
#pragma unroll 1
        for (int j = -1; j < 36; j++) {
          const uint8_t* su = gs->u + ((size_t)g2_block(ro.half, j) * D_ + ro.dt * 144) * 128;
          const int uc = j < 0 ? FL_U : FL_U + 1 + 2 * ro.half + (j > 16);
          if (j == -1 || j == 12 || j == 24) wait_counter(gs->flags, uc, 288u, look, 100);
          if (j == (ro.skip ? 4 : -1) || j == 3) mbar_wait_u(bars + B_UDONE + (j == 3 ? 8 : 0), 0);
          if (j >= ro.skip - 1) mbar_wait(bars + B_EMPTY + r.s * 8, r.ph ^ 1);
          if (j >= ro.skip - 1 && elect_one()) {
            bulk_g2s(sb + r.s * ro.pitch + ASZ, su + (ro.half ^ 1) * 9216, 9216, bars + B_FULL + r.s * 8);
            bulk_g2s(sb + r.s * ro.pitch + ASZ + 9216, su + ro.half * 9216, 9216, bars + B_FULL + r.s * 8);
          }
          if (j == 9 || j == 21) look = flag_ld(gs->flags, uc);
          r.next();
        }
#pragma unroll 1
        for (int o = lane; o < ST * 73728 / 16 / NG2; o += 32) ((uint4*)gs->h)[ro.cs * (ST * 73728 / 16 / NG2) + o] = make_uint4(0u, 0u, 0u, 0u);
      }
    } else if (warp == 8) {
      const uint64_t pol = stream_policy();
      Ring r{0, 0};
#pragma unroll 1
      for (int i = 0; i < 32; i++) {
        if (i < ST) spin_until(t_start, A0 + i * AD + (i >= AN ? AL : 0));
        if (i == ST) {
          asm volatile("barrier.cluster.wait.aligned;" ::: "memory");
          if (roles.by_sm) {
            uint32_t sm;
            asm volatile("mov.u32 %0, %%smid;" : "=r"(sm));
            if (elect_one()) { mbar_expect(bars + B_PEER, 8); st_async2(mapa(bars + B_END, ro.half ^ 1), sm, sm, mapa(bars + B_PEER, ro.half ^ 1)); }
            mbar_wait_u(bars + B_PEER, 0);
            if ((lds32(bars + B_END) ^ sm) != 1 || sm >= NCTA) asm volatile("trap;");
          }
        }
        if (i >= ST) mbar_wait(bars + B_EMPTY + r.s * 8, r.ph ^ 1);
        if (elect_one()) {
          mbar_expect(bars + B_FULL + r.s * 8, ro.pitch);
          tma_weights(sb + r.s * ro.pitch, &tm.m[M_W1], i * 64, ro.g1_mt * 2, bars + B_FULL + r.s * 8, pol);
        }
        r.next();
      }
      if (ro.kind != 2) {
#pragma unroll 1
        for (int j = -1; j < 36; j++) {
          if (j == 3 && ro.kind == 0) mbar_wait_u(bars + B_CEMPTY + 24, 0);
          if (j >= ro.skip - 1) mbar_wait(bars + B_EMPTY + r.s * 8, r.ph ^ 1);
          if (j >= ro.skip - 1 && elect_one()) {
            mbar_expect(bars + B_FULL + r.s * 8, PITCH_S);
            tma_weights(sb + r.s * ro.pitch, &tm.m[M_W2], g2_block(ro.half, j) * 64, ro.g2_m >> 6, bars + B_FULL + r.s * 8, pol);
            if (j == 26 + ro.dt) tma_weights_prefetch(&tm.m[M_W2], g2_block(ro.half, j + 6) * 64, ro.g2_m >> 6, pol);
          }
          r.next();
        }
        if (lane < 2) mbar_expect(bars + B_RFULL + lane * 8, 9216);
        __syncwarp();
        mbar_wait(bars + B_EMPTY + r.s * 8, r.ph ^ 1);
        if (lane == 0) mbar_arrive_cluster(mapa(bars + B_GO, ro.half ^ 1));
      }
    } else {
      const uint64_t pol = stream_policy();
      {
        const uint32_t hb = (ro.pitch - ASZ) >> 1, raw = bars + B_RAW + (warp - 9) * 40, dst = sb + ASZ + (warp - 9) * hb;
        const uint8_t* src = gs->h + (2 * ro.g1_nt + warp - 9) * hb;
        auto fetch_h = [&](int i) { if (elect_one()) { mbar_expect(raw + i * 8, hb); bulk_g2s(dst + i * ro.pitch, src + i * 73728, hb, raw + i * 8); } };
        int next = 0;
#pragma unroll 1
        for (int i = -1; i < ST; i++) {
          if (i >= 0) {
#pragma unroll 1
            for (uint32_t tries = 0;; tries++) {
              mbar_wait_u(raw + i * 8, tries & 1);
              const uint32_t pa = dst + i * ro.pitch + lane * 32 + (lane >> 2) * 4;
              uint32_t m = 1;
#pragma unroll
              for (int j = 0; j < 12; j++) m = min(m, lds32(pa + (j < 9 || ro.kind ? j : 0) * 1024));
              if (__all_sync(0xffffffffu, m)) break;
              fetch_h(i);
            }
            if (elect_one()) asm volatile("mbarrier.complete_tx.relaxed.cta.shared::cta.b64 [%0], %1;" ::"r"(bars + B_FULL + i * 8), "r"(hb) : "memory");
          }
#pragma unroll 1
          for (const int end = min(next + (i == 0 ? 1 : 2), ST); next < end; next++) {
            if (i < 0) spin_until(t_start, H0 + next * HD);
            fetch_h(next);
          }
          if (i < 0 && warp == 10) named_arrive(10, 64);
        }
      }
      const int chan = conv_chan(ro, lane < ro.nconv ? lane : 0);
      const uint32_t dskip = ldg16(ssmD + chan);
      uint4 shk;
      mbar_wait_u(bars + B_KVGO + (ro.kind ? 8 : (warp - 9) * 8), 0);
      if (ro.kind) shk = ldg128(ssmk + (size_t)chan * S_);
      else {
        const int cs = ro.cs, grp = (cs / 3) * 2 + warp - 9, cb0 = (cs % 3) * 3;
        const uint32_t kin_s = sb + ST * PITCH_S + (warp - 9) * KVW, kout = kin_s + 2 * KVIN, fb = bars + B_KFULL + (warp - 9) * 16;
        auto fetch = [&](int i) {
          if (elect_one()) {
            mbar_expect(fb + (i & 1) * 8, KVIN);
            tma2d_stream(kin_s + (i & 1) * KVIN, &tm.m[M_K], (cb0 + i) * 64, grp * 32 - 4, fb + (i & 1) * 8, pol);
            tma2d_stream(kin_s + (i & 1) * KVIN + 4608, &tm.m[M_V], (cb0 + i) * 64, grp * 32 - 1, fb + (i & 1) * 8, pol);
          }
        };
        fetch(0);
        shk = ldg128(shiftk + (cb0 * 64 + lane * 2) * 4);
#pragma unroll 1
        for (int i = 0; i < 3; i++) {
          const uint32_t w0 = __byte_perm(shk.x, shk.z, 0x5410), w1 = __byte_perm(shk.x, shk.z, 0x7632);
          const uint32_t w2 = __byte_perm(shk.y, shk.w, 0x5410), w3 = __byte_perm(shk.y, shk.w, 0x7632);
          const uint32_t ka = kin_s + (i & 1) * KVIN + lane * 4;
          mbar_wait_u(fb + (i & 1) * 8, i >> 1);
          if (i < 2) fetch(i + 1);
          shk = ldg128(i < 2 ? shiftk + ((cb0 + i + 1) * 64 + lane * 2) * 4 : ssmk + (size_t)chan * S_);
          uint32_t kr[8], vr[8], t1, t2, t3, xp;
          {
            const uint32_t k0 = lds32(ka), k1 = lds32(ka + 128), k2 = lds32(ka + 256), k3 = lds32(ka + 384), v0 = lds32(ka + 4608);
#pragma unroll
            for (int j = 0; j < 8; j++) { kr[j] = lds32(ka + 512 + j * 128); vr[j] = lds32(ka + 4736 + j * 128); }
            xp = hmul2(hfma2(k3, w0, hfma2(k2, w1, hfma2(k1, w2, hmul2(k0, w3)))), v0);
            t1 = hfma2(k3, w1, hfma2(k2, w2, hmul2(k1, w3)));
            t2 = hfma2(k3, w2, hmul2(k2, w3));
            t3 = hmul2(k3, w3);
          }
#pragma unroll 1
          for (int o = 0; o < 4; o++) {
            const uint32_t from = ka + o * 1024, to = kout + (o >> 1) * 5120 + lane * 80 + (o & 1) * 32;
#pragma unroll
            for (int m = 0; m < 8; m += 4) {
              uint32_t x[4];
#pragma unroll
              for (int j = 0; j < 4; j++) {
                x[j] = hmul2(hfma2(kr[m + j], w0, t1), vr[m + j]);
                t1 = hfma2(kr[m + j], w1, t2);
                t2 = hfma2(kr[m + j], w2, t3);
                t3 = hmul2(kr[m + j], w3);
              }
#pragma unroll
              for (int c = 0; c < 2; c++) {
                const uint32_t sel = c ? 0x7632 : 0x5410;
                sts128(to + c * 2560 + m * 4, __byte_perm(x[0], xp, sel), __byte_perm(x[1], x[0], sel), __byte_perm(x[2], x[1], sel), __byte_perm(x[3], x[2], sel));
              }
#pragma unroll
              for (int j = m; j < m + 4; j++) { kr[j] = lds32_if(from + 1536 + j * 128, o < 3); vr[j] = lds32_if(from + 5760 + j * 128, o < 3); }
              xp = x[3];
            }
            if (o & 1) {
              fence_async_smem();
              __syncwarp();
              if (elect_one()) {
                bulk_wait_all();
                if (o == 1 && i) flag_add(gs->flags, FL_KV + i - 1, 1);
                tma4d_store(&tm.m[M_KV], (cb0 + i) * 32, 0, 2 * grp + (o >> 1), kout + (o >> 1) * 5120);
                bulk_commit();
              }
              __syncwarp();
            }
          }
        }
        look = flag_ld(gs->flags, FL_KV + warp - 9);
        if (lane == 2 * (warp - 9)) bulk_prefetch(ssmk + (size_t)chan * S_, 2 * S_ * 2, pol);
        if (elect_one()) {
          bulk_wait_all();
          flag_add(gs->flags, FL_KV + 2, 1);
        }
        __syncwarp();
      }
      {
        shk.x = __byte_perm(pack_bf16(bf_lo(shk.x) + bf_lo(dskip), 0.f), shk.x, 0x7610);
        const int mid = ro.kind ? 1 : 2;
#pragma unroll 1
        for (int i = warp == 9 ? 0 : mid; i < (warp == 9 ? mid : ro.nconv); i++) {
          const int b = i & 3, d = __shfl_sync(0xffffffffu, chan, i);
          const uint32_t base = conv_buf(sb, ro.kind, b), cf = bars + B_CFULL + b * 8;
          if (ro.kind ? i < 2 : !(i & 1)) wait_counter(gs->flags, FL_KV + (ro.kind ? 2 : i >> 1), 192u, i < 4 ? look : 0u, 200);
          if (i == mid) {
            mbar_wait_u(bars + B_CVGO, 0);
            if (ro.kind) mbar_wait_u(bars + B_EMPTY + (32 % ST) * 8, ((32 / ST) & 1) ^ 1);
            else spin_until(clock_now(), 600);
          }
          if (i == mid + 1) {
            mbar_wait_u(bars + B_G1DONE, 0);
            if (lane == 4 || lane == 5) bulk_prefetch(ssmk + (size_t)chan * S_, S_ * 2, pol);
          }
          if (i >= 4) mbar_wait_u(bars + B_CEMPTY + b * 8, 0);
          if (lane == i) sts128(base + CH_OFF, shk.x, shk.y, shk.z, shk.w);
          if (lane >= 29) sts128(base + CH_OFF + (lane - 32) * 16, 0u, 0u, 0u, 0u);
          fence_async_smem();
          __syncwarp();
          if (elect_one()) mbar_expect(cf, 4080 + 64 * 160);
#pragma unroll 1
          for (int k = 0; k < 5; k++) {
            if (elect_one()) {
              if (k < 4) asm volatile("cp.async.bulk.tensor.3d.shared::cluster.global.mbarrier::complete_tx::bytes [%0], [%1, {%3, %4, %5}], [%2];"
                                      ::"r"(base + CT_OFF + k * 2560), "l"(&tm.m[M_KL]), "r"(cf), "r"(0), "r"(k * 16), "r"(d) : "memory");
              else bulk_g2s_stream(base + CH_OFF + 16, ssmk + (size_t)d * S_ + 8, 4080, cf, pol);
            }
          }
        }
      }
      if (warp == 9) {
        if (lane < 6) sts32(bars + B_END + 8 + lane * 4, chan_pos(chan));
        __syncwarp();
        if (elect_one()) {
          const uint32_t bsz = ro.pitch - ASZ;
          if (ro.kind) { mbar_wait_u(bars + B_G1DONE, 0); gate_arrive(gs->flags, GDELAY + BLK_NS - (ro.kind == 1 ? GBIG : 0)); }
#pragma unroll 1
          for (int w = 0; w < 2; w++) {
            const uint32_t src = u_stage(sb, ro.pitch, w);
            mbar_wait_u(bars + B_USTG + w * 8, 0);
            bulk_s2g(gs->u + (size_t)(2 * ro.g1_mt + w) * D_ * 128 + ro.g1_nt * bsz, src, bsz);
            bulk_commit();
#pragma unroll 1
            for (int k = 0; k < ro.skip * w; k++) {
              mbar_arrive(bars + B_FULL + (2 + k) * 8);
              mbar_arrive(bars + B_EMPTY + (2 + k) * 8);
              mbar_arrive(bars + B_EMPTY + (2 + k) * 8);
            }
            bulk_wait_read();
            mbar_arrive(bars + B_UDONE + w * 8);
            if (ro.kind && !w) continue;
            bulk_wait_all();
            flag_add(gs->flags, FL_U + (w ? 1 + 2 * ro.half + (ro.kind != 0) : 0), ro.kind ? 16 : 3 + 3 * w);
          }
#pragma unroll 1
          for (int i = 0; i < ro.nconv; i++) {
            mbar_wait_u(bars + B_SFULL + (i & 1) * 8, (i >> 1) & 1);
            bulk_s2g(gs->z + (size_t)lds32(bars + B_END + 8 + i * 4) * S_, conv_stage(sb, ro.kind) + (i & 1) * 4096, 4096);
            bulk_commit();
            if (ro.kind == 0 && i == ro.nconv - 4) gate_arrive(gs->flags, ro.skip * BLK_NS);
            bulk_wait_read();
            mbar_arrive(bars + B_SEMPTY + (i & 1) * 8);
          }
          bulk_wait_all();
          flag_add(gs->flags, FL_Z, 1);
        }
      } else if (ro.kind != 2) {
        mbar_wait_u(bars + B_G1DONE, 0);
        uint2 gate;
#pragma unroll 1
        for (uint32_t spins = 0;; spins++) {
          asm volatile("ld.relaxed.gpu.global.v2.u32 {%0, %1}, [%2];" : "=r"(gate.x), "=r"(gate.y) : "l"(gs->flags + FL_GATE * 32) : "memory");
          if (gate.x == NCTA) break;
          __nanosleep(100);
          if (spins > SPIN_LIMIT) asm volatile("trap;");
        }
#pragma unroll 1
        for (int w = 0; w < 2; w++) {
          while (time_now() - gate.y < GDELAY + ro.skip * BLK_NS + w * GDELAY1) {}
          if (lane == 0) mbar_arrive(bars + B_G2GO + (w ^ (ro.nconv & 1)) * 8);
        }
        wait_counter(gs->flags, FL_Z, NCTA, 0, 300);
        spin_until(clock_now(), ZRAMP * cta);
        if (elect_one()) {
          mbar_expect(bars + B_ZFULL, 18432);
          tma2d(sb + ST * ro.pitch, &tm.m[M_Z], ro.g2_m, ro.dt * 144 + ro.half * 72, bars + B_ZFULL);
          tma2d(sb + ST * ro.pitch + 9216, &tm.m[M_Z], ro.g2_m + 64, ro.dt * 144 + ro.half * 72, bars + B_ZFULL);
        }
      }
    }
    if (warp >= 10) polling_done(gs->flags, lane);
  } else {
    asm volatile("setmaxnreg.inc.sync.aligned.u32 224;");
    const int wi = warp & 3, g = lane >> 2, qd = lane & 3, wt = tid & 127;
    const bool leader = wt == 0;
    Pipe p{{0, 0}, 0, false};
    asm volatile("barrier.cluster.wait.aligned;" ::: "memory");
    int kind;
    {
      const Role ro = get_role(roles);
      kind = ro.kind;
      const int f0 = ro.g1_mt * 128 + wg * 64 + wi * 16 + g;
      uint32_t bias0 = ldg16(b1 + f0), bias1 = ldg16(b1 + f0 + 8);
      const uint32_t so = ((lane >> 4) * 8 + (lane & 7)) * 128 + (((2 * wi + ((lane >> 3) & 1)) ^ (lane & 7)) << 4);
      const int cB = (g >> 1) & 1, cA = g >> 2, b = 2 * wi + (g & 1), nconv = ro.nconv;
      const uint32_t toff = pin(CT_OFF + (40 * (2 * cA + cB) + 8 + b - 2 * qd) * 4);
      const int phi = 2 * cA + (qd >> 1) + cB, pp = cB ? (phi & 3) : ((phi + 3) & 3);
      const int srcB = shfl_ordered(((pp >> 1) << 4) | ((cB ^ 1) << 3) | ((g & 1) << 2) | ((pp & 1) << 1) | (qd & 1), lane);
      const bool pB1 = cB && phi < 4, pB2 = cB && phi == 4;
      const int word = (8 * cB + 2 * (phi & 3) + (qd & 1)) * 8 + b;
      const uint32_t sto = shfl_ordered(conv_stage(sb, kind) + wg * 4096 + (word ^ (((word >> 5) & 3) << 1)) * 4, lane);
      const uint32_t sa = shfl_ordered(u_stage(sb, ro.pitch, wg) + so, lane);
      uint32_t a[16][4];
      auto load_a = [&](uint32_t base, int t, uint32_t on) {
        const uint32_t pt = base + toff + (t >> 1) * 1280 + (t & 1) * 64;
        a[t][0] = lds32_if(pt + 32, on); a[t][1] = lds32_if(pt + 672, on); a[t][2] = lds32_if(pt, on); a[t][3] = lds32_if(pt + 640, on);
      };
      auto gemm1_done = [&]() {
        pipe_drain(p, bars, leader);
        if (leader) mbar_arrive(bars + B_G1DONE);
        mbar_wait_u(bars + B_EMPTY + (2 - wg) * 8, wg ^ 1);
      };
      {
        float acc[72];
        if (kind) {
          float big[96];
          gemm_run<1, LEAD_B>(big, 32, 0, p, sb, PITCH_B, wg, leader);
          if (wg == 1) named_arrive(6, 256);
          if (wg < nconv) mbar_wait_u(bars + B_CFULL + wg * 8, 0);
#pragma unroll
          for (int t = 0; t < 8; t++) load_a(conv_buf(sb, 1, wg), t, wg < nconv);
          gemm1_done();
          gelu_store<72, 96>(big, bias0, bias1, sa, 0u, [](int) { return 0u; });
#pragma unroll
          for (int i = 0; i < 72; i++) asm volatile("mov.b32 %0, %1;" : "=f"(acc[i]) : "f"(big[i]));
        } else {
          gemm_run<1, 0>(acc, 32 - LEAD_S, 0, p, sb, PITCH_S, wg, leader);
          if (wg == 1) { pipe_drain(p, bars, leader); named_bar(8, 256); }
#pragma unroll
          for (int k = 32 - LEAD_S; k < 32; k++) {
            mbar_wait_u(bars + B_FULL + (k % ST) * 8, (k / ST) & 1);
            wg_fence();
#pragma unroll
            for (int i = 0; i < 4; i++)
              wgmma_ss<1>(acc, desc_lo(sb + wg * 8192, 8192) + (k % ST) * (PITCH_S >> 4) + i * 128, desc_lo(sb + ASZ, 128) + (k % ST) * (PITCH_S >> 4) + i * 16, 1);
            wg_commit();
            if (k == 32 - PREN) mbar_wait_u(bars + B_CFULL + wg * 8, 0);
            if (k >= 32 - PREN) {
#pragma unroll
              for (int t = (k - 32 + PREN) * 8 / PREN; t < (k - 31 + PREN) * 8 / PREN; t++) load_a(conv_buf(sb, 0, wg), t, 1);
            }
            wg_wait<1>();
            if (leader && (k > 32 - LEAD_S || wg == 0)) mbar_arrive(bars + B_EMPTY + ((k - 1) % ST) * 8);
          }
          p.prev = 31 % ST;
          named_arrive(8 - 2 * wg, 256);
          gemm1_done();
        }
        gelu_store<0, 72>(acc, bias0, bias1, sa, roles.by_sm >> 1, [&](int t) { return t + GLAG < 9 ? lds32(bars) : 0u; });
        fence_async_smem();
        __syncwarp();
        if (lane == 0) mbar_arrive(bars + B_USTG + wg * 8);
      }
      {
#pragma unroll 1
        for (int i = wg; i < nconv; i += 2) {
          const uint32_t base = conv_buf(sb, kind, i & 3), next = conv_buf(sb, kind, (i + 2) & 3);
          const uint64_t dH = mkdesc(base + CH_OFF, 16, 128, 0);
          float y[8][16];
          if (toff < CT_OFF + 32) a[0][2] = 0u;
          named_bar(6 + wg, 256);
          wg_fence();
#pragma unroll
          for (int t = 0; t < 16; t++) {
            if (t == 8) wg_fence();
            if (t == CTURN) named_arrive(7 - wg, 256);
#pragma unroll
            for (int cb = t >> 1; cb < 8; cb++) {
              wgmma_rs_n32(y[cb], a[t][0], a[t][1], a[t][2], a[t][3], dH + (32 * cb - 32 * (t >> 1) - 2 * (t & 1) - 1), t);
              const int n = 8 * t - (t >> 1) * ((t - 1) >> 1) - (t >> 1) + cb + 1;
              if (n % CPER == 0 && n / CPER <= 8) load_a(base, 7 + n / CPER, 1);
            }
          }
          wg_commit();
          const bool more = i + 2 < nconv;
          if (more) mbar_wait_u(bars + B_CFULL + ((i + 2) & 3) * 8, (i + 2) >> 2);
          mbar_wait_u(bars + B_SEMPTY + wg * 8, ((i >> 1) & 1) ^ 1);
          wg_wait<0>();
          if (lane == 0) mbar_arrive(bars + B_CEMPTY + (i & 3) * 8);
          uint32_t P[16], Q[16], R[16], o[8];
#pragma unroll
          for (int j = 0; j < 32; j++) {
            if ((j & 3) == 0) load_a(next, j >> 2, more);
            float v0 = y[j >> 2][4 * (j & 3)], v1 = y[j >> 2][4 * (j & 3) + 1];
            if (j >= 2) { v0 += y[(j - 2) >> 2][4 * ((j - 2) & 3) + 2]; v1 += y[(j - 2) >> 2][4 * ((j - 2) & 3) + 3]; }
            if (j & 1) R[j >> 1] = shfl_ordered(pack_bf16(v0, v1), lane ^ 16);
            else P[j >> 1] = pack_bf16(v0, v1);
          }
#pragma unroll
          for (int m = 0; m < 16; m++) Q[m] = hadd2(P[m], cA ? R[m] : (m ? R[m - 1] : 0u));
#pragma unroll
          for (int m = 0; m < 8; m++) o[m] = shfl_ordered(pB1 ? Q[2 * m] : (pB2 ? (m ? Q[2 * m - 1] : 0u) : Q[2 * m + 1]), srcB);
#pragma unroll
          for (int m = 0; m < 8; m++) sts32(sto + m * 512, hadd2(pB1 ? Q[2 * m + 1] : Q[2 * m], o[m]));
          fence_async_smem();
          __syncwarp();
          if (lane == 0) mbar_arrive(bars + B_SFULL + wg * 8);
        }
        if (wg == (nconv & 1)) named_bar(6 + wg, 256);
      }
    }
    if (kind != 2) {
      const Role ro = get_role(roles);
      const uint32_t pitch = ro.pitch;
      const int s0 = ro.g2_m + wg * 64 + wi * 16 + g;
      const size_t go = (size_t)s0 * D_ + ro.dt * 128 + ro.half * 64 + qd * 8, go8 = (size_t)s0 * D_ + 512 + ro.dt * 16 + ro.half * 8 + qd * 2;
      uint32_t x[2][9], sg[2][9];
      float acc[72];
      p.r = Ring{(uint32_t)(2 + ro.skip), 0};
      mbar_wait_u(bars + B_G2GO + wg * 8, 0);
      gemm_run<0, 0>(acc, XAT + 2 * wg + 1 - ro.skip, 0, p, sb, pitch, wg, leader);
#pragma unroll
      for (int J = 0; J < 4; J++) {
        const uint4 v = ldg128(q + go + (J & 1) * 8 * D_ + (J >> 1) * 32);
        x[J & 1][4 * (J >> 1)] = v.x; x[J & 1][4 * (J >> 1) + 1] = v.y; x[J & 1][4 * (J >> 1) + 2] = v.z; x[J & 1][4 * (J >> 1) + 3] = v.w;
      }
      x[0][8] = ldg32(q + go8); x[1][8] = ldg32(q + go8 + 8 * D_);
      const uint4 st0 = ld_l2(gs->stats + s0), st1 = ld_l2(gs->stats + s0 + 8);
      const uint32_t braw0 = ldg16(b2 + s0), braw1 = ldg16(b2 + s0 + 8);
      gemm_run<0, 0>(acc, ZAT - XAT, 1, p, sb, pitch, wg, leader);
      {
        const int zw = 8 * wi + (g ^ ((((ro.g2_m >> 6) + wg) & 3) << 1));
        const uint32_t za = sb + ST * pitch + wg * 9216 + qd * 256 + (zw & 3) * 4;
        mbar_wait_u(bars + B_ZFULL, 0);
#pragma unroll
        for (int j = 0; j < 9; j++) {
          sg[0][j] = lds32(za + j * 1024 + (((zw >> 2) ^ (2 * qd)) << 4));
          sg[1][j] = lds32(za + j * 1024 + 128 + (((zw >> 2) ^ (2 * qd + 1)) << 4));
        }
      }
      gemm_run<0, 0>(acc, 1, 1, p, sb, pitch, wg, leader);
#pragma unroll
      for (int j = 0; j < 9; j++) {
        const uint32_t z0 = __byte_perm(sg[0][j], sg[1][j], 0x5410), z1 = __byte_perm(sg[0][j], sg[1][j], 0x7632);
        sg[0][j] = hmul2(ln_apply(x[0][j], st0), z0);
        sg[1][j] = hmul2(ln_apply(x[1][j], st1), z1);
        asm volatile("" : "+r"(sg[0][j]), "+r"(sg[1][j]));
      }
      gemm_run<0, SKEW>(acc, 35 - ZAT - LAG - 2 * wg, 1, p, sb, pitch, wg, leader);
      const uint32_t rbuf = sb + (69 % ST) * pitch + warp * 2304;
      const uint32_t rdst = mapa(rbuf, ro.half ^ 1), rbar = mapa(bars + B_RFULL + wg * 8, ro.half ^ 1);
      pipe_drain(p, bars, leader);
      float cs[36], ck[36];
      split_acc(acc, cs, ck);
      gemm2_part<0, 0, 4 * LAG>(cs, sb, pitch, wg);
      if (KPRE) gemm2_part<72, 0, KPRE>(ck, sb, pitch, wg);
      const float hb0 = fmaf(bf_lo(braw0), 0.5f, __uint_as_float(st0.w)), hb1 = fmaf(bf_lo(braw1), 0.5f, __uint_as_float(st1.w));
      mbar_wait(bars + B_GO, 0);
      wg_wait<KPRE ? 1 : 0>();
#pragma unroll
      for (int i = 0; i < 5; i++) {
        const float* c = &cs[8 * i];
        const uint32_t v0 = pack_bf16(fmaf(c[0], 0.25f, hb0), fmaf(c[1], 0.25f, hb0)), v1 = pack_bf16(fmaf(c[2], 0.25f, hb1), fmaf(c[3], 0.25f, hb1));
        if (i < 4) st_async4(rdst + i * 512 + lane * 16, v0, v1, pack_bf16(fmaf(c[4], 0.25f, hb0), fmaf(c[5], 0.25f, hb0)), pack_bf16(fmaf(c[6], 0.25f, hb1), fmaf(c[7], 0.25f, hb1)), rbar);
        else st_async2(rdst + 2048 + lane * 8, v0, v1, rbar);
      }
      if (wg == 1) named_bar(7, 256);
      gemm2_part<72, KPRE, 4 * LAG>(ck, sb, pitch, wg);
      uint32_t rp[18];
      mbar_wait(bars + B_RFULL + wg * 8, 0);
#pragma unroll
      for (int m = 0; m < 4; m++) {
        const uint4 v = lds128(rbuf + m * 512 + lane * 16);
        rp[4 * m] = v.x; rp[4 * m + 1] = v.y; rp[4 * m + 2] = v.z; rp[4 * m + 3] = v.w;
      }
      { const uint2 v = lds64(rbuf + 2048 + lane * 8); rp[16] = v.x; rp[17] = v.y; }
      __nv_bfloat16* o = out + go;
      wg_wait<0>();
      float h[2][4], t[2][4], half = 0.25f;
#pragma unroll
      for (int j = 0; j <= 9; j++) {
        if (j < 9) {
          const uint32_t ra = rp[2 * j], rb = rp[2 * j + 1];
          if (j >= 2) half = fmaf(t[j & 1][3], 0.f, 0.25f);
          h[j & 1][0] = fmaf(ck[4 * j], half, bf_lo(ra)); h[j & 1][1] = fmaf(ck[4 * j + 1], half, bf_hi(ra));
          h[j & 1][2] = fmaf(ck[4 * j + 2], half, bf_lo(rb)); h[j & 1][3] = fmaf(ck[4 * j + 3], half, bf_hi(rb));
#pragma unroll
          for (int u = 0; u < 4; u++) t[j & 1][u] = tanh_ordered(h[j & 1][u]);
        }
        if (j > 0) {
          const int k = j - 1;
          const float* hh = h[k & 1];
          const float* tt = t[k & 1];
          x[0][k] = hfma2(sg[0][k], pack_bf16(fmaf(hh[0], tt[0], hh[0]), fmaf(hh[1], tt[1], hh[1])), x[0][k]);
          x[1][k] = hfma2(sg[1][k], pack_bf16(fmaf(hh[2], tt[2], hh[2]), fmaf(hh[3], tt[3], hh[3])), x[1][k]);
          if ((k & 3) == 3) {
            *(uint4*)(o + (k >> 2) * 32) = make_uint4(x[0][k - 3], x[0][k - 2], x[0][k - 1], x[0][k]);
            *(uint4*)(o + 8 * D_ + (k >> 2) * 32) = make_uint4(x[1][k - 3], x[1][k - 2], x[1][k - 1], x[1][k]);
          }
        }
      }
      *(uint32_t*)(out + go8) = x[0][8];
      *(uint32_t*)(out + go8 + 8 * D_) = x[1][8];
    }
  }
}

typedef CUresult (*EncodeFn)(CUtensorMap*, CUtensorMapDataType, cuuint32_t, void*, const cuuint64_t*, const cuuint64_t*, const cuuint32_t*,
                             const cuuint32_t*, CUtensorMapInterleave, CUtensorMapSwizzle, CUtensorMapL2promotion, CUtensorMapFloatOOBfill);

uint32_t role_of_pair(int t) {
  int grp, i;
  if (t < 32) { const int j = t & 7; i = t >> 3; grp = j < 6 ? 1 + j : 12 + 2 * (j - 6); }
  else if (t < 60) { const int j = (t - 32) % 7; i = (t - 32) / 7; grp = j < 5 ? 7 + j : 13 + 2 * (j - 5); }
  else if (t < 62) return 2u | (uint32_t)(t - 60) << 2 | (uint32_t)(14 + 3 * (t - 60)) << 8 | 2u << 16;
  else { grp = 0; i = t - 62; }
  if (grp < 12) return (uint32_t)(i << 2 | grp << 4 | grp << 8 | i << 16);
  const int u = (grp & 1) * 4 + i;
  return (uint32_t)(1 | i << 2 | grp << 4 | (12 + 3 * ((grp - 12) >> 1) + u / 3) << 8 | (u % 3) << 16);
}

}

extern "C" void kernel_launch(void* const* d_in, const int* in_sizes, int n_in, void* d_out, int out_size) {
  (void)in_sizes; (void)n_in; (void)out_size;
  EncodeFn enc = nullptr;
  cudaDriverEntryPointQueryResult qr;
  cudaGetDriverEntryPoint("cuTensorMapEncodeTiled", (void**)&enc, cudaEnableDefault, &qr);
  Scratch* gs = nullptr;
  cudaGetSymbolAddress((void**)&gs, g_scratch);
  void *zp = gs->z, *hp = gs->h, *kvp = gs->kv;
  Maps tm;
  for (int w = 0; w < 2; w++) {
    cuuint64_t gd[2] = {D_, S_};
    cuuint64_t st[1] = {D_ * 2};
    cuuint32_t bx[2] = {64, w ? 33u : 36u};
    cuuint32_t es[2] = {1, 1};
    enc(w ? &tm.m[M_V] : &tm.m[M_K], CU_TENSOR_MAP_DATA_TYPE_BFLOAT16, 2, d_in[1 + w], gd, st, bx, es, CU_TENSOR_MAP_INTERLEAVE_NONE, CU_TENSOR_MAP_SWIZZLE_NONE,
        CU_TENSOR_MAP_L2_PROMOTION_L2_128B, CU_TENSOR_MAP_FLOAT_OOB_FILL_NONE);
  }
  {
    cuuint64_t gd[4] = {16, D_ / 2, 2, 128};
    cuuint64_t st[3] = {2 * KVT, KVT, 64};
    cuuint32_t bx[4] = {20, 32, 2, 1};
    cuuint32_t es[4] = {1, 1, 1, 1};
    enc(&tm.m[M_KV], CU_TENSOR_MAP_DATA_TYPE_UINT32, 4, kvp, gd, st, bx, es, CU_TENSOR_MAP_INTERLEAVE_NONE, CU_TENSOR_MAP_SWIZZLE_NONE,
        CU_TENSOR_MAP_L2_PROMOTION_NONE, CU_TENSOR_MAP_FLOAT_OOB_FILL_NONE);
  }
  {
    cuuint64_t gd[3] = {40, 64, D_};
    cuuint64_t st[2] = {128, KVT};
    cuuint32_t bx[3] = {40, 16, 1};
    cuuint32_t es[3] = {1, 1, 1};
    enc(&tm.m[M_KL], CU_TENSOR_MAP_DATA_TYPE_UINT32, 3, (uint8_t*)kvp - 32, gd, st, bx, es, CU_TENSOR_MAP_INTERLEAVE_NONE, CU_TENSOR_MAP_SWIZZLE_NONE,
        CU_TENSOR_MAP_L2_PROMOTION_NONE, CU_TENSOR_MAP_FLOAT_OOB_FILL_NONE);
  }
  {
    cuuint64_t gd[3] = {64, 32 * 72, 8};
    cuuint64_t st[2] = {1024, 128};
    cuuint32_t bx[3] = {64, 72, 1};
    cuuint32_t es[3] = {1, 1, 1};
    enc(&tm.m[M_H], CU_TENSOR_MAP_DATA_TYPE_BFLOAT16, 3, hp, gd, st, bx, es, CU_TENSOR_MAP_INTERLEAVE_NONE, CU_TENSOR_MAP_SWIZZLE_128B,
        CU_TENSOR_MAP_L2_PROMOTION_NONE, CU_TENSOR_MAP_FLOAT_OOB_FILL_NONE);
  }
  for (int w = 0; w < 2; w++) {
    const cuuint64_t M = w ? S_ : F_, K = w ? F_ : S_;
    cuuint64_t gd[3] = {64, K, M / 64};
    cuuint64_t st[2] = {M * 2, 128};
    cuuint32_t bx[3] = {64, 64, 2};
    cuuint32_t es[3] = {1, 1, 1};
    enc(w ? &tm.m[M_W2] : &tm.m[M_W1], CU_TENSOR_MAP_DATA_TYPE_BFLOAT16, 3, d_in[w ? 9 : 7], gd, st, bx, es, CU_TENSOR_MAP_INTERLEAVE_NONE,
        CU_TENSOR_MAP_SWIZZLE_128B, CU_TENSOR_MAP_L2_PROMOTION_L2_256B, CU_TENSOR_MAP_FLOAT_OOB_FILL_NONE);
  }
  {
    cuuint64_t gd[2] = {S_, D_};
    cuuint64_t st[1] = {S_ * 2};
    cuuint32_t bx[2] = {64, 72};
    cuuint32_t es[2] = {1, 1};
    enc(&tm.m[M_Z], CU_TENSOR_MAP_DATA_TYPE_BFLOAT16, 2, zp, gd, st, bx, es, CU_TENSOR_MAP_INTERLEAVE_NONE, CU_TENSOR_MAP_SWIZZLE_128B,
        CU_TENSOR_MAP_L2_PROMOTION_L2_256B, CU_TENSOR_MAP_FLOAT_OOB_FILL_NONE);
  }
  RoleMap roles;
  int dev = 0, sms = 0;
  cudaGetDevice(&dev);
  cudaDeviceGetAttribute(&sms, cudaDevAttrMultiProcessorCount, dev);
  roles.by_sm = sms == NCTA;
  for (int k = 0; k < NCTA / 2; k++) roles.role[k] = role_of_pair(k);
  cudaFuncSetAttribute(fused_kernel, cudaFuncAttributeMaxDynamicSharedMemorySize, SMEM_BYTES);
  fused_kernel<<<NCTA, 384, SMEM_BYTES>>>((const __nv_bfloat16*)d_in[0], gs, (const __nv_bfloat16*)d_in[8], (const __nv_bfloat16*)d_in[3],
                                          (const __nv_bfloat16*)d_in[4], (const __nv_bfloat16*)d_in[5], tm,
                                          roles, (const __nv_bfloat16*)d_in[10], (__nv_bfloat16*)d_out);
}
```

```cpp
#include <cuda_runtime.h>
#include <cuda_bf16.h>
#include <cuda.h>
#include <stdint.h>

namespace {

constexpr int S_ = 2048, D_ = 576, F_ = 4608;
constexpr int NCTA = 132, NG2 = 128;
constexpr int ST = 5, ASZ = 16384, PITCH_S = ASZ + 144 * 128, PITCH_B = ASZ + 192 * 128;
constexpr int CBUF = 14464, CH_OFF = 128, CT_OFF = 4224, KVT = 8192;
constexpr int KVIN = (36 + 33) * 128, KVW = 2 * CBUF;
constexpr int BAR_OFF = ST * PITCH_S + 2 * KVW;
constexpr int SMEM_BYTES = BAR_OFF + 512;
constexpr int LEAD_S = 4, LEAD_B = 4;
constexpr int PREN = 3;
constexpr int GLAG = 4;
constexpr int CTURN = 14, CPER = 4;
constexpr int XAT = 12, ZAT = 22;
constexpr int SKEW = 1;
constexpr int LAG = 4;
constexpr int KPRE = 2, TURN = 4;
constexpr int LNROT = 120;
constexpr int QLATE = 40, QDELAY = 400, QRAMP = 5;
constexpr int W9 = 1200;
constexpr int A0 = 1200, AD = 300, AN = 2, AL = 1500;
constexpr int H0 = 3100, HD = 400, HW = 4200;
constexpr int HS2 = 5, LK1 = 7, LK2 = 14, KVGO = 6, KVGO1 = 12, CVGO = 31;
constexpr int BLK_NS = 336, GDELAY = 1280, GBIG = 640, GDELAY1 = 128, ZGAP = 300;
constexpr uint32_t SPIN_LIMIT = 1u << 22;

constexpr int FL_H = 0, FL_U = 3, FL_KV = 8, FL_Z = 11, FL_GATE = 13, FL_DONE = 14, FL_N = 15;
struct Scratch {
  uint32_t flags[64 * 32];
  uint4 stats[S_];
  uint8_t h[32 * 72 * 1024];
  uint8_t u[72 * D_ * 128];
  uint8_t kv[D_ * KVT];
  __nv_bfloat16 z[D_ * S_];
};
__device__ __align__(1024) Scratch g_scratch;
extern __shared__ __align__(1024) uint8_t smem_raw[];
enum { M_W1, M_H, M_K, M_V, M_KV, M_KL, M_W2, M_Z, M_N };
struct Maps { CUtensorMap m[M_N]; };
struct RoleMap { uint32_t role[NCTA / 2]; uint32_t by_sm; };

template<int TB> __device__ __forceinline__ void wgmma_ss(float (&d)[96], uint32_t da, uint32_t db, int sd) {
  asm volatile("{\n.reg .pred p;\n.reg .b64 a, b;\nsetp.ne.b32 p, %98, 0;\nmov.b64 a, {%96, %100};\nmov.b64 b, {%97, %101};\n"
    "wgmma.mma_async.sync.aligned.m64n192k16.f32.bf16.bf16 {%0, %1, %2, %3, %4, %5, %6, %7, %8, %9, %10, %11, %12, %13, %14, %15, %16, %17, %18, %19, %20, %21, %22, %23, %24, %25, %26, %27, %28, %29, %30, %31, %32, %33, %34, %35, %36, %37, %38, %39, %40, %41, %42, %43, %44, %45, %46, %47, %48, %49, %50, %51, %52, %53, %54, %55, %56, %57, %58, %59, %60, %61, %62, %63, %64, %65, %66, %67, %68, %69, %70, %71, %72, %73, %74, %75, %76, %77, %78, %79, %80, %81, %82, %83, %84, %85, %86, %87, %88, %89, %90, %91, %92, %93, %94, %95}, a, b, p, 1, 1, 1, %99;\n}\n"
    : "+f"(d[0]), "+f"(d[1]), "+f"(d[2]), "+f"(d[3]), "+f"(d[4]), "+f"(d[5]), "+f"(d[6]), "+f"(d[7]), "+f"(d[8]), "+f"(d[9]), "+f"(d[10]), "+f"(d[11]), "+f"(d[12]), "+f"(d[13]), "+f"(d[14]), "+f"(d[15]), "+f"(d[16]), "+f"(d[17]), "+f"(d[18]), "+f"(d[19]), "+f"(d[20]), "+f"(d[21]), "+f"(d[22]), "+f"(d[23]), "+f"(d[24]), "+f"(d[25]), "+f"(d[26]), "+f"(d[27]), "+f"(d[28]), "+f"(d[29]), "+f"(d[30]), "+f"(d[31]), "+f"(d[32]), "+f"(d[33]), "+f"(d[34]), "+f"(d[35]), "+f"(d[36]), "+f"(d[37]), "+f"(d[38]), "+f"(d[39]), "+f"(d[40]), "+f"(d[41]), "+f"(d[42]), "+f"(d[43]), "+f"(d[44]), "+f"(d[45]), "+f"(d[46]), "+f"(d[47]), "+f"(d[48]), "+f"(d[49]), "+f"(d[50]), "+f"(d[51]), "+f"(d[52]), "+f"(d[53]), "+f"(d[54]), "+f"(d[55]), "+f"(d[56]), "+f"(d[57]), "+f"(d[58]), "+f"(d[59]), "+f"(d[60]), "+f"(d[61]), "+f"(d[62]), "+f"(d[63]), "+f"(d[64]), "+f"(d[65]), "+f"(d[66]), "+f"(d[67]), "+f"(d[68]), "+f"(d[69]), "+f"(d[70]), "+f"(d[71]), "+f"(d[72]), "+f"(d[73]), "+f"(d[74]), "+f"(d[75]), "+f"(d[76]), "+f"(d[77]), "+f"(d[78]), "+f"(d[79]), "+f"(d[80]), "+f"(d[81]), "+f"(d[82]), "+f"(d[83]), "+f"(d[84]), "+f"(d[85]), "+f"(d[86]), "+f"(d[87]), "+f"(d[88]), "+f"(d[89]), "+f"(d[90]), "+f"(d[91]), "+f"(d[92]), "+f"(d[93]), "+f"(d[94]), "+f"(d[95])
    : "r"(da), "r"(db), "r"(sd), "n"(TB), "r"(0x40000040u), "r"(TB ? 0x40u : 0x40000040u));
}
template<int TB> __device__ __forceinline__ void wgmma_ss(float (&d)[72], uint32_t da, uint32_t db, int sd) {
  asm volatile("{\n.reg .pred p;\n.reg .b64 a, b;\nsetp.ne.b32 p, %74, 0;\nmov.b64 a, {%72, %76};\nmov.b64 b, {%73, %77};\n"
    "wgmma.mma_async.sync.aligned.m64n144k16.f32.bf16.bf16 {%0, %1, %2, %3, %4, %5, %6, %7, %8, %9, %10, %11, %12, %13, %14, %15, %16, %17, %18, %19, %20, %21, %22, %23, %24, %25, %26, %27, %28, %29, %30, %31, %32, %33, %34, %35, %36, %37, %38, %39, %40, %41, %42, %43, %44, %45, %46, %47, %48, %49, %50, %51, %52, %53, %54, %55, %56, %57, %58, %59, %60, %61, %62, %63, %64, %65, %66, %67, %68, %69, %70, %71}, a, b, p, 1, 1, 1, %75;\n}\n"
    : "+f"(d[0]), "+f"(d[1]), "+f"(d[2]), "+f"(d[3]), "+f"(d[4]), "+f"(d[5]), "+f"(d[6]), "+f"(d[7]), "+f"(d[8]), "+f"(d[9]), "+f"(d[10]), "+f"(d[11]), "+f"(d[12]), "+f"(d[13]), "+f"(d[14]), "+f"(d[15]), "+f"(d[16]), "+f"(d[17]), "+f"(d[18]), "+f"(d[19]), "+f"(d[20]), "+f"(d[21]), "+f"(d[22]), "+f"(d[23]), "+f"(d[24]), "+f"(d[25]), "+f"(d[26]), "+f"(d[27]), "+f"(d[28]), "+f"(d[29]), "+f"(d[30]), "+f"(d[31]), "+f"(d[32]), "+f"(d[33]), "+f"(d[34]), "+f"(d[35]), "+f"(d[36]), "+f"(d[37]), "+f"(d[38]), "+f"(d[39]), "+f"(d[40]), "+f"(d[41]), "+f"(d[42]), "+f"(d[43]), "+f"(d[44]), "+f"(d[45]), "+f"(d[46]), "+f"(d[47]), "+f"(d[48]), "+f"(d[49]), "+f"(d[50]), "+f"(d[51]), "+f"(d[52]), "+f"(d[53]), "+f"(d[54]), "+f"(d[55]), "+f"(d[56]), "+f"(d[57]), "+f"(d[58]), "+f"(d[59]), "+f"(d[60]), "+f"(d[61]), "+f"(d[62]), "+f"(d[63]), "+f"(d[64]), "+f"(d[65]), "+f"(d[66]), "+f"(d[67]), "+f"(d[68]), "+f"(d[69]), "+f"(d[70]), "+f"(d[71])
    : "r"(da), "r"(db), "r"(sd), "n"(TB), "r"(0x40000040u), "r"(TB ? 0x40u : 0x40000040u));
}
template<int TB> __device__ __forceinline__ void wgmma_ss(float (&d)[36], uint32_t da, uint32_t db, int sd) {
  asm volatile("{\n.reg .pred p;\n.reg .b64 a, b;\nsetp.ne.b32 p, %38, 0;\nmov.b64 a, {%36, %40};\nmov.b64 b, {%37, %41};\n"
    "wgmma.mma_async.sync.aligned.m64n72k16.f32.bf16.bf16 {%0, %1, %2, %3, %4, %5, %6, %7, %8, %9, %10, %11, %12, %13, %14, %15, %16, %17, %18, %19, %20, %21, %22, %23, %24, %25, %26, %27, %28, %29, %30, %31, %32, %33, %34, %35}, a, b, p, 1, 1, 1, %39;\n}\n"
    : "+f"(d[0]), "+f"(d[1]), "+f"(d[2]), "+f"(d[3]), "+f"(d[4]), "+f"(d[5]), "+f"(d[6]), "+f"(d[7]), "+f"(d[8]), "+f"(d[9]), "+f"(d[10]), "+f"(d[11]), "+f"(d[12]), "+f"(d[13]), "+f"(d[14]), "+f"(d[15]), "+f"(d[16]), "+f"(d[17]), "+f"(d[18]), "+f"(d[19]), "+f"(d[20]), "+f"(d[21]), "+f"(d[22]), "+f"(d[23]), "+f"(d[24]), "+f"(d[25]), "+f"(d[26]), "+f"(d[27]), "+f"(d[28]), "+f"(d[29]), "+f"(d[30]), "+f"(d[31]), "+f"(d[32]), "+f"(d[33]), "+f"(d[34]), "+f"(d[35])
    : "r"(da), "r"(db), "r"(sd), "n"(TB), "r"(0x40000040u), "r"(TB ? 0x40u : 0x40000040u));
}
__device__ __forceinline__ void wgmma_rs_n32(float (&d)[16], uint32_t a0, uint32_t a1, uint32_t a2, uint32_t a3, uint64_t db, int sd) {
  asm volatile("{\n.reg .pred p;\nsetp.ne.b32 p, %21, 0;\n"
    "wgmma.mma_async.sync.aligned.m64n32k16.f32.bf16.bf16 {%0, %1, %2, %3, %4, %5, %6, %7, %8, %9, %10, %11, %12, %13, %14, %15}, {%16, %17, %18, %19}, %20, p, 1, 1, 0;\n}\n"
    : "+f"(d[0]), "+f"(d[1]), "+f"(d[2]), "+f"(d[3]), "+f"(d[4]), "+f"(d[5]), "+f"(d[6]), "+f"(d[7]), "+f"(d[8]), "+f"(d[9]), "+f"(d[10]), "+f"(d[11]), "+f"(d[12]), "+f"(d[13]), "+f"(d[14]), "+f"(d[15])
    : "r"(a0), "r"(a1), "r"(a2), "r"(a3), "l"(db), "r"(sd));
}

__device__ __forceinline__ void wg_fence() { asm volatile("wgmma.fence.sync.aligned;" ::: "memory"); }
__device__ __forceinline__ void wg_commit() { asm volatile("wgmma.commit_group.sync.aligned;" ::: "memory"); }
template <int n> __device__ __forceinline__ void wg_wait() { asm volatile("wgmma.wait_group.sync.aligned %0;" ::"n"(n) : "memory"); }
__device__ __forceinline__ uint64_t mkdesc(uint32_t addr, uint32_t lbo, uint32_t sbo, uint32_t sw) {
  return (uint64_t)((addr & 0x3FFFF) >> 4) | ((uint64_t)(lbo >> 4) << 16) | ((uint64_t)(sbo >> 4) << 32) | ((uint64_t)sw << 62);
}
__device__ __forceinline__ void mbar_init(uint32_t a, int c) { asm volatile("mbarrier.init.shared::cta.b64 [%0], %1;" ::"r"(a), "r"(c)); }
__device__ __forceinline__ void mbar_expect(uint32_t a, uint32_t b) { asm volatile("mbarrier.arrive.expect_tx.shared::cta.b64 _, [%0], %1;" ::"r"(a), "r"(b) : "memory"); }
__device__ __forceinline__ void mbar_arrive(uint32_t a) { asm volatile("mbarrier.arrive.shared::cta.b64 _, [%0];" ::"r"(a) : "memory"); }
__device__ __forceinline__ void mbar_arrive_cluster(uint32_t raddr) { asm volatile("mbarrier.arrive.shared::cluster.b64 _, [%0];" ::"r"(raddr) : "memory"); }
__device__ __forceinline__ uint32_t mapa(uint32_t a, uint32_t cta) { uint32_t r; asm("mapa.shared::cluster.u32 %0, %1, %2;" : "=r"(r) : "r"(a), "r"(cta)); return r; }
__device__ __forceinline__ void mbar_wait(uint32_t a, uint32_t ph) {
  asm volatile(
      "{\n.reg .pred p;\n.reg .u32 c;\nmov.u32 c, 0;\n"
      "WAIT_LOOP:\nmbarrier.try_wait.parity.shared::cta.b64 p, [%0], %1;\n@p bra WAIT_DONE;\n"
      "add.u32 c, c, 1;\nsetp.lt.u32 p, c, %2;\n@p bra WAIT_LOOP;\ntrap;\nWAIT_DONE:\n}" ::"r"(a), "r"(ph), "n"(SPIN_LIMIT) : "memory");
}
__device__ __forceinline__ void mbar_wait_u(uint32_t a, uint32_t ph) {
  asm volatile("{\n.reg .pred p;\nWAIT_LOOP:\nmbarrier.try_wait.parity.shared::cta.b64 p, [%0], %1;\n@!p bra WAIT_LOOP;\n}" ::"r"(a), "r"(ph) : "memory");
}
__device__ __forceinline__ uint32_t desc_lo(uint32_t addr, uint32_t lbo) { return ((addr & 0x3FFFF) >> 4) | ((lbo >> 4) << 16); }
__device__ __forceinline__ void tma2d(uint32_t dst, const CUtensorMap* m, int c0, int c1, uint32_t bar) {
  asm volatile("cp.async.bulk.tensor.2d.shared::cluster.global.mbarrier::complete_tx::bytes [%0], [%1, {%3, %4}], [%2];" ::"r"(dst), "l"(m), "r"(bar), "r"(c0), "r"(c1) : "memory");
}
__device__ __forceinline__ void bulk_g2s(uint32_t dst, const void* src, uint32_t sz, uint32_t bar) {
  asm volatile("cp.async.bulk.shared::cluster.global.mbarrier::complete_tx::bytes [%0], [%1], %2, [%3];" ::"r"(dst), "l"(src), "r"(sz), "r"(bar) : "memory");
}
__device__ __forceinline__ void bulk_s2g(void* dst, uint32_t src, uint32_t sz) {
  asm volatile("cp.async.bulk.global.shared::cta.bulk_group [%0], [%1], %2;" ::"l"(dst), "r"(src), "r"(sz) : "memory");
}
__device__ __forceinline__ uint64_t stream_policy() {
  uint64_t p;
  asm volatile("createpolicy.fractional.L2::evict_first.b64 %0, 1.0;" : "=l"(p));
  return p;
}
__device__ __forceinline__ void tma_weights(uint32_t dst, const CUtensorMap* m, int k0, int mchunk, uint32_t bar, uint64_t pol) {
  asm volatile("cp.async.bulk.tensor.3d.shared::cluster.global.mbarrier::complete_tx::bytes.L2::cache_hint [%0], [%1, {%6, %3, %4}], [%2], %5;"
               ::"r"(dst), "l"(m), "r"(bar), "r"(k0), "r"(mchunk), "l"(pol), "r"(0) : "memory");
}
__device__ __forceinline__ void tma_weights_prefetch(const CUtensorMap* m, int k0, int mchunk, uint64_t pol) {
  asm volatile("cp.async.bulk.prefetch.tensor.3d.L2.global.L2::cache_hint [%0, {%4, %1, %2}], %3;" ::"l"(m), "r"(k0), "r"(mchunk), "l"(pol), "r"(0) : "memory");
}
__device__ __forceinline__ bool elect_one() {
  uint32_t p;
  asm volatile("{\n.reg .pred P;\nelect.sync _|P, 0xffffffff;\nselp.u32 %0, 1, 0, P;\n}" : "=r"(p));
  return p;
}
__device__ __forceinline__ void bulk_g2s_stream(uint32_t dst, const void* src, uint32_t sz, uint32_t bar, uint64_t pol) {
  asm volatile("cp.async.bulk.shared::cluster.global.mbarrier::complete_tx::bytes.L2::cache_hint [%0], [%1], %2, [%3], %4;"
               ::"r"(dst), "l"(src), "r"(sz), "r"(bar), "l"(pol) : "memory");
}
__device__ __forceinline__ void tma3d_store(const CUtensorMap* m, int c1, int c2, uint32_t src) {
  asm volatile("cp.async.bulk.tensor.3d.global.shared::cta.bulk_group [%0, {%4, %2, %3}], [%1];" ::"l"(m), "r"(src), "r"(c1), "r"(c2), "r"(0) : "memory");
}
__device__ __forceinline__ void tma2d_stream(uint32_t dst, const CUtensorMap* m, int c0, int c1, uint32_t bar, uint64_t pol) {
  asm volatile("cp.async.bulk.tensor.2d.shared::cluster.global.mbarrier::complete_tx::bytes.L2::cache_hint [%0], [%1, {%3, %4}], [%2], %5;"
               ::"r"(dst), "l"(m), "r"(bar), "r"(c0), "r"(c1), "l"(pol) : "memory");
}
__device__ __forceinline__ void tma4d_store(const CUtensorMap* m, int c1, int c2, int c3, uint32_t src) {
  asm volatile("cp.async.bulk.tensor.4d.global.shared::cta.bulk_group [%0, {%5, %2, %3, %4}], [%1];" ::"l"(m), "r"(src), "r"(c1), "r"(c2), "r"(c3), "r"(0) : "memory");
}
__device__ __forceinline__ void bulk_commit() { asm volatile("cp.async.bulk.commit_group;" ::: "memory"); }
__device__ __forceinline__ void bulk_wait_all() { asm volatile("cp.async.bulk.wait_group 0;" ::: "memory"); }
__device__ __forceinline__ void fence_async_smem() { asm volatile("fence.proxy.async.shared::cta;" ::: "memory"); }
__device__ __forceinline__ void fence_async_global() { asm volatile("fence.proxy.async.global;" ::: "memory"); }
__device__ __forceinline__ void named_bar(int id, int n) { asm volatile("bar.sync %0, %1;" ::"r"(id), "r"(n) : "memory"); }
__device__ __forceinline__ void named_arrive(int id, int n) { asm volatile("bar.arrive %0, %1;" ::"r"(id), "r"(n) : "memory"); }
__device__ __forceinline__ void flag_add(uint32_t* f, int i, uint32_t v) { asm volatile("red.relaxed.gpu.global.add.u32 [%0], %1;" ::"l"(f + i * 32), "r"(v) : "memory"); }
__device__ __forceinline__ uint32_t flag_ld(uint32_t* f, int i) { uint32_t v; asm volatile("ld.relaxed.gpu.global.u32 %0, [%1];" : "=r"(v) : "l"(f + i * 32) : "memory"); return v; }
__device__ __forceinline__ void prefetch_map(const CUtensorMap* m) { asm volatile("prefetch.tensormap [%0];" ::"l"(m) : "memory"); }
__device__ __forceinline__ void stsm4_t(uint32_t a, uint32_t r0, uint32_t r1, uint32_t r2, uint32_t r3) {
  asm volatile("stmatrix.sync.aligned.m8n8.x4.trans.shared.b16 [%0], {%1, %2, %3, %4};" ::"r"(a), "r"(r0), "r"(r1), "r"(r2), "r"(r3) : "memory");
}
__device__ __forceinline__ uint32_t lds32(uint32_t a) { uint32_t v; asm volatile("ld.shared.u32 %0, [%1];" : "=r"(v) : "r"(a) : "memory"); return v; }
__device__ __forceinline__ void sts32(uint32_t a, uint32_t v) { asm volatile("st.shared.u32 [%0], %1;" ::"r"(a), "r"(v) : "memory"); }
__device__ __forceinline__ uint4 ld_l2(const uint4* p) { uint4 v; asm volatile("ld.relaxed.gpu.global.v4.u32 {%0, %1, %2, %3}, [%4];" : "=r"(v.x), "=r"(v.y), "=r"(v.z), "=r"(v.w) : "l"(p) : "memory"); return v; }
__device__ __forceinline__ void sts128(uint32_t a, uint32_t x, uint32_t y, uint32_t z, uint32_t w) { asm volatile("st.shared.v4.u32 [%0], {%1, %2, %3, %4};" ::"r"(a), "r"(x), "r"(y), "r"(z), "r"(w) : "memory"); }
__device__ __forceinline__ uint4 lds128(uint32_t a) { uint4 v; asm volatile("ld.shared.v4.u32 {%0, %1, %2, %3}, [%4];" : "=r"(v.x), "=r"(v.y), "=r"(v.z), "=r"(v.w) : "r"(a) : "memory"); return v; }
__device__ __forceinline__ void st_async4(uint32_t raddr, uint32_t a, uint32_t b, uint32_t c, uint32_t d, uint32_t rbar) {
  asm volatile("st.async.weak.shared::cluster.mbarrier::complete_tx::bytes.v4.b32 [%0], {%1, %2, %3, %4}, [%5];" ::"r"(raddr), "r"(a), "r"(b), "r"(c), "r"(d), "r"(rbar) : "memory");
}
__device__ __forceinline__ uint32_t pack_bf16(float lo, float hi) { uint32_t r; asm("cvt.rn.bf16x2.f32 %0, %1, %2;" : "=r"(r) : "f"(hi), "f"(lo)); return r; }
__device__ __forceinline__ float bf_lo(uint32_t v) { return __uint_as_float(v << 16); }
__device__ __forceinline__ float bf_hi(uint32_t v) { return __uint_as_float(v & 0xffff0000u); }
__device__ __forceinline__ float bf_round(float x) { return bf_lo(pack_bf16(x, 0.f)); }
__device__ __forceinline__ uint32_t hmul2(uint32_t a, uint32_t b) { uint32_t r; asm("mul.rn.bf16x2 %0, %1, %2;" : "=r"(r) : "r"(a), "r"(b)); return r; }
__device__ __forceinline__ uint32_t hsub2(uint32_t a, uint32_t b) { uint32_t r; asm("sub.rn.bf16x2 %0, %1, %2;" : "=r"(r) : "r"(a), "r"(b)); return r; }
__device__ __forceinline__ uint32_t hfma2(uint32_t a, uint32_t b, uint32_t c) { uint32_t r; asm("fma.rn.bf16x2 %0, %1, %2, %3;" : "=r"(r) : "r"(a), "r"(b), "r"(c)); return r; }
__device__ __forceinline__ uint4 ldg128(const void* p) { uint4 v; asm volatile("ld.global.nc.v4.u32 {%0, %1, %2, %3}, [%4];" : "=r"(v.x), "=r"(v.y), "=r"(v.z), "=r"(v.w) : "l"(p)); return v; }
__device__ __forceinline__ uint32_t ldg16(const void* p) { uint32_t v; asm volatile("ld.global.nc.u16 %0, [%1];" : "=r"(v) : "l"(p)); return v; }
__device__ __forceinline__ float tanh_ordered(float x) { float y; asm volatile("tanh.approx.f32 %0, %1;" : "=f"(y) : "f"(x)); return y; }
__device__ __forceinline__ uint32_t tanh2_ordered(uint32_t x) { uint32_t y; asm volatile("tanh.approx.bf16x2 %0, %1;" : "=r"(y) : "r"(x)); return y; }
__device__ __forceinline__ void mma16816(float (&d)[4], uint32_t a0, uint32_t a1, uint32_t a2, uint32_t a3, uint32_t b0, uint32_t b1) {
  asm("mma.sync.aligned.m16n8k16.row.col.f32.bf16.bf16.f32 {%0, %1, %2, %3}, {%4, %5, %6, %7}, {%8, %9}, {%0, %1, %2, %3};"
      : "+f"(d[0]), "+f"(d[1]), "+f"(d[2]), "+f"(d[3]) : "r"(a0), "r"(a1), "r"(a2), "r"(a3), "r"(b0), "r"(b1));
}
__device__ __forceinline__ uint32_t hadd2(uint32_t a, uint32_t b) { uint32_t r; asm("add.rn.bf16x2 %0, %1, %2;" : "=r"(r) : "r"(a), "r"(b)); return r; }
__device__ __forceinline__ uint32_t ldg32(const void* p) { uint32_t v; asm volatile("ld.global.nc.L1::no_allocate.u32 %0, [%1];" : "=r"(v) : "l"(p)); return v; }
__device__ __forceinline__ uint2 lds64(uint32_t a) { uint2 v; asm volatile("ld.shared.v2.u32 {%0, %1}, [%2];" : "=r"(v.x), "=r"(v.y) : "r"(a) : "memory"); return v; }
__device__ __forceinline__ uint32_t lds32_if(uint32_t a, uint32_t on) {
  uint32_t v;
  asm volatile("{\n.reg .pred p;\nsetp.ne.u32 p, %2, 0;\n@p ld.shared.u32 %0, [%1];\n}" : "=r"(v) : "r"(a), "r"(on) : "memory");
  return v;
}
__device__ __forceinline__ uint32_t clock_now() { uint32_t t; asm volatile("mov.u32 %0, %%clock;" : "=r"(t)); return t; }
__device__ __forceinline__ uint32_t time_now() { uint32_t t; asm volatile("mov.u32 %0, %%globaltimer_lo;" : "=r"(t)); return t; }
__device__ __forceinline__ void spin_until(uint32_t t0, uint32_t n) { while (clock_now() - t0 < n) {} }
__device__ __forceinline__ uint2 ldg64_if(const void* p, uint32_t on) {
  uint2 v;
  asm volatile("{\n.reg .pred p;\nsetp.ne.u32 p, %3, 0;\n@p ld.global.nc.v2.u32 {%0, %1}, [%2];\n}" : "=r"(v.x), "=r"(v.y) : "l"(p), "r"(on));
  return v;
}
template <class T> __device__ __forceinline__ T pin(T v) { asm volatile("" : "+r"(v)); return v; }
__device__ __forceinline__ void st_async2(uint32_t raddr, uint32_t a, uint32_t b, uint32_t rbar) {
  asm volatile("st.async.weak.shared::cluster.mbarrier::complete_tx::bytes.v2.b32 [%0], {%1, %2}, [%3];" ::"r"(raddr), "r"(a), "r"(b), "r"(rbar) : "memory");
}
__device__ __forceinline__ void bulk_prefetch(const void* src, uint32_t sz, uint64_t pol) {
  asm volatile("cp.async.bulk.prefetch.L2.global.L2::cache_hint [%0], %1, %2;" ::"l"(src), "r"(sz), "l"(pol) : "memory");
}
__device__ __forceinline__ void bulk_wait_read() { asm volatile("cp.async.bulk.wait_group.read 0;" ::: "memory"); }
__device__ __forceinline__ uint32_t shfl_ordered(uint32_t v, int src) { uint32_t r; asm volatile("shfl.sync.idx.b32 %0, %1, %2, 0x1f, 0xffffffff;" : "=r"(r) : "r"(v), "r"(src)); return r; }
__device__ __forceinline__ int chan_pos(int d) {
  return d < 512 ? 72 * (d >> 6) + ((d & 33) | ((d & 6) << 2) | ((d >> 2) & 6)) : 72 * ((d - 512) >> 3) + 64 + (d & 7);
}

struct Ring {
  uint32_t s, ph;
  __device__ __forceinline__ void next() { if (++s == ST) { s = 0; ph ^= 1; } }
};
constexpr int B_FULL = 0, B_GO = 40, B_CFULL = 48, B_SEMPTY = 80, B_PEER = 96, B_RFULL = 104, B_UDONE = 120, B_KFULL = 136, B_RAW = 168, B_CVGO = 248, B_G2GO = 264, B_KVGO = 280, B_ZFULL = 296,
              B_EMPTY = 312, B_G1DONE = 352,
              B_CEMPTY = 360, B_SFULL = 392, B_USTG = 408, B_END = 424;

static_assert((B_EMPTY - B_GO) % 16 == 0 && (B_CEMPTY - B_EMPTY) % 16 == 0 && (B_END - B_CEMPTY) % 16 == 0, "barrier groups");

__device__ __forceinline__ void wait_counter(uint32_t* f, int idx, uint32_t want, uint32_t first, uint32_t nap) {
#pragma unroll 1
  for (uint32_t spins = 0; first != want; spins++) {
    if (nap && spins) __nanosleep(nap);
    first = flag_ld(f, idx);
    if (spins > SPIN_LIMIT) asm volatile("trap;");
  }
  fence_async_global();
}

__device__ __forceinline__ void gate_arrive(uint32_t* f, uint32_t back) {
  asm volatile("red.relaxed.gpu.global.max.u32 [%0], %1;" ::"l"(f + FL_GATE * 32 + 1), "r"(time_now() - back) : "memory");
  flag_add(f, FL_GATE, 1);
}

__device__ __forceinline__ float ln_rinv(float var) {
  float rt, rinv;
  asm("sqrt.approx.ftz.f32 %0, %1;" : "=f"(rt) : "f"(bf_round(bf_round(var) + 1e-5f)));
  asm("rcp.approx.ftz.f32 %0, %1;" : "=f"(rinv) : "f"(bf_round(rt)));
  return rinv;
}
__device__ __forceinline__ uint32_t ln_apply(uint32_t x, const uint4& st) {
  const uint32_t d = hsub2(x, st.x);
  return hfma2(d, st.y, hmul2(d, st.z));
}

__device__ __forceinline__ void polling_done(uint32_t* f, int lane) {
  unsigned old = 0;
  if (elect_one()) asm volatile("atom.relaxed.gpu.global.inc.u32 %0, [%1], 0xffff;" : "=r"(old) : "l"(f + FL_DONE * 32) : "memory");
  if (__any_sync(0xffffffffu, old == 2 * NCTA - 1)) {
    if (lane < FL_N) *(uint2*)(f + lane * 32) = make_uint2(0u, 0u);
  }
}

struct Pipe { Ring r; uint32_t prev; bool pending; };
__device__ __forceinline__ void pipe_drain(Pipe& p, uint32_t bars, bool leader) {
  wg_wait<0>();
  if (leader) mbar_arrive(bars + B_EMPTY + p.prev * 8);
  p.pending = false;
}
template <int TB, int LEAD, int R>
__device__ __forceinline__ void gemm_run(float (&acc)[R], int n, int accumulate, Pipe& p, uint32_t sb, uint32_t pitch, int wg, bool leader) {
  const uint32_t bars = sb + BAR_OFF;
  const uint32_t dA0 = desc_lo(sb + wg * 8192, 8192), dB0 = desc_lo(sb + ASZ, TB ? 128 : 16);
  constexpr int KB_STEP = TB ? 16 : 2;
#pragma unroll 1
  for (int kb = 0; kb < n; kb++) {
    if (LEAD && kb == n - LEAD && wg == 1) { if (TB) pipe_drain(p, bars, leader); named_bar(8, 256); }
    mbar_wait(bars + B_FULL + p.r.s * 8, p.r.ph);
    const uint32_t dA = dA0 + p.r.s * (pitch >> 4), dB = dB0 + p.r.s * (pitch >> 4);
    wg_fence();
    wgmma_ss<TB>(acc, dA, dB, accumulate | kb);
#pragma unroll
    for (int k = 1; k < 4; k++) wgmma_ss<TB>(acc, dA + k * 128, dB + k * KB_STEP, 1);
    wg_commit();
    wg_wait<1>();
    if (p.pending && leader) mbar_arrive(bars + B_EMPTY + p.prev * 8);
    p.pending = true;
    p.prev = p.r.s;
    p.r.next();
  }
  if (LEAD && wg == 0) named_arrive(8, 256);
}

template <int BROW0, int I0, int I1>
__device__ __forceinline__ void gemm2_part(float (&c)[36], uint32_t sb, uint32_t pitch, int wg) {
  const uint32_t dA0 = desc_lo(sb + wg * 8192, 8192), dB0 = desc_lo(sb + ASZ + BROW0 * 128, 16);
  wg_fence();
#pragma unroll
  for (int i = I0; i < I1; i++) {
    const int step = 69 - LAG + (i >> 2);
    if ((i & 3) == 0 && BROW0 == 0) mbar_wait_u(sb + BAR_OFF + B_FULL + (step % ST) * 8, (step / ST) & 1);
    if (i == 4 * LAG - TURN && BROW0 && wg == 0) named_arrive(7, 256);
    wgmma_ss<0>(c, dA0 + (step % ST) * (pitch >> 4) + (i & 3) * 128, dB0 + (step % ST) * (pitch >> 4) + (i & 3) * 2, 1);
  }
  wg_commit();
}
__device__ __forceinline__ void split_acc(const float (&acc)[72], float (&a)[36], float (&b)[36]) {
#pragma unroll
  for (int i = 0; i < 36; i++) { asm volatile("mov.b32 %0, %1;" : "=f"(a[i]) : "f"(acc[i])); asm volatile("mov.b32 %0, %1;" : "=f"(b[i]) : "f"(acc[36 + i])); }
}
template <int V0, int V1, int R, class Slice>
__device__ __forceinline__ void gelu_store(const float (&acc)[R], uint32_t bias0, uint32_t bias1, uint32_t sa, uint32_t zero, Slice slice) {
  const uint32_t bb[2] = {pin(bias0) * 0x10001u, pin(bias1) * 0x10001u};
  uint32_t x[2][4], t[2][4], dep[V1 / 8], c3 = 0x3d123d12u;
#pragma unroll
  for (int j = V0 / 8; j <= V1 / 8; j++) {
    if (j < V1 / 8) {
      if (j >= V0 / 8 + GLAG) c3 = (dep[j - GLAG] & zero) | 0x3d123d12u;
#pragma unroll
      for (int u = 0; u < 4; u++) {
        x[j & 1][u] = hadd2(pack_bf16(acc[8 * j + 2 * u], acc[8 * j + 2 * u + 1]), bb[u & 1]);
        t[j & 1][u] = tanh2_ordered(hmul2(x[j & 1][u], hfma2(hmul2(x[j & 1][u], c3), x[j & 1][u], 0x3f4c3f4cu)));
      }
    }
    if (j > V0 / 8) {
      const uint32_t *xx = x[(j - 1) & 1], *tt = t[(j - 1) & 1];
      stsm4_t(sa + (j - 1) * 2048, hfma2(xx[0], tt[0], xx[0]), hfma2(xx[1], tt[1], xx[1]), hfma2(xx[2], tt[2], xx[2]), hfma2(xx[3], tt[3], xx[3]));
      dep[j - 1] = slice(j - 1);
    }
  }
}
struct Role { int half, kind, g2_m, dt, g1_mt, g1_nt, cs, nconv, skip; uint32_t pitch; };
__device__ __forceinline__ Role get_role(const RoleMap& roles) {
  uint32_t b, sm;
  asm volatile("mov.u32 %0, %%ctaid.x;" : "=r"(b));
  asm volatile("mov.u32 %0, %%smid;" : "=r"(sm));
  const uint32_t w = roles.role[(roles.by_sm ? sm : b) >> 1];
  const int half = b & 1, kind = w & 3, m = (w >> 4) & 15, dt = (w >> 2) & 3;
  return Role{half, kind, m * 128, dt, half * 18 + (int)((w >> 8) & 31), (int)(w >> 16), (m * 4 + dt) * 2 + half,
              kind ? 12 * (kind - 1) : 6 - half, kind ? kind & 1 : 2 - 2 * half, kind ? (uint32_t)PITCH_B : (uint32_t)PITCH_S};
}
__device__ __forceinline__ int g2_block(int half, int j) { return j < 0 ? 0 : half * 36 + (j < 12 ? 2 * j : j < 24 ? 2 * j - 23 : j); }
__device__ __forceinline__ int conv_chan(const Role& ro, int i) {
  const bool early = ro.kind == 0 && i < 4;
  const int late = ro.kind ? 144 + 12 * (ro.cs & 3) + i : i == 4 ? ro.cs : 96 + (ro.cs >> 1);
  const int k = early ? 2 * ro.cs + (i & 1) : late;
  return (3 * (k >> 6) + (early ? i >> 1 : 2)) * 64 + (k & 63);
}
__device__ __forceinline__ uint32_t conv_buf(uint32_t sb, int kind, int b) {
  return sb + (kind ? (b ? b + 1 : ST) * PITCH_B : b == 3 ? (36 % ST) * PITCH_S : ST * PITCH_S + b * CBUF);
}
__device__ __forceinline__ uint32_t conv_stage(uint32_t sb, int kind) { return sb + (kind ? ST * PITCH_B + CBUF : ST * PITCH_S + 3 * CBUF); }
__device__ __forceinline__ uint32_t u_stage(uint32_t sb, uint32_t pitch, int w) { return sb + (2 - w) * pitch + ASZ; }

__global__ void __cluster_dims__(2, 1, 1) __launch_bounds__(384, 1)
fused_kernel(const __nv_bfloat16* __restrict__ q, Scratch* __restrict__ gs, const __nv_bfloat16* __restrict__ b1,
             const __nv_bfloat16* __restrict__ shiftk, const __nv_bfloat16* __restrict__ ssmk, const __nv_bfloat16* __restrict__ ssmD,
             const __grid_constant__ Maps tm, const __grid_constant__ RoleMap roles, const __nv_bfloat16* __restrict__ b2,
             __nv_bfloat16* __restrict__ out) {
  const int cta = blockIdx.x;
  const int tid = threadIdx.x;

  const uint32_t t_start = clock_now();
  const int lc = (cta + LNROT) & 127;
  const uint32_t do_ln = cta < 128 && tid < 256;
  const int oct = lc + (tid & 128), ln_row = oct * 8 + ((tid >> 4) & 7), l16 = tid & 15;
  uint2 xr[9];
  const __nv_bfloat16* qrow = q + (size_t)ln_row * D_ + l16 * 4;
  asm volatile("" : "+l"(qrow));
  const int warp = __shfl_sync(0xffffffffu, tid >> 5, 0);
  if (warp < 8 || warp == 11) asm volatile("barrier.cluster.arrive.relaxed.aligned;" ::: "memory");
  if (do_ln && oct >= QLATE) spin_until(t_start, QDELAY + QRAMP * oct / 2);
#pragma unroll
  for (int i = 0; i < 9; i++) xr[i] = ldg64_if(qrow + i * 64, do_ln);
  const uint32_t sb = __shfl_sync(0xffffffffu, (uint32_t)__cvta_generic_to_shared(smem_raw), 0);
  const uint32_t bars = sb + BAR_OFF;
  const int lane = tid & 31;
  const int wg = warp >> 2;
  constexpr int LN_OFF = ST * PITCH_B;

  uint32_t look = 0;
  if (warp < 8 || warp == 11) {
    const int hq = (lane & 16) >> 3, hb = (lane & 16) + hq;
    float da[3][4] = {};
#pragma unroll
    for (int i = 0; i < 9; i++) mma16816(da[i % 3], xr[i].x, 0x3f803f80u, xr[i].y, 0x3f803f80u, xr[i].x, xr[i].y);
    const float r1 = ((da[0][2] + da[0][3]) + (da[1][2] + da[1][3])) + (da[2][2] + da[2][3]);
    const float r2 = (lane & 4) ? (da[0][1] + da[1][1]) + da[2][1] : (da[0][0] + da[1][0]) + da[2][0];
    const float s1 = __shfl_sync(0xffffffffu, r1, hq) + __shfl_sync(0xffffffffu, r1, hq + 1);
    const float s2 = (__shfl_sync(0xffffffffu, r2, hb) + __shfl_sync(0xffffffffu, r2, hb + 4)) + (__shfl_sync(0xffffffffu, r2, hb + 9) + __shfl_sync(0xffffffffu, r2, hb + 13));
    const float mean = s1 * (1.f / D_), var = fmaxf(fmaf(-mean, mean, s2 * (1.f / D_)), 0.f);
    const float rinv = ln_rinv(var), rinv2 = ln_rinv(var * rinv * rinv), scale = rinv * rinv2, shift = -bf_round((mean - bf_round(mean)) * rinv) * rinv2;
    const uint32_t m2 = pack_bf16(mean, mean), hi2 = pack_bf16(scale, scale), lo2 = pack_bf16(scale - bf_lo(hi2), scale - bf_lo(hi2)), sh2 = pack_bf16(shift, shift);
    const uint32_t hi1 = pack_bf16(rinv, rinv);
    asm volatile("{\n.reg .pred p;\nsetp.eq.u32 p, %5, 0;\n@p st.shared.v4.u32 [%0], {%1, %2, %3, %4};\n}" ::"r"(sb + LN_OFF + 18432 + tid), "r"(m2), "r"(hi1),
                 "r"(pack_bf16(rinv - bf_lo(hi1), rinv - bf_lo(hi1))), "r"(0u), "r"(tid & 0x10f) : "memory");
    const uint32_t g0 = 4 * (l16 >> 3) + 2 * (l16 & 1), hrow = sb + LN_OFF + ((tid >> 7) & 1) * 9216 + (tid & 0x70);
    const uint32_t hs0 = hrow + g0 * 128 + ((l16 >> 1) & 3) * 4, hs8 = ((hrow + (l16 >> 1) * 1152) ^ ((l16 >> 1) << 4)) + 1024 + (l16 & 1) * 8;
    uint32_t w[18];
#pragma unroll
    for (int i = 0; i < 18; i++) {
      const uint32_t d = hsub2((i & 1) ? xr[i >> 1].y : xr[i >> 1].x, m2);
      asm("max.u32 %0, %1, 1;" : "=r"(w[i]) : "r"(hfma2(d, hi2, hfma2(d, lo2, sh2))));
    }
#pragma unroll
    for (int i = 0; i < 16; i++) {
      const int gi = 9 * (i >> 1) + (i & 1);
      asm volatile("{\n.reg .pred p;\nsetp.ne.u32 p, %2, 0;\n@p st.shared.u32 [%0], %1;\n}" ::"r"((hs0 ^ ((g0 * 16 + (gi & 7) * 16) & 0x70)) + gi * 128), "r"(w[i]), "r"(do_ln) : "memory");
    }
    asm volatile("{\n.reg .pred p;\nsetp.ne.u32 p, %3, 0;\n@p st.shared.v2.u32 [%0], {%1, %2};\n}" ::"r"(hs8), "r"(w[16]), "r"(w[17]), "r"(do_ln) : "memory");
    fence_async_smem();
    if (warp < 8) named_arrive(wg, 160);
  } else if (warp != 8) {
    spin_until(t_start, W9);
  }

  if (wg == 2) {
    asm volatile("setmaxnreg.dec.sync.aligned.u32 56;");
    auto store_h = [&](int w) {
      named_bar(w, 160);
      if (cta < 128 && elect_one()) {
        tma3d_store(&tm.m[M_H], ((lc >> 3) + 16 * w) * 72, lc & 7, sb + LN_OFF + w * 9216);
        bulk_s2g(gs->stats + (lc + 128 * w) * 8, sb + LN_OFF + 18432 + w * 128, 128);
        bulk_commit();
      }
    };
    auto publish_h = [&](int w) {
      if (cta < 128 && elect_one()) { bulk_wait_all(); flag_add(gs->flags, FL_H + (w ? 2 : lc >> 6), 2 - w); }
      __syncwarp();
    };
    if (warp == 11) {
      if (lc >= 64) spin_until(t_start, HW);
      store_h(0);
      look = flag_ld(gs->flags, FL_H);
      if (lc < 64) publish_h(0);
    } else {
      if (elect_one()) {
        if (warp == 8) {
#pragma unroll
          for (int o = 0; o < B_GO; o += 8) mbar_init(bars + o, 1);
        } else {
#pragma unroll
          for (int o = 0; o < (B_EMPTY - B_GO) / 2; o += 8) mbar_init(bars + B_GO + (warp - 9) * ((B_EMPTY - B_GO) / 2) + o, 1);
#pragma unroll
          for (int o = 0; o < (B_CEMPTY - B_EMPTY) / 2; o += 8) mbar_init(bars + B_EMPTY + (warp - 9) * ((B_CEMPTY - B_EMPTY) / 2) + o, 2);
#pragma unroll
          for (int o = 0; o < (B_END - B_CEMPTY) / 2; o += 8) mbar_init(bars + B_CEMPTY + (warp - 9) * ((B_END - B_CEMPTY) / 2) + o, 4);
        }
        asm volatile("fence.mbarrier_init.release.cluster;" ::: "memory");
      }
      __syncwarp();
      asm volatile("barrier.cluster.arrive.relaxed.aligned;" ::: "memory");
#pragma unroll
      for (int k = 0; k < 3; k++) prefetch_map(&tm.m[warp == 8 ? k : 3 * warp - 25 + k]);
    }
    const Role ro = get_role(roles);
    if (warp != 8) asm volatile("barrier.cluster.wait.aligned;" ::: "memory");
    if (warp == 11) {
      Ring r{0, 1};
      const uint32_t bsz = ro.pitch - ASZ;
      const uint8_t* src = gs->h + ro.g1_nt * bsz + ST * 73728;
      named_bar(10, 64);
#pragma unroll 1
      for (int i = ST; i < 32; i++) {
        if (i == ST || i == 8 || i == 16) wait_counter(gs->flags, FL_H + (i >> 3), 128u, look, 0);
        if (i == LK1 || i == LK2) look = flag_ld(gs->flags, FL_H + (i >> 3) + 1);
        mbar_wait(bars + B_EMPTY + r.s * 8, r.ph ^ 1);
        if (elect_one()) bulk_g2s(sb + r.s * ro.pitch + ASZ, src, bsz, bars + B_FULL + r.s * 8);
        if (i == HS2) store_h(1);
        if (i == HS2 + 2 || (i == ST && lc >= 64)) publish_h(i != ST);
        if (i == KVGO1 && lane == 0) mbar_arrive(bars + B_KVGO + 8);
        if (i == KVGO && lane == 0) mbar_arrive(bars + B_KVGO);
        if (i == CVGO && lane == 0) mbar_arrive(bars + B_CVGO);
        src += 73728;
        r.next();
      }
      if (ro.kind != 2) {
        look = 0;
#pragma unroll 1
        for (int j = -1; j < 36; j++) {
          const uint8_t* su = gs->u + ((size_t)g2_block(ro.half, j) * D_ + ro.dt * 144) * 128;
          const int uc = j < 0 ? FL_U : FL_U + 1 + 2 * ro.half + (j > 16);
          if (j == -1 || j == 12 || j == 24) wait_counter(gs->flags, uc, 288u, look, 100);
          if (j == (ro.skip ? 4 : -1) || j == 3) mbar_wait_u(bars + B_UDONE + (j == 3 ? 8 : 0), 0);
          if (j >= ro.skip - 1) mbar_wait(bars + B_EMPTY + r.s * 8, r.ph ^ 1);
          if (j >= ro.skip - 1 && elect_one()) {
            bulk_g2s(sb + r.s * ro.pitch + ASZ, su + (ro.half ^ 1) * 9216, 9216, bars + B_FULL + r.s * 8);
            bulk_g2s(sb + r.s * ro.pitch + ASZ + 9216, su + ro.half * 9216, 9216, bars + B_FULL + r.s * 8);
          }
          if (j == 9 || j == 21) look = flag_ld(gs->flags, uc);
          r.next();
        }
#pragma unroll 1
        for (int o = lane; o < ST * 73728 / 16 / NG2; o += 32) ((uint4*)gs->h)[ro.cs * (ST * 73728 / 16 / NG2) + o] = make_uint4(0u, 0u, 0u, 0u);
      }
    } else if (warp == 8) {
      const uint64_t pol = stream_policy();
      Ring r{0, 0};
#pragma unroll 1
      for (int i = 0; i < 32; i++) {
        if (i < ST) spin_until(t_start, A0 + i * AD + (i >= AN ? AL : 0));
        if (i == ST) {
          asm volatile("barrier.cluster.wait.aligned;" ::: "memory");
          if (roles.by_sm) {
            uint32_t sm;
            asm volatile("mov.u32 %0, %%smid;" : "=r"(sm));
            if (elect_one()) { mbar_expect(bars + B_PEER, 8); st_async2(mapa(bars + B_END, ro.half ^ 1), sm, sm, mapa(bars + B_PEER, ro.half ^ 1)); }
            mbar_wait_u(bars + B_PEER, 0);
            if ((lds32(bars + B_END) ^ sm) != 1 || sm >= NCTA) asm volatile("trap;");
          }
        }
        if (i >= ST) mbar_wait(bars + B_EMPTY + r.s * 8, r.ph ^ 1);
        if (elect_one()) {
          mbar_expect(bars + B_FULL + r.s * 8, ro.pitch);
          tma_weights(sb + r.s * ro.pitch, &tm.m[M_W1], i * 64, ro.g1_mt * 2, bars + B_FULL + r.s * 8, pol);
        }
        r.next();
      }
      if (ro.kind != 2) {
#pragma unroll 1
        for (int j = -1; j < 36; j++) {
          if (j == 3 && ro.kind == 0) mbar_wait_u(bars + B_CEMPTY + 24, 0);
          if (j >= ro.skip - 1) mbar_wait(bars + B_EMPTY + r.s * 8, r.ph ^ 1);
          if (j >= ro.skip - 1 && elect_one()) {
            mbar_expect(bars + B_FULL + r.s * 8, PITCH_S);
            tma_weights(sb + r.s * ro.pitch, &tm.m[M_W2], g2_block(ro.half, j) * 64, ro.g2_m >> 6, bars + B_FULL + r.s * 8, pol);
            if (j == 26 + ro.dt) tma_weights_prefetch(&tm.m[M_W2], g2_block(ro.half, j + 6) * 64, ro.g2_m >> 6, pol);
          }
          r.next();
        }
        if (lane < 2) mbar_expect(bars + B_RFULL + lane * 8, 9216);
        __syncwarp();
        mbar_wait(bars + B_EMPTY + r.s * 8, r.ph ^ 1);
        if (lane == 0) mbar_arrive_cluster(mapa(bars + B_GO, ro.half ^ 1));
      }
    } else {
      const uint64_t pol = stream_policy();
      {
        const uint32_t hb = (ro.pitch - ASZ) >> 1, raw = bars + B_RAW + (warp - 9) * 40, dst = sb + ASZ + (warp - 9) * hb;
        const uint8_t* src = gs->h + (2 * ro.g1_nt + warp - 9) * hb;
        auto fetch_h = [&](int i) { if (elect_one()) { mbar_expect(raw + i * 8, hb); bulk_g2s(dst + i * ro.pitch, src + i * 73728, hb, raw + i * 8); } };
        int next = 0;
#pragma unroll 1
        for (int i = -1; i < ST; i++) {
          if (i >= 0) {
#pragma unroll 1
            for (uint32_t tries = 0;; tries++) {
              mbar_wait_u(raw + i * 8, tries & 1);
              const uint32_t pa = dst + i * ro.pitch + lane * 32 + (lane >> 2) * 4;
              uint32_t m = 1;
#pragma unroll
              for (int j = 0; j < 12; j++) m = min(m, lds32(pa + (j < 9 || ro.kind ? j : 0) * 1024));
              if (__all_sync(0xffffffffu, m)) break;
              fetch_h(i);
            }
            if (elect_one()) asm volatile("mbarrier.complete_tx.relaxed.cta.shared::cta.b64 [%0], %1;" ::"r"(bars + B_FULL + i * 8), "r"(hb) : "memory");
          }
#pragma unroll 1
          for (const int end = min(next + (i == 0 ? 1 : 2), ST); next < end; next++) {
            if (i < 0) spin_until(t_start, H0 + next * HD);
            fetch_h(next);
          }
          if (i < 0 && warp == 10) named_arrive(10, 64);
        }
      }
      const int chan = conv_chan(ro, lane < ro.nconv ? lane : 0);
      const uint32_t dskip = ldg16(ssmD + chan);
      uint4 shk;
      mbar_wait_u(bars + B_KVGO + (ro.kind ? 8 : (warp - 9) * 8), 0);
      if (ro.kind) shk = ldg128(ssmk + (size_t)chan * S_);
      else {
        const int cs = ro.cs, grp = (cs / 3) * 2 + warp - 9, cb0 = (cs % 3) * 3;
        const uint32_t kin_s = sb + ST * PITCH_S + (warp - 9) * KVW, kout = kin_s + 2 * KVIN, fb = bars + B_KFULL + (warp - 9) * 16;
        auto fetch = [&](int i) {
          if (elect_one()) {
            mbar_expect(fb + (i & 1) * 8, KVIN);
            tma2d_stream(kin_s + (i & 1) * KVIN, &tm.m[M_K], (cb0 + i) * 64, grp * 32 - 4, fb + (i & 1) * 8, pol);
            tma2d_stream(kin_s + (i & 1) * KVIN + 4608, &tm.m[M_V], (cb0 + i) * 64, grp * 32 - 1, fb + (i & 1) * 8, pol);
          }
        };
        fetch(0);
        shk = ldg128(shiftk + (cb0 * 64 + lane * 2) * 4);
#pragma unroll 1
        for (int i = 0; i < 3; i++) {
          const uint32_t w0 = __byte_perm(shk.x, shk.z, 0x5410), w1 = __byte_perm(shk.x, shk.z, 0x7632);
          const uint32_t w2 = __byte_perm(shk.y, shk.w, 0x5410), w3 = __byte_perm(shk.y, shk.w, 0x7632);
          const uint32_t ka = kin_s + (i & 1) * KVIN + lane * 4;
          mbar_wait_u(fb + (i & 1) * 8, i >> 1);
          if (i < 2) fetch(i + 1);
          shk = ldg128(i < 2 ? shiftk + ((cb0 + i + 1) * 64 + lane * 2) * 4 : ssmk + (size_t)chan * S_);
          uint32_t kr[8], vr[8], t1, t2, t3, xp;
          {
            const uint32_t k0 = lds32(ka), k1 = lds32(ka + 128), k2 = lds32(ka + 256), k3 = lds32(ka + 384), v0 = lds32(ka + 4608);
#pragma unroll
            for (int j = 0; j < 8; j++) { kr[j] = lds32(ka + 512 + j * 128); vr[j] = lds32(ka + 4736 + j * 128); }
            xp = hmul2(hfma2(k3, w0, hfma2(k2, w1, hfma2(k1, w2, hmul2(k0, w3)))), v0);
            t1 = hfma2(k3, w1, hfma2(k2, w2, hmul2(k1, w3)));
            t2 = hfma2(k3, w2, hmul2(k2, w3));
            t3 = hmul2(k3, w3);
          }
#pragma unroll 1
          for (int o = 0; o < 4; o++) {
            const uint32_t from = ka + o * 1024, to = kout + (o >> 1) * 5120 + lane * 80 + (o & 1) * 32;
#pragma unroll
            for (int m = 0; m < 8; m += 4) {
              uint32_t x[4];
#pragma unroll
              for (int j = 0; j < 4; j++) {
                x[j] = hmul2(hfma2(kr[m + j], w0, t1), vr[m + j]);
                t1 = hfma2(kr[m + j], w1, t2);
                t2 = hfma2(kr[m + j], w2, t3);
                t3 = hmul2(kr[m + j], w3);
              }
#pragma unroll
              for (int c = 0; c < 2; c++) {
                const uint32_t sel = c ? 0x7632 : 0x5410;
                sts128(to + c * 2560 + m * 4, __byte_perm(x[0], xp, sel), __byte_perm(x[1], x[0], sel), __byte_perm(x[2], x[1], sel), __byte_perm(x[3], x[2], sel));
              }
#pragma unroll
              for (int j = m; j < m + 4; j++) { kr[j] = lds32_if(from + 1536 + j * 128, o < 3); vr[j] = lds32_if(from + 5760 + j * 128, o < 3); }
              xp = x[3];
            }
            if (o & 1) {
              fence_async_smem();
              __syncwarp();
              if (elect_one()) {
                bulk_wait_all();
                if (o == 1 && i) flag_add(gs->flags, FL_KV + i - 1, 1);
                tma4d_store(&tm.m[M_KV], (cb0 + i) * 32, 0, 2 * grp + (o >> 1), kout + (o >> 1) * 5120);
                bulk_commit();
              }
              __syncwarp();
            }
          }
        }
        look = flag_ld(gs->flags, FL_KV + warp - 9);
        if (lane == 2 * (warp - 9)) bulk_prefetch(ssmk + (size_t)chan * S_, 2 * S_ * 2, pol);
        if (elect_one()) {
          bulk_wait_all();
          flag_add(gs->flags, FL_KV + 2, 1);
        }
        __syncwarp();
      }
      {
        shk.x = __byte_perm(pack_bf16(bf_lo(shk.x) + bf_lo(dskip), 0.f), shk.x, 0x7610);
        const int mid = ro.kind ? 1 : 2;
#pragma unroll 1
        for (int i = warp == 9 ? 0 : mid; i < (warp == 9 ? min(mid, ro.nconv) : ro.nconv); i++) {
          const int b = i & 3, d = __shfl_sync(0xffffffffu, chan, i);
          const uint32_t base = conv_buf(sb, ro.kind, b), cf = bars + B_CFULL + b * 8;
          if (ro.kind ? i < 2 : !(i & 1)) wait_counter(gs->flags, FL_KV + (ro.kind ? 2 : i >> 1), 192u, i < 4 ? look : 0u, 200);
          if (i == mid) {
            mbar_wait_u(bars + B_CVGO, 0);
            if (ro.kind) mbar_wait_u(bars + B_EMPTY + (32 % ST) * 8, ((32 / ST) & 1) ^ 1);
            else spin_until(clock_now(), 600);
          }
          if (i == mid + 1) {
            mbar_wait_u(bars + B_G1DONE, 0);
            if (lane >= 4 && lane < ro.nconv) bulk_prefetch(ssmk + (size_t)chan * S_, S_ * 2, pol);
          }
          if (i >= 4) mbar_wait_u(bars + B_CEMPTY + b * 8, i >> 3);
          if (lane == i) sts128(base + CH_OFF, shk.x, shk.y, shk.z, shk.w);
          if (lane >= 29) sts128(base + CH_OFF + (lane - 32) * 16, 0u, 0u, 0u, 0u);
          fence_async_smem();
          __syncwarp();
          if (elect_one()) mbar_expect(cf, 4080 + 64 * 160);
#pragma unroll 1
          for (int k = 0; k < 5; k++) {
            if (elect_one()) {
              if (k < 4) asm volatile("cp.async.bulk.tensor.3d.shared::cluster.global.mbarrier::complete_tx::bytes [%0], [%1, {%3, %4, %5}], [%2];"
                                      ::"r"(base + CT_OFF + k * 2560), "l"(&tm.m[M_KL]), "r"(cf), "r"(0), "r"(k * 16), "r"(d) : "memory");
              else bulk_g2s_stream(base + CH_OFF + 16, ssmk + (size_t)d * S_ + 8, 4080, cf, pol);
            }
          }
        }
      }
      if (warp == 9) {
        if (lane < 12) asm volatile("st.shared.u16 [%0], %1;" ::"r"(bars + B_END + 8 + lane * 2), "h"((uint16_t)chan_pos(chan)) : "memory");
        __syncwarp();
        if (elect_one()) {
          const uint32_t bsz = ro.pitch - ASZ;
          if (ro.kind) { mbar_wait_u(bars + B_G1DONE, 0); gate_arrive(gs->flags, GDELAY + BLK_NS - (ro.kind == 1 ? GBIG : 0)); }
#pragma unroll 1
          for (int w = 0; w < 2; w++) {
            const uint32_t src = u_stage(sb, ro.pitch, w);
            mbar_wait_u(bars + B_USTG + w * 8, 0);
            bulk_s2g(gs->u + (size_t)(2 * ro.g1_mt + w) * D_ * 128 + ro.g1_nt * bsz, src, bsz);
            bulk_commit();
            if (w < ro.skip) {
              mbar_arrive(bars + B_FULL + (2 + w) * 8);
              mbar_arrive(bars + B_EMPTY + (2 + w) * 8);
              mbar_arrive(bars + B_EMPTY + (2 + w) * 8);
            }
            bulk_wait_read();
            mbar_arrive(bars + B_UDONE + w * 8);
            if (ro.kind && !w) continue;
            bulk_wait_all();
            flag_add(gs->flags, FL_U + (w ? 1 + 2 * ro.half + (ro.kind != 0) : 0), ro.kind ? 16 : 3 + 3 * w);
          }
#pragma unroll 1
          for (int i = 0; i < ro.nconv; i++) {
            mbar_wait_u(bars + B_SFULL + (i & 1) * 8, (i >> 1) & 1);
            uint32_t pos;
            asm volatile("ld.shared.u16 %0, [%1];" : "=r"(pos) : "r"(bars + B_END + 8 + i * 2) : "memory");
            bulk_s2g(gs->z + (size_t)pos * S_, conv_stage(sb, ro.kind) + (i & 1) * 4096, 4096);
            bulk_commit();
            if (ro.kind == 0 && i == ro.nconv - 4) gate_arrive(gs->flags, ro.skip * BLK_NS);
            bulk_wait_read();
            mbar_arrive(bars + B_SEMPTY + (i & 1) * 8);
          }
          bulk_wait_all();
          flag_add(gs->flags, FL_Z + (ro.kind >> 1), ro.kind == 2 ? 32 : 1);
        }
      } else if (ro.kind != 2) {
        mbar_wait_u(bars + B_G1DONE, 0);
        uint2 gate;
#pragma unroll 1
        for (uint32_t spins = 0;; spins++) {
          asm volatile("ld.relaxed.gpu.global.v2.u32 {%0, %1}, [%2];" : "=r"(gate.x), "=r"(gate.y) : "l"(gs->flags + FL_GATE * 32) : "memory");
          if (gate.x == NCTA) break;
          __nanosleep(100);
          if (spins > SPIN_LIMIT) asm volatile("trap;");
        }
#pragma unroll 1
        for (int w = 0; w < 2; w++) {
          while (time_now() - gate.y < GDELAY + ro.skip * BLK_NS + w * GDELAY1) {}
          if (lane == 0) mbar_arrive(bars + B_G2GO + (w ^ (ro.nconv & 1)) * 8);
        }
        if (lane < 2) mbar_expect(bars + B_ZFULL + lane * 8, lane ? 2048 : 16384);
#pragma unroll 1
        for (int k = 0; k < 18; k++) {
          if ((k & 15) == 0) wait_counter(gs->flags, FL_Z + (k >> 4), NG2, 0, 100);
          if (k < 16) spin_until(clock_now(), ZGAP);
          if (elect_one()) tma2d(sb + ST * ro.pitch + (k & 1) * 9216 + (k >> 1) * 1024, &tm.m[M_Z], ro.g2_m + (k & 1) * 64, ro.dt * 144 + ro.half * 72 + (k >> 1) * 8, bars + B_ZFULL + (k >> 4) * 8);
        }
      }
    }
    if (warp >= 10) polling_done(gs->flags, lane);
  } else {
    asm volatile("setmaxnreg.inc.sync.aligned.u32 224;");
    const int wi = warp & 3, g = lane >> 2, qd = lane & 3, wt = tid & 127;
    const bool leader = wt == 0;
    Pipe p{{0, 0}, 0, false};
    asm volatile("barrier.cluster.wait.aligned;" ::: "memory");
    int kind;
    {
      const Role ro = get_role(roles);
      kind = ro.kind;
      const int f0 = ro.g1_mt * 128 + wg * 64 + wi * 16 + g;
      uint32_t bias0 = ldg16(b1 + f0), bias1 = ldg16(b1 + f0 + 8);
      const uint32_t so = ((lane >> 4) * 8 + (lane & 7)) * 128 + (((2 * wi + ((lane >> 3) & 1)) ^ (lane & 7)) << 4);
      const int cB = (g >> 1) & 1, cA = g >> 2, b = 2 * wi + (g & 1), nconv = ro.nconv;
      const uint32_t toff = pin(CT_OFF + (40 * (2 * cA + cB) + 8 + b - 2 * qd) * 4);
      const int phi = 2 * cA + (qd >> 1) + cB, pp = cB ? (phi & 3) : ((phi + 3) & 3);
      const int srcB = shfl_ordered(((pp >> 1) << 4) | ((cB ^ 1) << 3) | ((g & 1) << 2) | ((pp & 1) << 1) | (qd & 1), lane);
      const bool pB1 = cB && phi < 4, pB2 = cB && phi == 4;
      const int word = (8 * cB + 2 * (phi & 3) + (qd & 1)) * 8 + b;
      const uint32_t sto = shfl_ordered(conv_stage(sb, kind) + wg * 4096 + (word ^ (((word >> 5) & 3) << 1)) * 4, lane);
      const uint32_t sa = shfl_ordered(u_stage(sb, ro.pitch, wg) + so, lane);
      uint32_t a[16][4];
      auto load_a = [&](uint32_t base, int t, uint32_t on) {
        const uint32_t pt = base + toff + (t >> 1) * 1280 + (t & 1) * 64;
        a[t][0] = lds32_if(pt + 32, on); a[t][1] = lds32_if(pt + 672, on); a[t][2] = lds32_if(pt, on); a[t][3] = lds32_if(pt + 640, on);
      };
      auto gemm1_done = [&]() {
        pipe_drain(p, bars, leader);
        if (leader) mbar_arrive(bars + B_G1DONE);
        mbar_wait_u(bars + B_EMPTY + (2 - wg) * 8, wg ^ 1);
      };
      {
        float acc[72];
        if (kind) {
          float big[96];
          gemm_run<1, LEAD_B>(big, 32, 0, p, sb, PITCH_B, wg, leader);
          if (wg == 1) named_arrive(6, 256);
          if (wg < nconv) mbar_wait_u(bars + B_CFULL + wg * 8, 0);
#pragma unroll
          for (int t = 0; t < 8; t++) load_a(conv_buf(sb, 1, wg), t, wg < nconv);
          gemm1_done();
          gelu_store<72, 96>(big, bias0, bias1, sa, 0u, [](int) { return 0u; });
#pragma unroll
          for (int i = 0; i < 72; i++) asm volatile("mov.b32 %0, %1;" : "=f"(acc[i]) : "f"(big[i]));
        } else {
          gemm_run<1, 0>(acc, 32 - LEAD_S, 0, p, sb, PITCH_S, wg, leader);
          if (wg == 1) { pipe_drain(p, bars, leader); named_bar(8, 256); }
#pragma unroll
          for (int k = 32 - LEAD_S; k < 32; k++) {
            mbar_wait_u(bars + B_FULL + (k % ST) * 8, (k / ST) & 1);
            wg_fence();
#pragma unroll
            for (int i = 0; i < 4; i++)
              wgmma_ss<1>(acc, desc_lo(sb + wg * 8192, 8192) + (k % ST) * (PITCH_S >> 4) + i * 128, desc_lo(sb + ASZ, 128) + (k % ST) * (PITCH_S >> 4) + i * 16, 1);
            wg_commit();
            if (k == 32 - PREN) mbar_wait_u(bars + B_CFULL + wg * 8, 0);
            if (k >= 32 - PREN) {
#pragma unroll
              for (int t = (k - 32 + PREN) * 8 / PREN; t < (k - 31 + PREN) * 8 / PREN; t++) load_a(conv_buf(sb, 0, wg), t, 1);
            }
            wg_wait<1>();
            if (leader && (k > 32 - LEAD_S || wg == 0)) mbar_arrive(bars + B_EMPTY + ((k - 1) % ST) * 8);
          }
          p.prev = 31 % ST;
          named_arrive(8 - 2 * wg, 256);
          gemm1_done();
        }
        gelu_store<0, 72>(acc, bias0, bias1, sa, roles.by_sm >> 1, [&](int t) { return t + GLAG < 9 ? lds32(bars) : 0u; });
        fence_async_smem();
        __syncwarp();
        if (lane == 0) mbar_arrive(bars + B_USTG + wg * 8);
      }
      {
#pragma unroll 1
        for (int i = wg; i < nconv; i += 2) {
          const uint32_t base = conv_buf(sb, kind, i & 3), next = conv_buf(sb, kind, (i + 2) & 3);
          const uint64_t dH = mkdesc(base + CH_OFF, 16, 128, 0);
          float y[8][16];
          if (toff < CT_OFF + 32) a[0][2] = 0u;
          named_bar(6 + wg, 256);
          wg_fence();
#pragma unroll
          for (int t = 0; t < 16; t++) {
            if (t == 8) wg_fence();
            if (t == CTURN) named_arrive(7 - wg, 256);
#pragma unroll
            for (int cb = t >> 1; cb < 8; cb++) {
              wgmma_rs_n32(y[cb], a[t][0], a[t][1], a[t][2], a[t][3], dH + (32 * cb - 32 * (t >> 1) - 2 * (t & 1) - 1), t);
              const int n = 8 * t - (t >> 1) * ((t - 1) >> 1) - (t >> 1) + cb + 1;
              if (n % CPER == 0 && n / CPER <= 8) load_a(base, 7 + n / CPER, 1);
            }
          }
          wg_commit();
          const bool more = i + 2 < nconv;
          if (more) mbar_wait_u(bars + B_CFULL + ((i + 2) & 3) * 8, ((i + 2) >> 2) & 1);
          mbar_wait_u(bars + B_SEMPTY + wg * 8, ((i >> 1) & 1) ^ 1);
          wg_wait<0>();
          if (lane == 0) mbar_arrive(bars + B_CEMPTY + (i & 3) * 8);
          uint32_t P[16], Q[16], R[16], o[8];
#pragma unroll
          for (int j = 0; j < 32; j++) {
            if ((j & 3) == 0) load_a(next, j >> 2, more);
            float v0 = y[j >> 2][4 * (j & 3)], v1 = y[j >> 2][4 * (j & 3) + 1];
            if (j >= 2) { v0 += y[(j - 2) >> 2][4 * ((j - 2) & 3) + 2]; v1 += y[(j - 2) >> 2][4 * ((j - 2) & 3) + 3]; }
            if (j & 1) R[j >> 1] = shfl_ordered(pack_bf16(v0, v1), lane ^ 16);
            else P[j >> 1] = pack_bf16(v0, v1);
          }
#pragma unroll
          for (int m = 0; m < 16; m++) Q[m] = hadd2(P[m], cA ? R[m] : (m ? R[m - 1] : 0u));
#pragma unroll
          for (int m = 0; m < 8; m++) o[m] = shfl_ordered(pB1 ? Q[2 * m] : (pB2 ? (m ? Q[2 * m - 1] : 0u) : Q[2 * m + 1]), srcB);
#pragma unroll
          for (int m = 0; m < 8; m++) sts32(sto + m * 512, hadd2(pB1 ? Q[2 * m + 1] : Q[2 * m], o[m]));
          fence_async_smem();
          __syncwarp();
          if (lane == 0) mbar_arrive(bars + B_SFULL + wg * 8);
        }
        if (wg == (nconv & 1)) named_bar(6 + wg, 256);
      }
    }
    if (kind != 2) {
      const Role ro = get_role(roles);
      const uint32_t pitch = ro.pitch;
      const int s0 = ro.g2_m + wg * 64 + wi * 16 + g;
      const size_t go = (size_t)s0 * D_ + ro.dt * 128 + ro.half * 64 + qd * 8, go8 = (size_t)s0 * D_ + 512 + ro.dt * 16 + ro.half * 8 + qd * 2;
      uint32_t x[2][9], sg[2][9];
      float acc[72];
      p.r = Ring{(uint32_t)(2 + ro.skip), 0};
      mbar_wait_u(bars + B_G2GO + wg * 8, 0);
      gemm_run<0, 0>(acc, XAT + 2 * wg + 1 - ro.skip, 0, p, sb, pitch, wg, leader);
#pragma unroll
      for (int J = 0; J < 4; J++) {
        const uint4 v = ldg128(q + go + (J & 1) * 8 * D_ + (J >> 1) * 32);
        x[J & 1][4 * (J >> 1)] = v.x; x[J & 1][4 * (J >> 1) + 1] = v.y; x[J & 1][4 * (J >> 1) + 2] = v.z; x[J & 1][4 * (J >> 1) + 3] = v.w;
      }
      x[0][8] = ldg32(q + go8); x[1][8] = ldg32(q + go8 + 8 * D_);
      const uint4 st0 = ld_l2(gs->stats + s0), st1 = ld_l2(gs->stats + s0 + 8);
      const uint32_t braw0 = ldg16(b2 + s0), braw1 = ldg16(b2 + s0 + 8);
      gemm_run<0, 0>(acc, ZAT - XAT, 1, p, sb, pitch, wg, leader);
      const int zw = 8 * wi + (g ^ ((((ro.g2_m >> 6) + wg) & 3) << 1));
      const uint32_t za = sb + ST * pitch + wg * 9216 + qd * 256 + (zw & 3) * 4 + (((zw >> 2) ^ (2 * qd)) << 4);
      mbar_wait_u(bars + B_ZFULL, 0);
#pragma unroll
      for (int j = 0; j < 8; j++) { sg[0][j] = lds32(za + j * 1024); sg[1][j] = lds32((za ^ 16) + j * 1024 + 128); }
      gemm_run<0, 0>(acc, 1, 1, p, sb, pitch, wg, leader);
#pragma unroll
      for (int j = 0; j < 9; j++) {
        const uint32_t xn0 = ln_apply(x[0][j], st0), xn1 = ln_apply(x[1][j], st1);
        if (j < 8) {
          const uint32_t z0 = __byte_perm(sg[0][j], sg[1][j], 0x5410), z1 = __byte_perm(sg[0][j], sg[1][j], 0x7632);
          sg[0][j] = hmul2(xn0, z0); sg[1][j] = hmul2(xn1, z1);
        } else { sg[0][j] = xn0; sg[1][j] = xn1; }
        asm volatile("" : "+r"(sg[0][j]), "+r"(sg[1][j]));
      }
      gemm_run<0, SKEW>(acc, 35 - ZAT - LAG - 2 * wg, 1, p, sb, pitch, wg, leader);
      const uint32_t rbuf = sb + (69 % ST) * pitch + warp * 2304;
      const uint32_t rdst = mapa(rbuf, ro.half ^ 1), rbar = mapa(bars + B_RFULL + wg * 8, ro.half ^ 1);
      pipe_drain(p, bars, leader);
      float cs[36], ck[36];
      split_acc(acc, cs, ck);
      gemm2_part<0, 0, 4 * LAG>(cs, sb, pitch, wg);
      if (KPRE) gemm2_part<72, 0, KPRE>(ck, sb, pitch, wg);
      const float hb0 = fmaf(bf_lo(braw0), 0.5f, __uint_as_float(st0.w)), hb1 = fmaf(bf_lo(braw1), 0.5f, __uint_as_float(st1.w));
      mbar_wait(bars + B_GO, 0);
      wg_wait<KPRE ? 1 : 0>();
#pragma unroll
      for (int i = 0; i < 5; i++) {
        const float* c = &cs[8 * i];
        const uint32_t v0 = pack_bf16(fmaf(c[0], 0.25f, hb0), fmaf(c[1], 0.25f, hb0)), v1 = pack_bf16(fmaf(c[2], 0.25f, hb1), fmaf(c[3], 0.25f, hb1));
        if (i < 4) st_async4(rdst + i * 512 + lane * 16, v0, v1, pack_bf16(fmaf(c[4], 0.25f, hb0), fmaf(c[5], 0.25f, hb0)), pack_bf16(fmaf(c[6], 0.25f, hb1), fmaf(c[7], 0.25f, hb1)), rbar);
        else st_async2(rdst + 2048 + lane * 8, v0, v1, rbar);
      }
      if (wg == 1) named_bar(7, 256);
      gemm2_part<72, KPRE, 4 * LAG>(ck, sb, pitch, wg);
      uint32_t rp[18];
      mbar_wait_u(bars + B_ZFULL + 8, 0);
      const uint32_t zl0 = lds32(za + 8192), zl1 = lds32((za ^ 16) + 8192 + 128);
      mbar_wait(bars + B_RFULL + wg * 8, 0);
#pragma unroll
      for (int m = 0; m < 4; m++) {
        const uint4 v = lds128(rbuf + m * 512 + lane * 16);
        rp[4 * m] = v.x; rp[4 * m + 1] = v.y; rp[4 * m + 2] = v.z; rp[4 * m + 3] = v.w;
      }
      { const uint2 v = lds64(rbuf + 2048 + lane * 8); rp[16] = v.x; rp[17] = v.y; }
      sg[0][8] = hmul2(sg[0][8], __byte_perm(zl0, zl1, 0x5410)); sg[1][8] = hmul2(sg[1][8], __byte_perm(zl0, zl1, 0x7632));
      __nv_bfloat16* o = out + go;
      wg_wait<0>();
      float h[2][4], t[2][4], half = 0.25f;
#pragma unroll
      for (int j = 0; j <= 9; j++) {
        if (j < 9) {
          const uint32_t ra = rp[2 * j], rb = rp[2 * j + 1];
          if (j >= 2) half = fmaf(t[j & 1][3], 0.f, 0.25f);
          h[j & 1][0] = fmaf(ck[4 * j], half, bf_lo(ra)); h[j & 1][1] = fmaf(ck[4 * j + 1], half, bf_hi(ra));
          h[j & 1][2] = fmaf(ck[4 * j + 2], half, bf_lo(rb)); h[j & 1][3] = fmaf(ck[4 * j + 3], half, bf_hi(rb));
#pragma unroll
          for (int u = 0; u < 4; u++) t[j & 1][u] = tanh_ordered(h[j & 1][u]);
        }
        if (j > 0) {
          const int k = j - 1;
          const float* hh = h[k & 1];
          const float* tt = t[k & 1];
          x[0][k] = hfma2(sg[0][k], pack_bf16(fmaf(hh[0], tt[0], hh[0]), fmaf(hh[1], tt[1], hh[1])), x[0][k]);
          x[1][k] = hfma2(sg[1][k], pack_bf16(fmaf(hh[2], tt[2], hh[2]), fmaf(hh[3], tt[3], hh[3])), x[1][k]);
          if ((k & 3) == 3) {
            *(uint4*)(o + (k >> 2) * 32) = make_uint4(x[0][k - 3], x[0][k - 2], x[0][k - 1], x[0][k]);
            *(uint4*)(o + 8 * D_ + (k >> 2) * 32) = make_uint4(x[1][k - 3], x[1][k - 2], x[1][k - 1], x[1][k]);
          }
        }
      }
      *(uint32_t*)(out + go8) = x[0][8];
      *(uint32_t*)(out + go8 + 8 * D_) = x[1][8];
    }
  }
}

typedef CUresult (*EncodeFn)(CUtensorMap*, CUtensorMapDataType, cuuint32_t, void*, const cuuint64_t*, const cuuint64_t*, const cuuint32_t*,
                             const cuuint32_t*, CUtensorMapInterleave, CUtensorMapSwizzle, CUtensorMapL2promotion, CUtensorMapFloatOOBfill);

uint32_t role_of_pair(int t) {
  int grp, i;
  if (t < 32) { const int j = t & 7; i = t >> 3; grp = j < 6 ? 1 + j : 12 + 2 * (j - 6); }
  else if (t < 60) { const int j = (t - 32) % 7; i = (t - 32) / 7; grp = j < 5 ? 7 + j : 13 + 2 * (j - 5); }
  else if (t < 62) return 2u | (uint32_t)(t - 60) << 2 | (uint32_t)(14 + 3 * (t - 60)) << 8 | 2u << 16;
  else { grp = 0; i = t - 62; }
  if (grp < 12) return (uint32_t)(i << 2 | grp << 4 | grp << 8 | i << 16);
  const int u = (grp & 1) * 4 + i;
  return (uint32_t)(1 | i << 2 | grp << 4 | (12 + 3 * ((grp - 12) >> 1) + u / 3) << 8 | (u % 3) << 16);
}

}

extern "C" void kernel_launch(void* const* d_in, const int* in_sizes, int n_in, void* d_out, int out_size) {
  (void)in_sizes; (void)n_in; (void)out_size;
  EncodeFn enc = nullptr;
  cudaDriverEntryPointQueryResult qr;
  cudaGetDriverEntryPoint("cuTensorMapEncodeTiled", (void**)&enc, cudaEnableDefault, &qr);
  Scratch* gs = nullptr;
  cudaGetSymbolAddress((void**)&gs, g_scratch);
  void *zp = gs->z, *hp = gs->h, *kvp = gs->kv;
  Maps tm;
  for (int w = 0; w < 2; w++) {
    cuuint64_t gd[2] = {D_, S_};
    cuuint64_t st[1] = {D_ * 2};
    cuuint32_t bx[2] = {64, w ? 33u : 36u};
    cuuint32_t es[2] = {1, 1};
    enc(w ? &tm.m[M_V] : &tm.m[M_K], CU_TENSOR_MAP_DATA_TYPE_BFLOAT16, 2, d_in[1 + w], gd, st, bx, es, CU_TENSOR_MAP_INTERLEAVE_NONE, CU_TENSOR_MAP_SWIZZLE_NONE,
        CU_TENSOR_MAP_L2_PROMOTION_L2_128B, CU_TENSOR_MAP_FLOAT_OOB_FILL_NONE);
  }
  {
    cuuint64_t gd[4] = {16, D_ / 2, 2, 128};
    cuuint64_t st[3] = {2 * KVT, KVT, 64};
    cuuint32_t bx[4] = {20, 32, 2, 1};
    cuuint32_t es[4] = {1, 1, 1, 1};
    enc(&tm.m[M_KV], CU_TENSOR_MAP_DATA_TYPE_UINT32, 4, kvp, gd, st, bx, es, CU_TENSOR_MAP_INTERLEAVE_NONE, CU_TENSOR_MAP_SWIZZLE_NONE,
        CU_TENSOR_MAP_L2_PROMOTION_NONE, CU_TENSOR_MAP_FLOAT_OOB_FILL_NONE);
  }
  {
    cuuint64_t gd[3] = {40, 64, D_};
    cuuint64_t st[2] = {128, KVT};
    cuuint32_t bx[3] = {40, 16, 1};
    cuuint32_t es[3] = {1, 1, 1};
    enc(&tm.m[M_KL], CU_TENSOR_MAP_DATA_TYPE_UINT32, 3, (uint8_t*)kvp - 32, gd, st, bx, es, CU_TENSOR_MAP_INTERLEAVE_NONE, CU_TENSOR_MAP_SWIZZLE_NONE,
        CU_TENSOR_MAP_L2_PROMOTION_NONE, CU_TENSOR_MAP_FLOAT_OOB_FILL_NONE);
  }
  {
    cuuint64_t gd[3] = {64, 32 * 72, 8};
    cuuint64_t st[2] = {1024, 128};
    cuuint32_t bx[3] = {64, 72, 1};
    cuuint32_t es[3] = {1, 1, 1};
    enc(&tm.m[M_H], CU_TENSOR_MAP_DATA_TYPE_BFLOAT16, 3, hp, gd, st, bx, es, CU_TENSOR_MAP_INTERLEAVE_NONE, CU_TENSOR_MAP_SWIZZLE_128B,
        CU_TENSOR_MAP_L2_PROMOTION_NONE, CU_TENSOR_MAP_FLOAT_OOB_FILL_NONE);
  }
  for (int w = 0; w < 2; w++) {
    const cuuint64_t M = w ? S_ : F_, K = w ? F_ : S_;
    cuuint64_t gd[3] = {64, K, M / 64};
    cuuint64_t st[2] = {M * 2, 128};
    cuuint32_t bx[3] = {64, 64, 2};
    cuuint32_t es[3] = {1, 1, 1};
    enc(w ? &tm.m[M_W2] : &tm.m[M_W1], CU_TENSOR_MAP_DATA_TYPE_BFLOAT16, 3, d_in[w ? 9 : 7], gd, st, bx, es, CU_TENSOR_MAP_INTERLEAVE_NONE,
        CU_TENSOR_MAP_SWIZZLE_128B, CU_TENSOR_MAP_L2_PROMOTION_L2_256B, CU_TENSOR_MAP_FLOAT_OOB_FILL_NONE);
  }
  {
    cuuint64_t gd[2] = {S_, D_};
    cuuint64_t st[1] = {S_ * 2};
    cuuint32_t bx[2] = {64, 8};
    cuuint32_t es[2] = {1, 1};
    enc(&tm.m[M_Z], CU_TENSOR_MAP_DATA_TYPE_BFLOAT16, 2, zp, gd, st, bx, es, CU_TENSOR_MAP_INTERLEAVE_NONE, CU_TENSOR_MAP_SWIZZLE_128B,
        CU_TENSOR_MAP_L2_PROMOTION_L2_256B, CU_TENSOR_MAP_FLOAT_OOB_FILL_NONE);
  }
  RoleMap roles;
  int dev = 0, sms = 0;
  cudaGetDevice(&dev);
  cudaDeviceGetAttribute(&sms, cudaDevAttrMultiProcessorCount, dev);
  roles.by_sm = sms == NCTA;
  for (int k = 0; k < NCTA / 2; k++) roles.role[k] = role_of_pair(k);
  cudaFuncSetAttribute(fused_kernel, cudaFuncAttributeMaxDynamicSharedMemorySize, SMEM_BYTES);
  fused_kernel<<<NCTA, 384, SMEM_BYTES>>>((const __nv_bfloat16*)d_in[0], gs, (const __nv_bfloat16*)d_in[8], (const __nv_bfloat16*)d_in[3],
                                          (const __nv_bfloat16*)d_in[4], (const __nv_bfloat16*)d_in[5], tm,
                                          roles, (const __nv_bfloat16*)d_in[10], (__nv_bfloat16*)d_out);
}
```
